```python
import torch

def _softmax(x, axis=-1):
    return torch.softmax(x, dim=axis)
def _gelu(x):
    return torch.nn.functional.gelu(x, approximate="tanh")
def _silu(x):
    return torch.nn.functional.silu(x)
def _sigmoid(x):
    return torch.sigmoid(x)
def _layernorm(x, axis=-1, eps=1e-5):
    m = x.mean(dim=axis, keepdim=True)
    v = x.var(dim=axis, keepdim=True, unbiased=False)
    return (x - m) / torch.sqrt(v + eps)
def _scatter_add(tgt, idx, src, axis=0):
    return tgt.clone().index_add_(axis, idx, src)
def _segment_sum(src, seg, n):
    out = torch.zeros((n,) + src.shape[1:], dtype=src.dtype)
    return out.index_add_(0, seg, src)
def _pad(x, pw):
    flat = tuple(v for pair in reversed(pw) for v in pair)
    return torch.nn.functional.pad(x, flat)

kernel_name = 'sequential_preLN__ssm_conv_h3__dense_activation_squared_relu__prompt'

def setup_inputs():

    _w = (lambda a: (lambda t: t.to(torch.bfloat16) if t.is_floating_point() else t)(torch.as_tensor(a)))
    def _A_setup():
        B, S, D = 1, 2048, 1024
        ks = 4
        return {
            "q": _w((lambda *s: torch.randn(*s, dtype=torch.bfloat16) * 0.05)(B, S, D)),
            "k": _w((lambda *s: torch.randn(*s, dtype=torch.bfloat16) * 0.4)(B, S, D)),
            "v": _w((lambda *s: torch.randn(*s, dtype=torch.bfloat16) * 0.4)(B, S, D)),
            "shift_k": _w((lambda *s: torch.randn(*s, dtype=torch.bfloat16) * 0.4)(D, ks) * 0.5),
            "ssm_k": _w((lambda *s: torch.randn(*s, dtype=torch.bfloat16) * 0.4)(D, S) * (1.0 / S ** 0.5)),
            "ssm_D": _w((lambda *s: torch.randn(*s, dtype=torch.bfloat16) * 0.4)(D)),
        }
    _A_in = _A_setup()

    def _B_setup():
        B, S, D, F = 1, 2048, 1024, 3584
        return {
            "x": _w((lambda *s: torch.randn(*s, dtype=torch.bfloat16) * 0.05)(B, S, D)),
            "w1": _w((lambda *s: torch.randn(*s, dtype=torch.bfloat16) * 0.05)(D, F)),
            "b1": _w((lambda *s: torch.randn(*s, dtype=torch.bfloat16) * 0.4)(F)),
            "w2": _w((lambda *s: torch.randn(*s, dtype=torch.bfloat16) * 0.05)(F, D)),
            "b2": _w((lambda *s: torch.randn(*s, dtype=torch.bfloat16) * 3.2)(D)),
        }
    _B_in = _B_setup()

    return {
        "A_q": _A_in["q"],
        "A_k": _A_in["k"],
        "A_v": _A_in["v"],
        "A_shift_k": _A_in["shift_k"],
        "A_ssm_k": _A_in["ssm_k"],
        "A_ssm_D": _A_in["ssm_D"],
        "B_x": _B_in["x"],
        "B_w1": _B_in["w1"],
        "B_b1": _B_in["b1"],
        "B_w2": _B_in["w2"],
        "B_b2": _B_in["b2"],
    }

def reference(A_q, A_k, A_v, A_shift_k, A_ssm_k, A_ssm_D, B_x, B_w1, B_b1, B_w2, B_b2):
    def _A_ref(q, k, v, shift_k, ssm_k, ssm_D):
        B, S, D = q.shape
        ks = shift_k.shape[-1]
        k_pad = _pad(k, ((0, 0), (ks - 1, 0), (0, 0)))
        k_shift = torch.zeros_like(k)
        for t in range(ks):
            k_shift = k_shift + k_pad[:, t:t + S, :] * shift_k[:, ks - 1 - t][None, None, :]
        kv = k_shift * v
        L = 2 * S
        kv_pad = _pad(kv, ((0, 0), (0, S), (0, 0)))
        kf_pad = _pad(ssm_k, ((0, 0), (0, S)))
        kv_f = (lambda x, axes=(-2,-1): torch.fft.rfft2(x.float(), dim=axes))(kv_pad[:, None, :, :], axes=(1, 2))
        kf_f = (lambda x, axes=(-2,-1): torch.fft.rfft2(x.float(), dim=axes))(kf_pad[:, None, :], axes=(1, 2))
        kf_f = (lambda x, *d: x.permute(*d))(kf_f, 1, 2, 0)
        y_f = kv_f * kf_f[None, :, :, :]
        y = (lambda x, s, axes=(-2,-1): torch.fft.irfft2(x, s=s, dim=axes).to(torch.bfloat16))(y_f, (1, L), axes=(1, 2))[:, 0, :S, :]
        y = y + kv * ssm_D[None, None, :]
        return q * y

    def _B_ref(x, w1, b1, w2, b2):
        h = torch.einsum("bsd,df->bsf", x, w1) + b1
        zero = torch.zeros_like(h)
        r = torch.where(h > zero, h, zero)
        h = r * r
        out = torch.einsum("bsf,fd->bsd", h, w2) + b2
        return out

    x = A_q
    h = x + _A_ref(_layernorm(x, axis=-1), A_k, A_v, A_shift_k, A_ssm_k, A_ssm_D)
    h2 = h + _B_ref(_layernorm(h, axis=-1), B_w1, B_b1, B_w2, B_b2)
    return h2
```

```cpp
#include <cuda_runtime.h>
#include <cuda_bf16.h>
#include <cuda.h>
#include <stdint.h>

#define DBG_TS 0

namespace {

constexpr int S = 2048, D = 1024, F = 3584;
constexpr int NCTA = 128, NTHREADS = 384;

constexpr int UT_COPY = 1040 * 4;
constexpr int UT_SIZE = 2 * UT_COPY;
constexpr int KT_SIZE = 16 + 4096;
constexpr int T_SIZE = 2 * (UT_SIZE + KT_SIZE);
constexpr int KV_STAGE = 33 * 8 * 16;
constexpr int KV_SIZE = 8 * KV_STAGE;
constexpr int YW = 4096 + 96;
constexpr int YBUF = 4 * YW;
constexpr int OFF_T3 = 196608 - T_SIZE;
constexpr int OFF_KVB = (OFF_T3 - KV_SIZE) & ~127;
constexpr int OFF_T2 = OFF_KVB - T_SIZE;
constexpr int OFF_KVA = (OFF_T2 - KV_SIZE) & ~127;
constexpr int OFF_T1 = OFF_KVA - T_SIZE;
constexpr int OFF_T0 = OFF_T1 - T_SIZE;
constexpr int OFF_X = 196608;
constexpr int OFF_CSB2 = OFF_X + 32768;
constexpr int OFF_RED = OFF_X + 34304;
constexpr int OFF_XS = OFF_X + 34688;
constexpr int OFF_BAR = OFF_X + 34816;
constexpr int SMEM_BYTES = 232448;
static_assert(OFF_T0 >= 0 && 2 * YBUF <= KV_SIZE && 2 * YBUF <= 34304, "smem map");
static_assert(OFF_T2 >= 98304, "stage 1 must only overlap T0,T1,KVA");
static_assert(OFF_T3 >= 147456, "stage 2 must not overlap T3");

enum {
  B_KVFULL = 0, B_KFULL = 8, B_UFULL = 16, B_YFULL = 24, B_ZDONE = 28, B_FULL1 = 32, B_EMPTY1 = 36,
  B_FULL2 = 40, B_EMPTY2 = 46, B_CSFULL = 52, B_HRES = 53, B_ADONE = 54, B_HDONE = 56, B_CDONE = 60, B_XDONE = 61, B_COUNT = 62
};

struct Params {
  CUtensorMap tm_k, tm_v, tm_h, tm_w1, tm_act, tm_w2, tm_hres, tm_out;
  const __nv_bfloat16 *x, *shift_k, *ssm_k, *ssm_D, *w1, *b1, *w2, *b2;
};

__device__ __align__(1024) uint32_t g_z[4 * NCTA * S];
__device__ __align__(1024) __nv_bfloat16 g_h[S * D];
__device__ __align__(1024) __nv_bfloat16 g_act[S * F];
__device__ __align__(128) float2 g_hstat[S];
__device__ __align__(128) float g_cs[F];
__device__ __align__(128) uint32_t g_zflag[4 * NCTA];
__device__ __align__(128) uint32_t g_hflag[4 * NCTA];
__device__ __align__(128) uint32_t g_aflag[2 * NCTA];
__device__ __align__(128) uint32_t g_cflag[NCTA];
#define TS(slot) do {} while (0)

template<int N> __device__ __forceinline__ void wgmma_rs(float* d, const uint32_t* a, uint64_t db, int sc);
template<int N> __device__ __forceinline__ void wgmma_ss(float* d, uint64_t da, uint64_t db, int sc);
template<> __device__ __forceinline__ void wgmma_rs<16>(float* d, const uint32_t* a, uint64_t db, int sc) {
  asm volatile("{.reg .pred p; setp.ne.b32 p, %13, 0;\n"
  "wgmma.mma_async.sync.aligned.m64n16k16.f32.bf16.bf16 {%0,%1,%2,%3,%4,%5,%6,%7}, {%8,%9,%10,%11}, %12, p, 1, 1, 0;}\n"
  : "+f"(d[0]),"+f"(d[1]),"+f"(d[2]),"+f"(d[3]),"+f"(d[4]),"+f"(d[5]),"+f"(d[6]),"+f"(d[7])
  : "r"(a[0]), "r"(a[1]), "r"(a[2]), "r"(a[3]), "l"(db), "r"(sc));
}
template<> __device__ __forceinline__ void wgmma_rs<32>(float* d, const uint32_t* a, uint64_t db, int sc) {
  asm volatile("{.reg .pred p; setp.ne.b32 p, %21, 0;\n"
  "wgmma.mma_async.sync.aligned.m64n32k16.f32.bf16.bf16 {%0,%1,%2,%3,%4,%5,%6,%7,%8,%9,%10,%11,%12,%13,%14,%15}, {%16,%17,%18,%19}, %20, p, 1, 1, 0;}\n"
  : "+f"(d[0]),"+f"(d[1]),"+f"(d[2]),"+f"(d[3]),"+f"(d[4]),"+f"(d[5]),"+f"(d[6]),"+f"(d[7]),"+f"(d[8]),"+f"(d[9]),"+f"(d[10]),"+f"(d[11]),"+f"(d[12]),"+f"(d[13]),"+f"(d[14]),"+f"(d[15])
  : "r"(a[0]), "r"(a[1]), "r"(a[2]), "r"(a[3]), "l"(db), "r"(sc));
}
template<> __device__ __forceinline__ void wgmma_rs<48>(float* d, const uint32_t* a, uint64_t db, int sc) {
  asm volatile("{.reg .pred p; setp.ne.b32 p, %29, 0;\n"
  "wgmma.mma_async.sync.aligned.m64n48k16.f32.bf16.bf16 {%0,%1,%2,%3,%4,%5,%6,%7,%8,%9,%10,%11,%12,%13,%14,%15,%16,%17,%18,%19,%20,%21,%22,%23}, {%24,%25,%26,%27}, %28, p, 1, 1, 0;}\n"
  : "+f"(d[0]),"+f"(d[1]),"+f"(d[2]),"+f"(d[3]),"+f"(d[4]),"+f"(d[5]),"+f"(d[6]),"+f"(d[7]),"+f"(d[8]),"+f"(d[9]),"+f"(d[10]),"+f"(d[11]),"+f"(d[12]),"+f"(d[13]),"+f"(d[14]),"+f"(d[15]),"+f"(d[16]),"+f"(d[17]),"+f"(d[18]),"+f"(d[19]),"+f"(d[20]),"+f"(d[21]),"+f"(d[22]),"+f"(d[23])
  : "r"(a[0]), "r"(a[1]), "r"(a[2]), "r"(a[3]), "l"(db), "r"(sc));
}
template<> __device__ __forceinline__ void wgmma_rs<64>(float* d, const uint32_t* a, uint64_t db, int sc) {
  asm volatile("{.reg .pred p; setp.ne.b32 p, %37, 0;\n"
  "wgmma.mma_async.sync.aligned.m64n64k16.f32.bf16.bf16 {%0,%1,%2,%3,%4,%5,%6,%7,%8,%9,%10,%11,%12,%13,%14,%15,%16,%17,%18,%19,%20,%21,%22,%23,%24,%25,%26,%27,%28,%29,%30,%31}, {%32,%33,%34,%35}, %36, p, 1, 1, 0;}\n"
  : "+f"(d[0]),"+f"(d[1]),"+f"(d[2]),"+f"(d[3]),"+f"(d[4]),"+f"(d[5]),"+f"(d[6]),"+f"(d[7]),"+f"(d[8]),"+f"(d[9]),"+f"(d[10]),"+f"(d[11]),"+f"(d[12]),"+f"(d[13]),"+f"(d[14]),"+f"(d[15]),"+f"(d[16]),"+f"(d[17]),"+f"(d[18]),"+f"(d[19]),"+f"(d[20]),"+f"(d[21]),"+f"(d[22]),"+f"(d[23]),"+f"(d[24]),"+f"(d[25]),"+f"(d[26]),"+f"(d[27]),"+f"(d[28]),"+f"(d[29]),"+f"(d[30]),"+f"(d[31])
  : "r"(a[0]), "r"(a[1]), "r"(a[2]), "r"(a[3]), "l"(db), "r"(sc));
}
template<> __device__ __forceinline__ void wgmma_rs<80>(float* d, const uint32_t* a, uint64_t db, int sc) {
  asm volatile("{.reg .pred p; setp.ne.b32 p, %45, 0;\n"
  "wgmma.mma_async.sync.aligned.m64n80k16.f32.bf16.bf16 {%0,%1,%2,%3,%4,%5,%6,%7,%8,%9,%10,%11,%12,%13,%14,%15,%16,%17,%18,%19,%20,%21,%22,%23,%24,%25,%26,%27,%28,%29,%30,%31,%32,%33,%34,%35,%36,%37,%38,%39}, {%40,%41,%42,%43}, %44, p, 1, 1, 0;}\n"
  : "+f"(d[0]),"+f"(d[1]),"+f"(d[2]),"+f"(d[3]),"+f"(d[4]),"+f"(d[5]),"+f"(d[6]),"+f"(d[7]),"+f"(d[8]),"+f"(d[9]),"+f"(d[10]),"+f"(d[11]),"+f"(d[12]),"+f"(d[13]),"+f"(d[14]),"+f"(d[15]),"+f"(d[16]),"+f"(d[17]),"+f"(d[18]),"+f"(d[19]),"+f"(d[20]),"+f"(d[21]),"+f"(d[22]),"+f"(d[23]),"+f"(d[24]),"+f"(d[25]),"+f"(d[26]),"+f"(d[27]),"+f"(d[28]),"+f"(d[29]),"+f"(d[30]),"+f"(d[31]),"+f"(d[32]),"+f"(d[33]),"+f"(d[34]),"+f"(d[35]),"+f"(d[36]),"+f"(d[37]),"+f"(d[38]),"+f"(d[39])
  : "r"(a[0]), "r"(a[1]), "r"(a[2]), "r"(a[3]), "l"(db), "r"(sc));
}
template<> __device__ __forceinline__ void wgmma_rs<96>(float* d, const uint32_t* a, uint64_t db, int sc) {
  asm volatile("{.reg .pred p; setp.ne.b32 p, %53, 0;\n"
  "wgmma.mma_async.sync.aligned.m64n96k16.f32.bf16.bf16 {%0,%1,%2,%3,%4,%5,%6,%7,%8,%9,%10,%11,%12,%13,%14,%15,%16,%17,%18,%19,%20,%21,%22,%23,%24,%25,%26,%27,%28,%29,%30,%31,%32,%33,%34,%35,%36,%37,%38,%39,%40,%41,%42,%43,%44,%45,%46,%47}, {%48,%49,%50,%51}, %52, p, 1, 1, 0;}\n"
  : "+f"(d[0]),"+f"(d[1]),"+f"(d[2]),"+f"(d[3]),"+f"(d[4]),"+f"(d[5]),"+f"(d[6]),"+f"(d[7]),"+f"(d[8]),"+f"(d[9]),"+f"(d[10]),"+f"(d[11]),"+f"(d[12]),"+f"(d[13]),"+f"(d[14]),"+f"(d[15]),"+f"(d[16]),"+f"(d[17]),"+f"(d[18]),"+f"(d[19]),"+f"(d[20]),"+f"(d[21]),"+f"(d[22]),"+f"(d[23]),"+f"(d[24]),"+f"(d[25]),"+f"(d[26]),"+f"(d[27]),"+f"(d[28]),"+f"(d[29]),"+f"(d[30]),"+f"(d[31]),"+f"(d[32]),"+f"(d[33]),"+f"(d[34]),"+f"(d[35]),"+f"(d[36]),"+f"(d[37]),"+f"(d[38]),"+f"(d[39]),"+f"(d[40]),"+f"(d[41]),"+f"(d[42]),"+f"(d[43]),"+f"(d[44]),"+f"(d[45]),"+f"(d[46]),"+f"(d[47])
  : "r"(a[0]), "r"(a[1]), "r"(a[2]), "r"(a[3]), "l"(db), "r"(sc));
}
template<> __device__ __forceinline__ void wgmma_rs<112>(float* d, const uint32_t* a, uint64_t db, int sc) {
  asm volatile("{.reg .pred p; setp.ne.b32 p, %61, 0;\n"
  "wgmma.mma_async.sync.aligned.m64n112k16.f32.bf16.bf16 {%0,%1,%2,%3,%4,%5,%6,%7,%8,%9,%10,%11,%12,%13,%14,%15,%16,%17,%18,%19,%20,%21,%22,%23,%24,%25,%26,%27,%28,%29,%30,%31,%32,%33,%34,%35,%36,%37,%38,%39,%40,%41,%42,%43,%44,%45,%46,%47,%48,%49,%50,%51,%52,%53,%54,%55}, {%56,%57,%58,%59}, %60, p, 1, 1, 0;}\n"
  : "+f"(d[0]),"+f"(d[1]),"+f"(d[2]),"+f"(d[3]),"+f"(d[4]),"+f"(d[5]),"+f"(d[6]),"+f"(d[7]),"+f"(d[8]),"+f"(d[9]),"+f"(d[10]),"+f"(d[11]),"+f"(d[12]),"+f"(d[13]),"+f"(d[14]),"+f"(d[15]),"+f"(d[16]),"+f"(d[17]),"+f"(d[18]),"+f"(d[19]),"+f"(d[20]),"+f"(d[21]),"+f"(d[22]),"+f"(d[23]),"+f"(d[24]),"+f"(d[25]),"+f"(d[26]),"+f"(d[27]),"+f"(d[28]),"+f"(d[29]),"+f"(d[30]),"+f"(d[31]),"+f"(d[32]),"+f"(d[33]),"+f"(d[34]),"+f"(d[35]),"+f"(d[36]),"+f"(d[37]),"+f"(d[38]),"+f"(d[39]),"+f"(d[40]),"+f"(d[41]),"+f"(d[42]),"+f"(d[43]),"+f"(d[44]),"+f"(d[45]),"+f"(d[46]),"+f"(d[47]),"+f"(d[48]),"+f"(d[49]),"+f"(d[50]),"+f"(d[51]),"+f"(d[52]),"+f"(d[53]),"+f"(d[54]),"+f"(d[55])
  : "r"(a[0]), "r"(a[1]), "r"(a[2]), "r"(a[3]), "l"(db), "r"(sc));
}
template<> __device__ __forceinline__ void wgmma_rs<128>(float* d, const uint32_t* a, uint64_t db, int sc) {
  asm volatile("{.reg .pred p; setp.ne.b32 p, %69, 0;\n"
  "wgmma.mma_async.sync.aligned.m64n128k16.f32.bf16.bf16 {%0,%1,%2,%3,%4,%5,%6,%7,%8,%9,%10,%11,%12,%13,%14,%15,%16,%17,%18,%19,%20,%21,%22,%23,%24,%25,%26,%27,%28,%29,%30,%31,%32,%33,%34,%35,%36,%37,%38,%39,%40,%41,%42,%43,%44,%45,%46,%47,%48,%49,%50,%51,%52,%53,%54,%55,%56,%57,%58,%59,%60,%61,%62,%63}, {%64,%65,%66,%67}, %68, p, 1, 1, 0;}\n"
  : "+f"(d[0]),"+f"(d[1]),"+f"(d[2]),"+f"(d[3]),"+f"(d[4]),"+f"(d[5]),"+f"(d[6]),"+f"(d[7]),"+f"(d[8]),"+f"(d[9]),"+f"(d[10]),"+f"(d[11]),"+f"(d[12]),"+f"(d[13]),"+f"(d[14]),"+f"(d[15]),"+f"(d[16]),"+f"(d[17]),"+f"(d[18]),"+f"(d[19]),"+f"(d[20]),"+f"(d[21]),"+f"(d[22]),"+f"(d[23]),"+f"(d[24]),"+f"(d[25]),"+f"(d[26]),"+f"(d[27]),"+f"(d[28]),"+f"(d[29]),"+f"(d[30]),"+f"(d[31]),"+f"(d[32]),"+f"(d[33]),"+f"(d[34]),"+f"(d[35]),"+f"(d[36]),"+f"(d[37]),"+f"(d[38]),"+f"(d[39]),"+f"(d[40]),"+f"(d[41]),"+f"(d[42]),"+f"(d[43]),"+f"(d[44]),"+f"(d[45]),"+f"(d[46]),"+f"(d[47]),"+f"(d[48]),"+f"(d[49]),"+f"(d[50]),"+f"(d[51]),"+f"(d[52]),"+f"(d[53]),"+f"(d[54]),"+f"(d[55]),"+f"(d[56]),"+f"(d[57]),"+f"(d[58]),"+f"(d[59]),"+f"(d[60]),"+f"(d[61]),"+f"(d[62]),"+f"(d[63])
  : "r"(a[0]), "r"(a[1]), "r"(a[2]), "r"(a[3]), "l"(db), "r"(sc));
}
template<> __device__ __forceinline__ void wgmma_rs<144>(float* d, const uint32_t* a, uint64_t db, int sc) {
  asm volatile("{.reg .pred p; setp.ne.b32 p, %77, 0;\n"
  "wgmma.mma_async.sync.aligned.m64n144k16.f32.bf16.bf16 {%0,%1,%2,%3,%4,%5,%6,%7,%8,%9,%10,%11,%12,%13,%14,%15,%16,%17,%18,%19,%20,%21,%22,%23,%24,%25,%26,%27,%28,%29,%30,%31,%32,%33,%34,%35,%36,%37,%38,%39,%40,%41,%42,%43,%44,%45,%46,%47,%48,%49,%50,%51,%52,%53,%54,%55,%56,%57,%58,%59,%60,%61,%62,%63,%64,%65,%66,%67,%68,%69,%70,%71}, {%72,%73,%74,%75}, %76, p, 1, 1, 0;}\n"
  : "+f"(d[0]),"+f"(d[1]),"+f"(d[2]),"+f"(d[3]),"+f"(d[4]),"+f"(d[5]),"+f"(d[6]),"+f"(d[7]),"+f"(d[8]),"+f"(d[9]),"+f"(d[10]),"+f"(d[11]),"+f"(d[12]),"+f"(d[13]),"+f"(d[14]),"+f"(d[15]),"+f"(d[16]),"+f"(d[17]),"+f"(d[18]),"+f"(d[19]),"+f"(d[20]),"+f"(d[21]),"+f"(d[22]),"+f"(d[23]),"+f"(d[24]),"+f"(d[25]),"+f"(d[26]),"+f"(d[27]),"+f"(d[28]),"+f"(d[29]),"+f"(d[30]),"+f"(d[31]),"+f"(d[32]),"+f"(d[33]),"+f"(d[34]),"+f"(d[35]),"+f"(d[36]),"+f"(d[37]),"+f"(d[38]),"+f"(d[39]),"+f"(d[40]),"+f"(d[41]),"+f"(d[42]),"+f"(d[43]),"+f"(d[44]),"+f"(d[45]),"+f"(d[46]),"+f"(d[47]),"+f"(d[48]),"+f"(d[49]),"+f"(d[50]),"+f"(d[51]),"+f"(d[52]),"+f"(d[53]),"+f"(d[54]),"+f"(d[55]),"+f"(d[56]),"+f"(d[57]),"+f"(d[58]),"+f"(d[59]),"+f"(d[60]),"+f"(d[61]),"+f"(d[62]),"+f"(d[63]),"+f"(d[64]),"+f"(d[65]),"+f"(d[66]),"+f"(d[67]),"+f"(d[68]),"+f"(d[69]),"+f"(d[70]),"+f"(d[71])
  : "r"(a[0]), "r"(a[1]), "r"(a[2]), "r"(a[3]), "l"(db), "r"(sc));
}
template<> __device__ __forceinline__ void wgmma_rs<160>(float* d, const uint32_t* a, uint64_t db, int sc) {
  asm volatile("{.reg .pred p; setp.ne.b32 p, %85, 0;\n"
  "wgmma.mma_async.sync.aligned.m64n160k16.f32.bf16.bf16 {%0,%1,%2,%3,%4,%5,%6,%7,%8,%9,%10,%11,%12,%13,%14,%15,%16,%17,%18,%19,%20,%21,%22,%23,%24,%25,%26,%27,%28,%29,%30,%31,%32,%33,%34,%35,%36,%37,%38,%39,%40,%41,%42,%43,%44,%45,%46,%47,%48,%49,%50,%51,%52,%53,%54,%55,%56,%57,%58,%59,%60,%61,%62,%63,%64,%65,%66,%67,%68,%69,%70,%71,%72,%73,%74,%75,%76,%77,%78,%79}, {%80,%81,%82,%83}, %84, p, 1, 1, 0;}\n"
  : "+f"(d[0]),"+f"(d[1]),"+f"(d[2]),"+f"(d[3]),"+f"(d[4]),"+f"(d[5]),"+f"(d[6]),"+f"(d[7]),"+f"(d[8]),"+f"(d[9]),"+f"(d[10]),"+f"(d[11]),"+f"(d[12]),"+f"(d[13]),"+f"(d[14]),"+f"(d[15]),"+f"(d[16]),"+f"(d[17]),"+f"(d[18]),"+f"(d[19]),"+f"(d[20]),"+f"(d[21]),"+f"(d[22]),"+f"(d[23]),"+f"(d[24]),"+f"(d[25]),"+f"(d[26]),"+f"(d[27]),"+f"(d[28]),"+f"(d[29]),"+f"(d[30]),"+f"(d[31]),"+f"(d[32]),"+f"(d[33]),"+f"(d[34]),"+f"(d[35]),"+f"(d[36]),"+f"(d[37]),"+f"(d[38]),"+f"(d[39]),"+f"(d[40]),"+f"(d[41]),"+f"(d[42]),"+f"(d[43]),"+f"(d[44]),"+f"(d[45]),"+f"(d[46]),"+f"(d[47]),"+f"(d[48]),"+f"(d[49]),"+f"(d[50]),"+f"(d[51]),"+f"(d[52]),"+f"(d[53]),"+f"(d[54]),"+f"(d[55]),"+f"(d[56]),"+f"(d[57]),"+f"(d[58]),"+f"(d[59]),"+f"(d[60]),"+f"(d[61]),"+f"(d[62]),"+f"(d[63]),"+f"(d[64]),"+f"(d[65]),"+f"(d[66]),"+f"(d[67]),"+f"(d[68]),"+f"(d[69]),"+f"(d[70]),"+f"(d[71]),"+f"(d[72]),"+f"(d[73]),"+f"(d[74]),"+f"(d[75]),"+f"(d[76]),"+f"(d[77]),"+f"(d[78]),"+f"(d[79])
  : "r"(a[0]), "r"(a[1]), "r"(a[2]), "r"(a[3]), "l"(db), "r"(sc));
}
template<> __device__ __forceinline__ void wgmma_rs<176>(float* d, const uint32_t* a, uint64_t db, int sc) {
  asm volatile("{.reg .pred p; setp.ne.b32 p, %93, 0;\n"
  "wgmma.mma_async.sync.aligned.m64n176k16.f32.bf16.bf16 {%0,%1,%2,%3,%4,%5,%6,%7,%8,%9,%10,%11,%12,%13,%14,%15,%16,%17,%18,%19,%20,%21,%22,%23,%24,%25,%26,%27,%28,%29,%30,%31,%32,%33,%34,%35,%36,%37,%38,%39,%40,%41,%42,%43,%44,%45,%46,%47,%48,%49,%50,%51,%52,%53,%54,%55,%56,%57,%58,%59,%60,%61,%62,%63,%64,%65,%66,%67,%68,%69,%70,%71,%72,%73,%74,%75,%76,%77,%78,%79,%80,%81,%82,%83,%84,%85,%86,%87}, {%88,%89,%90,%91}, %92, p, 1, 1, 0;}\n"
  : "+f"(d[0]),"+f"(d[1]),"+f"(d[2]),"+f"(d[3]),"+f"(d[4]),"+f"(d[5]),"+f"(d[6]),"+f"(d[7]),"+f"(d[8]),"+f"(d[9]),"+f"(d[10]),"+f"(d[11]),"+f"(d[12]),"+f"(d[13]),"+f"(d[14]),"+f"(d[15]),"+f"(d[16]),"+f"(d[17]),"+f"(d[18]),"+f"(d[19]),"+f"(d[20]),"+f"(d[21]),"+f"(d[22]),"+f"(d[23]),"+f"(d[24]),"+f"(d[25]),"+f"(d[26]),"+f"(d[27]),"+f"(d[28]),"+f"(d[29]),"+f"(d[30]),"+f"(d[31]),"+f"(d[32]),"+f"(d[33]),"+f"(d[34]),"+f"(d[35]),"+f"(d[36]),"+f"(d[37]),"+f"(d[38]),"+f"(d[39]),"+f"(d[40]),"+f"(d[41]),"+f"(d[42]),"+f"(d[43]),"+f"(d[44]),"+f"(d[45]),"+f"(d[46]),"+f"(d[47]),"+f"(d[48]),"+f"(d[49]),"+f"(d[50]),"+f"(d[51]),"+f"(d[52]),"+f"(d[53]),"+f"(d[54]),"+f"(d[55]),"+f"(d[56]),"+f"(d[57]),"+f"(d[58]),"+f"(d[59]),"+f"(d[60]),"+f"(d[61]),"+f"(d[62]),"+f"(d[63]),"+f"(d[64]),"+f"(d[65]),"+f"(d[66]),"+f"(d[67]),"+f"(d[68]),"+f"(d[69]),"+f"(d[70]),"+f"(d[71]),"+f"(d[72]),"+f"(d[73]),"+f"(d[74]),"+f"(d[75]),"+f"(d[76]),"+f"(d[77]),"+f"(d[78]),"+f"(d[79]),"+f"(d[80]),"+f"(d[81]),"+f"(d[82]),"+f"(d[83]),"+f"(d[84]),"+f"(d[85]),"+f"(d[86]),"+f"(d[87])
  : "r"(a[0]), "r"(a[1]), "r"(a[2]), "r"(a[3]), "l"(db), "r"(sc));
}
template<> __device__ __forceinline__ void wgmma_rs<192>(float* d, const uint32_t* a, uint64_t db, int sc) {
  asm volatile("{.reg .pred p; setp.ne.b32 p, %101, 0;\n"
  "wgmma.mma_async.sync.aligned.m64n192k16.f32.bf16.bf16 {%0,%1,%2,%3,%4,%5,%6,%7,%8,%9,%10,%11,%12,%13,%14,%15,%16,%17,%18,%19,%20,%21,%22,%23,%24,%25,%26,%27,%28,%29,%30,%31,%32,%33,%34,%35,%36,%37,%38,%39,%40,%41,%42,%43,%44,%45,%46,%47,%48,%49,%50,%51,%52,%53,%54,%55,%56,%57,%58,%59,%60,%61,%62,%63,%64,%65,%66,%67,%68,%69,%70,%71,%72,%73,%74,%75,%76,%77,%78,%79,%80,%81,%82,%83,%84,%85,%86,%87,%88,%89,%90,%91,%92,%93,%94,%95}, {%96,%97,%98,%99}, %100, p, 1, 1, 0;}\n"
  : "+f"(d[0]),"+f"(d[1]),"+f"(d[2]),"+f"(d[3]),"+f"(d[4]),"+f"(d[5]),"+f"(d[6]),"+f"(d[7]),"+f"(d[8]),"+f"(d[9]),"+f"(d[10]),"+f"(d[11]),"+f"(d[12]),"+f"(d[13]),"+f"(d[14]),"+f"(d[15]),"+f"(d[16]),"+f"(d[17]),"+f"(d[18]),"+f"(d[19]),"+f"(d[20]),"+f"(d[21]),"+f"(d[22]),"+f"(d[23]),"+f"(d[24]),"+f"(d[25]),"+f"(d[26]),"+f"(d[27]),"+f"(d[28]),"+f"(d[29]),"+f"(d[30]),"+f"(d[31]),"+f"(d[32]),"+f"(d[33]),"+f"(d[34]),"+f"(d[35]),"+f"(d[36]),"+f"(d[37]),"+f"(d[38]),"+f"(d[39]),"+f"(d[40]),"+f"(d[41]),"+f"(d[42]),"+f"(d[43]),"+f"(d[44]),"+f"(d[45]),"+f"(d[46]),"+f"(d[47]),"+f"(d[48]),"+f"(d[49]),"+f"(d[50]),"+f"(d[51]),"+f"(d[52]),"+f"(d[53]),"+f"(d[54]),"+f"(d[55]),"+f"(d[56]),"+f"(d[57]),"+f"(d[58]),"+f"(d[59]),"+f"(d[60]),"+f"(d[61]),"+f"(d[62]),"+f"(d[63]),"+f"(d[64]),"+f"(d[65]),"+f"(d[66]),"+f"(d[67]),"+f"(d[68]),"+f"(d[69]),"+f"(d[70]),"+f"(d[71]),"+f"(d[72]),"+f"(d[73]),"+f"(d[74]),"+f"(d[75]),"+f"(d[76]),"+f"(d[77]),"+f"(d[78]),"+f"(d[79]),"+f"(d[80]),"+f"(d[81]),"+f"(d[82]),"+f"(d[83]),"+f"(d[84]),"+f"(d[85]),"+f"(d[86]),"+f"(d[87]),"+f"(d[88]),"+f"(d[89]),"+f"(d[90]),"+f"(d[91]),"+f"(d[92]),"+f"(d[93]),"+f"(d[94]),"+f"(d[95])
  : "r"(a[0]), "r"(a[1]), "r"(a[2]), "r"(a[3]), "l"(db), "r"(sc));
}
template<> __device__ __forceinline__ void wgmma_rs<208>(float* d, const uint32_t* a, uint64_t db, int sc) {
  asm volatile("{.reg .pred p; setp.ne.b32 p, %109, 0;\n"
  "wgmma.mma_async.sync.aligned.m64n208k16.f32.bf16.bf16 {%0,%1,%2,%3,%4,%5,%6,%7,%8,%9,%10,%11,%12,%13,%14,%15,%16,%17,%18,%19,%20,%21,%22,%23,%24,%25,%26,%27,%28,%29,%30,%31,%32,%33,%34,%35,%36,%37,%38,%39,%40,%41,%42,%43,%44,%45,%46,%47,%48,%49,%50,%51,%52,%53,%54,%55,%56,%57,%58,%59,%60,%61,%62,%63,%64,%65,%66,%67,%68,%69,%70,%71,%72,%73,%74,%75,%76,%77,%78,%79,%80,%81,%82,%83,%84,%85,%86,%87,%88,%89,%90,%91,%92,%93,%94,%95,%96,%97,%98,%99,%100,%101,%102,%103}, {%104,%105,%106,%107}, %108, p, 1, 1, 0;}\n"
  : "+f"(d[0]),"+f"(d[1]),"+f"(d[2]),"+f"(d[3]),"+f"(d[4]),"+f"(d[5]),"+f"(d[6]),"+f"(d[7]),"+f"(d[8]),"+f"(d[9]),"+f"(d[10]),"+f"(d[11]),"+f"(d[12]),"+f"(d[13]),"+f"(d[14]),"+f"(d[15]),"+f"(d[16]),"+f"(d[17]),"+f"(d[18]),"+f"(d[19]),"+f"(d[20]),"+f"(d[21]),"+f"(d[22]),"+f"(d[23]),"+f"(d[24]),"+f"(d[25]),"+f"(d[26]),"+f"(d[27]),"+f"(d[28]),"+f"(d[29]),"+f"(d[30]),"+f"(d[31]),"+f"(d[32]),"+f"(d[33]),"+f"(d[34]),"+f"(d[35]),"+f"(d[36]),"+f"(d[37]),"+f"(d[38]),"+f"(d[39]),"+f"(d[40]),"+f"(d[41]),"+f"(d[42]),"+f"(d[43]),"+f"(d[44]),"+f"(d[45]),"+f"(d[46]),"+f"(d[47]),"+f"(d[48]),"+f"(d[49]),"+f"(d[50]),"+f"(d[51]),"+f"(d[52]),"+f"(d[53]),"+f"(d[54]),"+f"(d[55]),"+f"(d[56]),"+f"(d[57]),"+f"(d[58]),"+f"(d[59]),"+f"(d[60]),"+f"(d[61]),"+f"(d[62]),"+f"(d[63]),"+f"(d[64]),"+f"(d[65]),"+f"(d[66]),"+f"(d[67]),"+f"(d[68]),"+f"(d[69]),"+f"(d[70]),"+f"(d[71]),"+f"(d[72]),"+f"(d[73]),"+f"(d[74]),"+f"(d[75]),"+f"(d[76]),"+f"(d[77]),"+f"(d[78]),"+f"(d[79]),"+f"(d[80]),"+f"(d[81]),"+f"(d[82]),"+f"(d[83]),"+f"(d[84]),"+f"(d[85]),"+f"(d[86]),"+f"(d[87]),"+f"(d[88]),"+f"(d[89]),"+f"(d[90]),"+f"(d[91]),"+f"(d[92]),"+f"(d[93]),"+f"(d[94]),"+f"(d[95]),"+f"(d[96]),"+f"(d[97]),"+f"(d[98]),"+f"(d[99]),"+f"(d[100]),"+f"(d[101]),"+f"(d[102]),"+f"(d[103])
  : "r"(a[0]), "r"(a[1]), "r"(a[2]), "r"(a[3]), "l"(db), "r"(sc));
}
template<> __device__ __forceinline__ void wgmma_rs<224>(float* d, const uint32_t* a, uint64_t db, int sc) {
  asm volatile("{.reg .pred p; setp.ne.b32 p, %117, 0;\n"
  "wgmma.mma_async.sync.aligned.m64n224k16.f32.bf16.bf16 {%0,%1,%2,%3,%4,%5,%6,%7,%8,%9,%10,%11,%12,%13,%14,%15,%16,%17,%18,%19,%20,%21,%22,%23,%24,%25,%26,%27,%28,%29,%30,%31,%32,%33,%34,%35,%36,%37,%38,%39,%40,%41,%42,%43,%44,%45,%46,%47,%48,%49,%50,%51,%52,%53,%54,%55,%56,%57,%58,%59,%60,%61,%62,%63,%64,%65,%66,%67,%68,%69,%70,%71,%72,%73,%74,%75,%76,%77,%78,%79,%80,%81,%82,%83,%84,%85,%86,%87,%88,%89,%90,%91,%92,%93,%94,%95,%96,%97,%98,%99,%100,%101,%102,%103,%104,%105,%106,%107,%108,%109,%110,%111}, {%112,%113,%114,%115}, %116, p, 1, 1, 0;}\n"
  : "+f"(d[0]),"+f"(d[1]),"+f"(d[2]),"+f"(d[3]),"+f"(d[4]),"+f"(d[5]),"+f"(d[6]),"+f"(d[7]),"+f"(d[8]),"+f"(d[9]),"+f"(d[10]),"+f"(d[11]),"+f"(d[12]),"+f"(d[13]),"+f"(d[14]),"+f"(d[15]),"+f"(d[16]),"+f"(d[17]),"+f"(d[18]),"+f"(d[19]),"+f"(d[20]),"+f"(d[21]),"+f"(d[22]),"+f"(d[23]),"+f"(d[24]),"+f"(d[25]),"+f"(d[26]),"+f"(d[27]),"+f"(d[28]),"+f"(d[29]),"+f"(d[30]),"+f"(d[31]),"+f"(d[32]),"+f"(d[33]),"+f"(d[34]),"+f"(d[35]),"+f"(d[36]),"+f"(d[37]),"+f"(d[38]),"+f"(d[39]),"+f"(d[40]),"+f"(d[41]),"+f"(d[42]),"+f"(d[43]),"+f"(d[44]),"+f"(d[45]),"+f"(d[46]),"+f"(d[47]),"+f"(d[48]),"+f"(d[49]),"+f"(d[50]),"+f"(d[51]),"+f"(d[52]),"+f"(d[53]),"+f"(d[54]),"+f"(d[55]),"+f"(d[56]),"+f"(d[57]),"+f"(d[58]),"+f"(d[59]),"+f"(d[60]),"+f"(d[61]),"+f"(d[62]),"+f"(d[63]),"+f"(d[64]),"+f"(d[65]),"+f"(d[66]),"+f"(d[67]),"+f"(d[68]),"+f"(d[69]),"+f"(d[70]),"+f"(d[71]),"+f"(d[72]),"+f"(d[73]),"+f"(d[74]),"+f"(d[75]),"+f"(d[76]),"+f"(d[77]),"+f"(d[78]),"+f"(d[79]),"+f"(d[80]),"+f"(d[81]),"+f"(d[82]),"+f"(d[83]),"+f"(d[84]),"+f"(d[85]),"+f"(d[86]),"+f"(d[87]),"+f"(d[88]),"+f"(d[89]),"+f"(d[90]),"+f"(d[91]),"+f"(d[92]),"+f"(d[93]),"+f"(d[94]),"+f"(d[95]),"+f"(d[96]),"+f"(d[97]),"+f"(d[98]),"+f"(d[99]),"+f"(d[100]),"+f"(d[101]),"+f"(d[102]),"+f"(d[103]),"+f"(d[104]),"+f"(d[105]),"+f"(d[106]),"+f"(d[107]),"+f"(d[108]),"+f"(d[109]),"+f"(d[110]),"+f"(d[111])
  : "r"(a[0]), "r"(a[1]), "r"(a[2]), "r"(a[3]), "l"(db), "r"(sc));
}
template<> __device__ __forceinline__ void wgmma_rs<240>(float* d, const uint32_t* a, uint64_t db, int sc) {
  asm volatile("{.reg .pred p; setp.ne.b32 p, %125, 0;\n"
  "wgmma.mma_async.sync.aligned.m64n240k16.f32.bf16.bf16 {%0,%1,%2,%3,%4,%5,%6,%7,%8,%9,%10,%11,%12,%13,%14,%15,%16,%17,%18,%19,%20,%21,%22,%23,%24,%25,%26,%27,%28,%29,%30,%31,%32,%33,%34,%35,%36,%37,%38,%39,%40,%41,%42,%43,%44,%45,%46,%47,%48,%49,%50,%51,%52,%53,%54,%55,%56,%57,%58,%59,%60,%61,%62,%63,%64,%65,%66,%67,%68,%69,%70,%71,%72,%73,%74,%75,%76,%77,%78,%79,%80,%81,%82,%83,%84,%85,%86,%87,%88,%89,%90,%91,%92,%93,%94,%95,%96,%97,%98,%99,%100,%101,%102,%103,%104,%105,%106,%107,%108,%109,%110,%111,%112,%113,%114,%115,%116,%117,%118,%119}, {%120,%121,%122,%123}, %124, p, 1, 1, 0;}\n"
  : "+f"(d[0]),"+f"(d[1]),"+f"(d[2]),"+f"(d[3]),"+f"(d[4]),"+f"(d[5]),"+f"(d[6]),"+f"(d[7]),"+f"(d[8]),"+f"(d[9]),"+f"(d[10]),"+f"(d[11]),"+f"(d[12]),"+f"(d[13]),"+f"(d[14]),"+f"(d[15]),"+f"(d[16]),"+f"(d[17]),"+f"(d[18]),"+f"(d[19]),"+f"(d[20]),"+f"(d[21]),"+f"(d[22]),"+f"(d[23]),"+f"(d[24]),"+f"(d[25]),"+f"(d[26]),"+f"(d[27]),"+f"(d[28]),"+f"(d[29]),"+f"(d[30]),"+f"(d[31]),"+f"(d[32]),"+f"(d[33]),"+f"(d[34]),"+f"(d[35]),"+f"(d[36]),"+f"(d[37]),"+f"(d[38]),"+f"(d[39]),"+f"(d[40]),"+f"(d[41]),"+f"(d[42]),"+f"(d[43]),"+f"(d[44]),"+f"(d[45]),"+f"(d[46]),"+f"(d[47]),"+f"(d[48]),"+f"(d[49]),"+f"(d[50]),"+f"(d[51]),"+f"(d[52]),"+f"(d[53]),"+f"(d[54]),"+f"(d[55]),"+f"(d[56]),"+f"(d[57]),"+f"(d[58]),"+f"(d[59]),"+f"(d[60]),"+f"(d[61]),"+f"(d[62]),"+f"(d[63]),"+f"(d[64]),"+f"(d[65]),"+f"(d[66]),"+f"(d[67]),"+f"(d[68]),"+f"(d[69]),"+f"(d[70]),"+f"(d[71]),"+f"(d[72]),"+f"(d[73]),"+f"(d[74]),"+f"(d[75]),"+f"(d[76]),"+f"(d[77]),"+f"(d[78]),"+f"(d[79]),"+f"(d[80]),"+f"(d[81]),"+f"(d[82]),"+f"(d[83]),"+f"(d[84]),"+f"(d[85]),"+f"(d[86]),"+f"(d[87]),"+f"(d[88]),"+f"(d[89]),"+f"(d[90]),"+f"(d[91]),"+f"(d[92]),"+f"(d[93]),"+f"(d[94]),"+f"(d[95]),"+f"(d[96]),"+f"(d[97]),"+f"(d[98]),"+f"(d[99]),"+f"(d[100]),"+f"(d[101]),"+f"(d[102]),"+f"(d[103]),"+f"(d[104]),"+f"(d[105]),"+f"(d[106]),"+f"(d[107]),"+f"(d[108]),"+f"(d[109]),"+f"(d[110]),"+f"(d[111]),"+f"(d[112]),"+f"(d[113]),"+f"(d[114]),"+f"(d[115]),"+f"(d[116]),"+f"(d[117]),"+f"(d[118]),"+f"(d[119])
  : "r"(a[0]), "r"(a[1]), "r"(a[2]), "r"(a[3]), "l"(db), "r"(sc));
}
template<> __device__ __forceinline__ void wgmma_rs<256>(float* d, const uint32_t* a, uint64_t db, int sc) {
  asm volatile("{.reg .pred p; setp.ne.b32 p, %133, 0;\n"
  "wgmma.mma_async.sync.aligned.m64n256k16.f32.bf16.bf16 {%0,%1,%2,%3,%4,%5,%6,%7,%8,%9,%10,%11,%12,%13,%14,%15,%16,%17,%18,%19,%20,%21,%22,%23,%24,%25,%26,%27,%28,%29,%30,%31,%32,%33,%34,%35,%36,%37,%38,%39,%40,%41,%42,%43,%44,%45,%46,%47,%48,%49,%50,%51,%52,%53,%54,%55,%56,%57,%58,%59,%60,%61,%62,%63,%64,%65,%66,%67,%68,%69,%70,%71,%72,%73,%74,%75,%76,%77,%78,%79,%80,%81,%82,%83,%84,%85,%86,%87,%88,%89,%90,%91,%92,%93,%94,%95,%96,%97,%98,%99,%100,%101,%102,%103,%104,%105,%106,%107,%108,%109,%110,%111,%112,%113,%114,%115,%116,%117,%118,%119,%120,%121,%122,%123,%124,%125,%126,%127}, {%128,%129,%130,%131}, %132, p, 1, 1, 0;}\n"
  : "+f"(d[0]),"+f"(d[1]),"+f"(d[2]),"+f"(d[3]),"+f"(d[4]),"+f"(d[5]),"+f"(d[6]),"+f"(d[7]),"+f"(d[8]),"+f"(d[9]),"+f"(d[10]),"+f"(d[11]),"+f"(d[12]),"+f"(d[13]),"+f"(d[14]),"+f"(d[15]),"+f"(d[16]),"+f"(d[17]),"+f"(d[18]),"+f"(d[19]),"+f"(d[20]),"+f"(d[21]),"+f"(d[22]),"+f"(d[23]),"+f"(d[24]),"+f"(d[25]),"+f"(d[26]),"+f"(d[27]),"+f"(d[28]),"+f"(d[29]),"+f"(d[30]),"+f"(d[31]),"+f"(d[32]),"+f"(d[33]),"+f"(d[34]),"+f"(d[35]),"+f"(d[36]),"+f"(d[37]),"+f"(d[38]),"+f"(d[39]),"+f"(d[40]),"+f"(d[41]),"+f"(d[42]),"+f"(d[43]),"+f"(d[44]),"+f"(d[45]),"+f"(d[46]),"+f"(d[47]),"+f"(d[48]),"+f"(d[49]),"+f"(d[50]),"+f"(d[51]),"+f"(d[52]),"+f"(d[53]),"+f"(d[54]),"+f"(d[55]),"+f"(d[56]),"+f"(d[57]),"+f"(d[58]),"+f"(d[59]),"+f"(d[60]),"+f"(d[61]),"+f"(d[62]),"+f"(d[63]),"+f"(d[64]),"+f"(d[65]),"+f"(d[66]),"+f"(d[67]),"+f"(d[68]),"+f"(d[69]),"+f"(d[70]),"+f"(d[71]),"+f"(d[72]),"+f"(d[73]),"+f"(d[74]),"+f"(d[75]),"+f"(d[76]),"+f"(d[77]),"+f"(d[78]),"+f"(d[79]),"+f"(d[80]),"+f"(d[81]),"+f"(d[82]),"+f"(d[83]),"+f"(d[84]),"+f"(d[85]),"+f"(d[86]),"+f"(d[87]),"+f"(d[88]),"+f"(d[89]),"+f"(d[90]),"+f"(d[91]),"+f"(d[92]),"+f"(d[93]),"+f"(d[94]),"+f"(d[95]),"+f"(d[96]),"+f"(d[97]),"+f"(d[98]),"+f"(d[99]),"+f"(d[100]),"+f"(d[101]),"+f"(d[102]),"+f"(d[103]),"+f"(d[104]),"+f"(d[105]),"+f"(d[106]),"+f"(d[107]),"+f"(d[108]),"+f"(d[109]),"+f"(d[110]),"+f"(d[111]),"+f"(d[112]),"+f"(d[113]),"+f"(d[114]),"+f"(d[115]),"+f"(d[116]),"+f"(d[117]),"+f"(d[118]),"+f"(d[119]),"+f"(d[120]),"+f"(d[121]),"+f"(d[122]),"+f"(d[123]),"+f"(d[124]),"+f"(d[125]),"+f"(d[126]),"+f"(d[127])
  : "r"(a[0]), "r"(a[1]), "r"(a[2]), "r"(a[3]), "l"(db), "r"(sc));
}
template<> __device__ __forceinline__ void wgmma_ss<128>(float* d, uint64_t da, uint64_t db, int sc) {
  asm volatile("{.reg .pred p; setp.ne.b32 p, %66, 0;\n"
  "wgmma.mma_async.sync.aligned.m64n128k16.f32.bf16.bf16 {%0,%1,%2,%3,%4,%5,%6,%7,%8,%9,%10,%11,%12,%13,%14,%15,%16,%17,%18,%19,%20,%21,%22,%23,%24,%25,%26,%27,%28,%29,%30,%31,%32,%33,%34,%35,%36,%37,%38,%39,%40,%41,%42,%43,%44,%45,%46,%47,%48,%49,%50,%51,%52,%53,%54,%55,%56,%57,%58,%59,%60,%61,%62,%63}, %64, %65, p, 1, 1, 0, 1;}\n"
  : "+f"(d[0]),"+f"(d[1]),"+f"(d[2]),"+f"(d[3]),"+f"(d[4]),"+f"(d[5]),"+f"(d[6]),"+f"(d[7]),"+f"(d[8]),"+f"(d[9]),"+f"(d[10]),"+f"(d[11]),"+f"(d[12]),"+f"(d[13]),"+f"(d[14]),"+f"(d[15]),"+f"(d[16]),"+f"(d[17]),"+f"(d[18]),"+f"(d[19]),"+f"(d[20]),"+f"(d[21]),"+f"(d[22]),"+f"(d[23]),"+f"(d[24]),"+f"(d[25]),"+f"(d[26]),"+f"(d[27]),"+f"(d[28]),"+f"(d[29]),"+f"(d[30]),"+f"(d[31]),"+f"(d[32]),"+f"(d[33]),"+f"(d[34]),"+f"(d[35]),"+f"(d[36]),"+f"(d[37]),"+f"(d[38]),"+f"(d[39]),"+f"(d[40]),"+f"(d[41]),"+f"(d[42]),"+f"(d[43]),"+f"(d[44]),"+f"(d[45]),"+f"(d[46]),"+f"(d[47]),"+f"(d[48]),"+f"(d[49]),"+f"(d[50]),"+f"(d[51]),"+f"(d[52]),"+f"(d[53]),"+f"(d[54]),"+f"(d[55]),"+f"(d[56]),"+f"(d[57]),"+f"(d[58]),"+f"(d[59]),"+f"(d[60]),"+f"(d[61]),"+f"(d[62]),"+f"(d[63])
  : "l"(da), "l"(db), "r"(sc));
}
template<> __device__ __forceinline__ void wgmma_ss<192>(float* d, uint64_t da, uint64_t db, int sc) {
  asm volatile("{.reg .pred p; setp.ne.b32 p, %98, 0;\n"
  "wgmma.mma_async.sync.aligned.m64n192k16.f32.bf16.bf16 {%0,%1,%2,%3,%4,%5,%6,%7,%8,%9,%10,%11,%12,%13,%14,%15,%16,%17,%18,%19,%20,%21,%22,%23,%24,%25,%26,%27,%28,%29,%30,%31,%32,%33,%34,%35,%36,%37,%38,%39,%40,%41,%42,%43,%44,%45,%46,%47,%48,%49,%50,%51,%52,%53,%54,%55,%56,%57,%58,%59,%60,%61,%62,%63,%64,%65,%66,%67,%68,%69,%70,%71,%72,%73,%74,%75,%76,%77,%78,%79,%80,%81,%82,%83,%84,%85,%86,%87,%88,%89,%90,%91,%92,%93,%94,%95}, %96, %97, p, 1, 1, 0, 1;}\n"
  : "+f"(d[0]),"+f"(d[1]),"+f"(d[2]),"+f"(d[3]),"+f"(d[4]),"+f"(d[5]),"+f"(d[6]),"+f"(d[7]),"+f"(d[8]),"+f"(d[9]),"+f"(d[10]),"+f"(d[11]),"+f"(d[12]),"+f"(d[13]),"+f"(d[14]),"+f"(d[15]),"+f"(d[16]),"+f"(d[17]),"+f"(d[18]),"+f"(d[19]),"+f"(d[20]),"+f"(d[21]),"+f"(d[22]),"+f"(d[23]),"+f"(d[24]),"+f"(d[25]),"+f"(d[26]),"+f"(d[27]),"+f"(d[28]),"+f"(d[29]),"+f"(d[30]),"+f"(d[31]),"+f"(d[32]),"+f"(d[33]),"+f"(d[34]),"+f"(d[35]),"+f"(d[36]),"+f"(d[37]),"+f"(d[38]),"+f"(d[39]),"+f"(d[40]),"+f"(d[41]),"+f"(d[42]),"+f"(d[43]),"+f"(d[44]),"+f"(d[45]),"+f"(d[46]),"+f"(d[47]),"+f"(d[48]),"+f"(d[49]),"+f"(d[50]),"+f"(d[51]),"+f"(d[52]),"+f"(d[53]),"+f"(d[54]),"+f"(d[55]),"+f"(d[56]),"+f"(d[57]),"+f"(d[58]),"+f"(d[59]),"+f"(d[60]),"+f"(d[61]),"+f"(d[62]),"+f"(d[63]),"+f"(d[64]),"+f"(d[65]),"+f"(d[66]),"+f"(d[67]),"+f"(d[68]),"+f"(d[69]),"+f"(d[70]),"+f"(d[71]),"+f"(d[72]),"+f"(d[73]),"+f"(d[74]),"+f"(d[75]),"+f"(d[76]),"+f"(d[77]),"+f"(d[78]),"+f"(d[79]),"+f"(d[80]),"+f"(d[81]),"+f"(d[82]),"+f"(d[83]),"+f"(d[84]),"+f"(d[85]),"+f"(d[86]),"+f"(d[87]),"+f"(d[88]),"+f"(d[89]),"+f"(d[90]),"+f"(d[91]),"+f"(d[92]),"+f"(d[93]),"+f"(d[94]),"+f"(d[95])
  : "l"(da), "l"(db), "r"(sc));
}
template<> __device__ __forceinline__ void wgmma_ss<256>(float* d, uint64_t da, uint64_t db, int sc) {
  asm volatile("{.reg .pred p; setp.ne.b32 p, %130, 0;\n"
  "wgmma.mma_async.sync.aligned.m64n256k16.f32.bf16.bf16 {%0,%1,%2,%3,%4,%5,%6,%7,%8,%9,%10,%11,%12,%13,%14,%15,%16,%17,%18,%19,%20,%21,%22,%23,%24,%25,%26,%27,%28,%29,%30,%31,%32,%33,%34,%35,%36,%37,%38,%39,%40,%41,%42,%43,%44,%45,%46,%47,%48,%49,%50,%51,%52,%53,%54,%55,%56,%57,%58,%59,%60,%61,%62,%63,%64,%65,%66,%67,%68,%69,%70,%71,%72,%73,%74,%75,%76,%77,%78,%79,%80,%81,%82,%83,%84,%85,%86,%87,%88,%89,%90,%91,%92,%93,%94,%95,%96,%97,%98,%99,%100,%101,%102,%103,%104,%105,%106,%107,%108,%109,%110,%111,%112,%113,%114,%115,%116,%117,%118,%119,%120,%121,%122,%123,%124,%125,%126,%127}, %128, %129, p, 1, 1, 0, 1;}\n"
  : "+f"(d[0]),"+f"(d[1]),"+f"(d[2]),"+f"(d[3]),"+f"(d[4]),"+f"(d[5]),"+f"(d[6]),"+f"(d[7]),"+f"(d[8]),"+f"(d[9]),"+f"(d[10]),"+f"(d[11]),"+f"(d[12]),"+f"(d[13]),"+f"(d[14]),"+f"(d[15]),"+f"(d[16]),"+f"(d[17]),"+f"(d[18]),"+f"(d[19]),"+f"(d[20]),"+f"(d[21]),"+f"(d[22]),"+f"(d[23]),"+f"(d[24]),"+f"(d[25]),"+f"(d[26]),"+f"(d[27]),"+f"(d[28]),"+f"(d[29]),"+f"(d[30]),"+f"(d[31]),"+f"(d[32]),"+f"(d[33]),"+f"(d[34]),"+f"(d[35]),"+f"(d[36]),"+f"(d[37]),"+f"(d[38]),"+f"(d[39]),"+f"(d[40]),"+f"(d[41]),"+f"(d[42]),"+f"(d[43]),"+f"(d[44]),"+f"(d[45]),"+f"(d[46]),"+f"(d[47]),"+f"(d[48]),"+f"(d[49]),"+f"(d[50]),"+f"(d[51]),"+f"(d[52]),"+f"(d[53]),"+f"(d[54]),"+f"(d[55]),"+f"(d[56]),"+f"(d[57]),"+f"(d[58]),"+f"(d[59]),"+f"(d[60]),"+f"(d[61]),"+f"(d[62]),"+f"(d[63]),"+f"(d[64]),"+f"(d[65]),"+f"(d[66]),"+f"(d[67]),"+f"(d[68]),"+f"(d[69]),"+f"(d[70]),"+f"(d[71]),"+f"(d[72]),"+f"(d[73]),"+f"(d[74]),"+f"(d[75]),"+f"(d[76]),"+f"(d[77]),"+f"(d[78]),"+f"(d[79]),"+f"(d[80]),"+f"(d[81]),"+f"(d[82]),"+f"(d[83]),"+f"(d[84]),"+f"(d[85]),"+f"(d[86]),"+f"(d[87]),"+f"(d[88]),"+f"(d[89]),"+f"(d[90]),"+f"(d[91]),"+f"(d[92]),"+f"(d[93]),"+f"(d[94]),"+f"(d[95]),"+f"(d[96]),"+f"(d[97]),"+f"(d[98]),"+f"(d[99]),"+f"(d[100]),"+f"(d[101]),"+f"(d[102]),"+f"(d[103]),"+f"(d[104]),"+f"(d[105]),"+f"(d[106]),"+f"(d[107]),"+f"(d[108]),"+f"(d[109]),"+f"(d[110]),"+f"(d[111]),"+f"(d[112]),"+f"(d[113]),"+f"(d[114]),"+f"(d[115]),"+f"(d[116]),"+f"(d[117]),"+f"(d[118]),"+f"(d[119]),"+f"(d[120]),"+f"(d[121]),"+f"(d[122]),"+f"(d[123]),"+f"(d[124]),"+f"(d[125]),"+f"(d[126]),"+f"(d[127])
  : "l"(da), "l"(db), "r"(sc));
}

__device__ __forceinline__ void wg_fence() { asm volatile("wgmma.fence.sync.aligned;" ::: "memory"); }
__device__ __forceinline__ void wg_commit() { asm volatile("wgmma.commit_group.sync.aligned;" ::: "memory"); }
template <int N> __device__ __forceinline__ void wg_wait() { asm volatile("wgmma.wait_group.sync.aligned %0;" ::"n"(N) : "memory"); }
__device__ __forceinline__ uint64_t mkdesc(uint32_t addr, uint32_t lbo, uint32_t sbo, uint32_t swz) {
  return (uint64_t)((addr & 0x3FFFF) >> 4) | ((uint64_t)(lbo >> 4) << 16) | ((uint64_t)(sbo >> 4) << 32) | ((uint64_t)swz << 62);
}
__device__ __forceinline__ void mbar_init(uint32_t a, uint32_t c) { asm volatile("mbarrier.init.shared.b64 [%0], %1;" ::"r"(a), "r"(c) : "memory"); }
__device__ __forceinline__ void mbar_expect_tx(uint32_t a, uint32_t b) { asm volatile("mbarrier.arrive.expect_tx.shared.b64 _, [%0], %1;" ::"r"(a), "r"(b) : "memory"); }
__device__ __forceinline__ void mbar_arrive(uint32_t a) { asm volatile("mbarrier.arrive.shared.b64 _, [%0];" ::"r"(a) : "memory"); }
__device__ __forceinline__ void mbar_wait(uint32_t a, uint32_t parity) {
  uint32_t done;
  int it = 0;
  do {
    asm volatile("{.reg .pred p; mbarrier.try_wait.parity.shared.b64 p, [%1], %2; selp.u32 %0,1,0,p;}" : "=r"(done) : "r"(a), "r"(parity) : "memory");
    if (++it > (1 << 22)) __trap();
  } while (!done);
}
__device__ __forceinline__ void tma2d(uint32_t dst, const CUtensorMap* m, uint32_t bar, int c0, int c1) {
  asm volatile("cp.async.bulk.tensor.2d.shared::cluster.global.mbarrier::complete_tx::bytes [%0], [%1, {%3,%4}], [%2];"
               ::"r"(dst), "l"(m), "r"(bar), "r"(c0), "r"(c1) : "memory");
}
__device__ __forceinline__ void tma3d(uint32_t dst, const CUtensorMap* m, uint32_t bar, int c0, int c1, int c2) {
  asm volatile("cp.async.bulk.tensor.3d.shared::cluster.global.mbarrier::complete_tx::bytes [%0], [%1, {%3,%4,%5}], [%2];"
               ::"r"(dst), "l"(m), "r"(bar), "r"(c0), "r"(c1), "r"(c2) : "memory");
}
__device__ __forceinline__ void tma5d(uint32_t dst, const CUtensorMap* m, uint32_t bar, int c0, int c4) {
  asm volatile("cp.async.bulk.tensor.5d.shared::cluster.global.mbarrier::complete_tx::bytes [%0], [%1, {%3,%5,%5,%5,%4}], [%2];"
               ::"r"(dst), "l"(m), "r"(bar), "r"(c0), "r"(c4), "r"(0) : "memory");
}
__device__ __forceinline__ void bulk_g2s(uint32_t dst, const void* src, uint32_t bytes, uint32_t bar) {
  asm volatile("cp.async.bulk.shared::cluster.global.mbarrier::complete_tx::bytes [%0], [%1], %2, [%3];"
               ::"r"(dst), "l"(src), "r"(bytes), "r"(bar) : "memory");
}
__device__ __forceinline__ void prefetch_l2(const void* src, uint32_t bytes) {
  asm volatile("cp.async.bulk.prefetch.L2.global [%0], %1;" ::"l"(src), "r"(bytes) : "memory");
}
__device__ __forceinline__ void prefetch_tmap(const CUtensorMap* m) { asm volatile("prefetch.tensormap [%0];" ::"l"(m) : "memory"); }
__device__ __forceinline__ void fence_async() { asm volatile("fence.proxy.async;" ::: "memory"); }
__device__ __forceinline__ void fence_gpu() { asm volatile("fence.acq_rel.gpu;" ::: "memory"); }
__device__ __forceinline__ void bar_sync(int id, int n) { asm volatile("bar.sync %0, %1;" ::"r"(id), "r"(n) : "memory"); }
__device__ __forceinline__ uint32_t lds32(uint32_t a) { uint32_t v; asm volatile("ld.volatile.shared.b32 %0,[%1];" : "=r"(v) : "r"(a)); return v; }
__device__ __forceinline__ uint2 lds64(uint32_t a) { uint2 v; asm volatile("ld.shared.v2.b32 {%0,%1},[%2];" : "=r"(v.x), "=r"(v.y) : "r"(a) : "memory"); return v; }
__device__ __forceinline__ uint4 lds128(uint32_t a) { uint4 v; asm volatile("ld.shared.v4.b32 {%0,%1,%2,%3},[%4];" : "=r"(v.x), "=r"(v.y), "=r"(v.z), "=r"(v.w) : "r"(a) : "memory"); return v; }
__device__ __forceinline__ float4 lds128f(uint32_t a) { float4 v; asm volatile("ld.shared.v4.f32 {%0,%1,%2,%3},[%4];" : "=f"(v.x), "=f"(v.y), "=f"(v.z), "=f"(v.w) : "r"(a) : "memory"); return v; }
__device__ __forceinline__ void sts128(uint32_t a, uint32_t x, uint32_t y, uint32_t z, uint32_t w) { asm volatile("st.shared.v4.b32 [%0],{%1,%2,%3,%4};" ::"r"(a), "r"(x), "r"(y), "r"(z), "r"(w) : "memory"); }
__device__ __forceinline__ uint32_t packbf(float lo, float hi) { uint32_t r; asm("cvt.rn.bf16x2.f32 %0, %1, %2;" : "=r"(r) : "f"(hi), "f"(lo)); return r; }
__device__ __forceinline__ uint32_t packbf_relu(float lo, float hi) { uint32_t r; asm("cvt.rn.relu.bf16x2.f32 %0, %1, %2;" : "=r"(r) : "f"(hi), "f"(lo)); return r; }
__device__ __forceinline__ uint32_t bmul2(uint32_t a, uint32_t b) { uint32_t r; asm("mul.rn.bf16x2 %0, %1, %2;" : "=r"(r) : "r"(a), "r"(b)); return r; }
__device__ __forceinline__ uint32_t bfma2(uint32_t a, uint32_t b, uint32_t c) { uint32_t r; asm("fma.rn.bf16x2 %0, %1, %2, %3;" : "=r"(r) : "r"(a), "r"(b), "r"(c)); return r; }
__device__ __forceinline__ float bflo(uint32_t v) { return __uint_as_float(v << 16); }
__device__ __forceinline__ float bfhi(uint32_t v) { return __uint_as_float(v & 0xffff0000u); }
__device__ __forceinline__ uint32_t ldg_relaxed(const uint32_t* p) { uint32_t v; asm volatile("ld.relaxed.gpu.global.b32 %0,[%1];" : "=r"(v) : "l"(p) : "memory"); return v; }
__device__ __forceinline__ uint4 ldg_cg4(const void* p) { uint4 v; asm volatile("ld.global.cg.v4.b32 {%0,%1,%2,%3},[%4];" : "=r"(v.x), "=r"(v.y), "=r"(v.z), "=r"(v.w) : "l"(p) : "memory"); return v; }
__device__ __forceinline__ void stg128(void* p, uint32_t x, uint32_t y, uint32_t z, uint32_t w) { asm volatile("st.global.v4.b32 [%0],{%1,%2,%3,%4};" ::"l"(p), "r"(x), "r"(y), "r"(z), "r"(w) : "memory"); }
__device__ __forceinline__ uint2 ldg_cg2(const void* p) { uint2 v; asm volatile("ld.global.cg.v2.b32 {%0,%1},[%2];" : "=r"(v.x), "=r"(v.y) : "l"(p) : "memory"); return v; }
__device__ __forceinline__ void stg64(void* p, uint32_t x, uint32_t y) { asm volatile("st.global.v2.b32 [%0],{%1,%2};" ::"l"(p), "r"(x), "r"(y) : "memory"); }
__device__ __forceinline__ uint4 ldg_acquire4(const uint32_t* p) { uint4 v; asm volatile("ld.acquire.gpu.global.v4.b32 {%0,%1,%2,%3},[%4];" : "=r"(v.x), "=r"(v.y), "=r"(v.z), "=r"(v.w) : "l"(p) : "memory"); return v; }
__device__ __forceinline__ uint32_t ldg_acquire(const uint32_t* p) { uint32_t v; asm volatile("ld.acquire.gpu.global.b32 %0,[%1];" : "=r"(v) : "l"(p) : "memory"); return v; }
__device__ __forceinline__ bool mbar_test(uint32_t a, uint32_t parity) {
  uint32_t done;
  asm volatile("{.reg .pred p; mbarrier.test_wait.parity.shared.b64 p, [%1], %2; selp.u32 %0,1,0,p;}" : "=r"(done) : "r"(a), "r"(parity) : "memory");
  return done != 0;
}

struct Publisher {
  uint32_t bar, epoch;
  int c, gi, next;
  static constexpr int N = 11;
  __device__ __forceinline__ void service() {
    if (next >= N) return;
    const int kind = (0x3e5104 >> (2 * next)) & 3;
    const int idx = (0x10ed90 >> (2 * next)) & 3;
    const int b = kind == 0 ? B_ZDONE : kind == 1 ? B_HDONE : kind == 2 ? B_CDONE : B_ADONE;
    if (!mbar_test(bar + 8 * (b + idx), 0)) return;
    uint32_t* f = kind == 0 ? g_zflag + idx * NCTA + c : kind == 1 ? g_hflag + idx * NCTA + gi : kind == 2 ? g_cflag + c : g_aflag + idx * NCTA + gi;
    fence_gpu();
    fence_async();
    asm volatile("st.relaxed.gpu.global.b32 [%0], %1;" ::"l"(f), "r"(epoch) : "memory");
    TS(32 + next);
    next++;
  }
  __device__ __forceinline__ void wait(uint32_t a, uint32_t parity) {
    int it = 0;
    while (!mbar_test(a, parity)) { service(); if (++it > (1 << 22)) __trap(); }
  }
  __device__ __forceinline__ void wait8(const uint32_t* f) {
    int it = 0;
    while (true) {
      const uint4 a = ldg_acquire4(f), b = ldg_acquire4(f + 4);
      if (a.x == epoch && a.y == epoch && a.z == epoch && a.w == epoch && b.x == epoch && b.y == epoch && b.z == epoch && b.w == epoch) break;
      service();
      if (++it > (1 << 21)) __trap();
    }
    fence_async();
  }
};

template <int LO, int HI> __device__ __forceinline__ void rename(float* d) {
#pragma unroll
  for (int i = LO; i < HI; i++) { float e; asm volatile("mov.b32 %0, %1;" : "=f"(e) : "f"(d[i])); d[i] = e; }
}
template <int M> __device__ __forceinline__ void drain4(const float* d, uint32_t ya) {
  uint32_t r[4];
#pragma unroll
  for (int q = 0; q < 4; q++) {
    const int mu = M + q;
    float v0 = d[4 * mu], v1 = d[4 * mu + 1];
    if (mu > 0) { v0 += d[4 * mu - 2]; v1 += d[4 * mu - 1]; }
    r[q] = packbf(v0, v1);
  }
  asm volatile("stmatrix.sync.aligned.m8n8.x4.trans.shared.b16 [%0],{%1,%2,%3,%4};" ::"r"(ya + M * 128), "r"(r[0]), "r"(r[1]), "r"(r[2]), "r"(r[3]) : "memory");
}
__device__ __forceinline__ void lda(uint32_t* a, uint32_t ua) { a[0] = lds32(ua); a[1] = lds32(ua + 128); a[2] = lds32(ua - 16); a[3] = lds32(ua + 112); }
template <int P> struct Pass {
  static __device__ __forceinline__ void run(float* d, uint32_t (*a)[4], uint32_t ua, uint64_t db, uint32_t ya, uint32_t ubar, bool first) {
    if constexpr (P > 0) rename<8 * (P - 1), 128>(d);
    wg_fence();
    wgmma_rs<256 - 16 * P>(d + 8 * P, a[P & 1], db, P != 0);
    wg_commit();
    if constexpr (P < 15) {
      if constexpr (P & 1) { if (first) mbar_wait(ubar + 8 * ((P + 1) / 2), 0); }
      lda(a[(P + 1) & 1], ua + (P + 1) * 256);
    }
    if constexpr (P >= 2 && (P & 1) == 0) drain4<2 * P - 4>(d, ya);
    wg_wait<0>();
    if constexpr (P < 15) Pass<P + 1>::run(d, a, ua, db, ya, ubar, first);
    else { rename<120, 128>(d); drain4<28>(d, ya); }
  }
};

__device__ __forceinline__ uint32_t off_T(int r) { return r == 0 ? OFF_T0 : r == 1 ? OFF_T1 : r == 2 ? OFF_T2 : OFF_T3; }
__device__ __forceinline__ uint32_t off_Y(int r) { return r == 1 ? OFF_KVA : r == 2 ? OFF_KVB : OFF_X; }

template <int NT>
__device__ __forceinline__ void gemm1_tile(uint32_t sb, int tile, int wg, int w, int lane, int row0, int n0, uint32_t csb) {
  const uint32_t bar = sb + OFF_BAR;
  float acc[NT / 2];
  const bool elect = (threadIdx.x & 127) == 0;
#pragma unroll 1
  for (int kb = 0; kb < 16; kb++) {
    const int s = kb & 3;
    mbar_wait(bar + 8 * (B_FULL1 + s), (kb >> 2) & 1);
    const uint32_t sa = sb + s * 49152;
    const uint64_t da = mkdesc(sa + wg * 8192, 16, 1024, 1), db = mkdesc(sa + 16384, 8192, 1024, 1);
    wg_fence();
#pragma unroll
    for (int kk = 0; kk < 4; kk++) wgmma_ss<NT>(acc, da + kk * 2, db + kk * 128, (kb | kk) != 0);
    wg_commit();
    wg_wait<1>();
    if (kb > 0 && elect) mbar_arrive(bar + 8 * (B_EMPTY1 + ((kb - 1) & 3)));
  }
  const int g = lane >> 2, t = lane & 3;
  const int r0 = row0 + 64 * wg + 16 * w + g;
  float2 st0, st1;
  asm volatile("ld.global.cg.v2.f32 {%0,%1},[%2];" : "=f"(st0.x), "=f"(st0.y) : "l"(g_hstat + r0) : "memory");
  asm volatile("ld.global.cg.v2.f32 {%0,%1},[%2];" : "=f"(st1.x), "=f"(st1.y) : "l"(g_hstat + r0 + 8) : "memory");
  if (tile == 0) mbar_wait(bar + 8 * B_CSFULL, 0);
  wg_wait<0>();
  rename<0, NT / 2>(acc);
  if (elect) mbar_arrive(bar + 8 * (B_EMPTY1 + 3));
  __nv_bfloat16* p0 = g_act + (size_t)r0 * F + n0 + 8 * t;
  __nv_bfloat16* p1 = p0 + 8 * F;
#pragma unroll
  for (int J = 0; J < NT / 32; J++) {
    uint32_t o0[4], o1[4];
#pragma unroll
    for (int jj = 0; jj < 4; jj++) {
      const int mu = 4 * J + jj;
      const float4 c = lds128f(csb + (4 * mu + t) * 16);
      const float a0 = fmaf(acc[4 * mu + 0], st0.y, fmaf(st0.x, c.x, c.z));
      const float a1 = fmaf(acc[4 * mu + 1], st0.y, fmaf(st0.x, c.y, c.w));
      const float a2 = fmaf(acc[4 * mu + 2], st1.y, fmaf(st1.x, c.x, c.z));
      const float a3 = fmaf(acc[4 * mu + 3], st1.y, fmaf(st1.x, c.y, c.w));
      const uint32_t u0 = packbf_relu(a0, a1), u1 = packbf_relu(a2, a3);
      o0[jj] = bmul2(u0, u0);
      o1[jj] = bmul2(u1, u1);
    }
    stg128(p0 + 32 * J, o0[0], o0[1], o0[2], o0[3]);
    stg128(p1 + 32 * J, o1[0], o1[1], o1[2], o1[3]);
  }
  __syncwarp();
  if (lane == 0) mbar_arrive(bar + 8 * (B_ADONE + tile));
}

__global__ void __launch_bounds__(NTHREADS, 1) fused_kernel(const __grid_constant__ Params P) {
  extern __shared__ __align__(1024) unsigned char smem[];
  const uint32_t sb = (uint32_t)__cvta_generic_to_shared(smem);
  const uint32_t bar = sb + OFF_BAR;
  const int tid = threadIdx.x, warp = tid >> 5, lane = tid & 31;
  const int c = blockIdx.x, m = c & 15, j = c >> 4;
  const int gi = m * 8 + j;

  if (tid == 256) {
    TS(0);
    for (int i = 0; i < 8; i++) { mbar_init(bar + 8 * (B_KVFULL + i), 1); mbar_init(bar + 8 * (B_KFULL + i), 2); mbar_init(bar + 8 * (B_UFULL + i), 1); }
    for (int i = 0; i < 4; i++) { mbar_init(bar + 8 * (B_YFULL + i), 8); mbar_init(bar + 8 * (B_ZDONE + i), 3); mbar_init(bar + 8 * (B_HDONE + i), 3); mbar_init(bar + 8 * (B_FULL1 + i), 1); mbar_init(bar + 8 * (B_EMPTY1 + i), 2); }
    for (int i = 0; i < 6; i++) { mbar_init(bar + 8 * (B_FULL2 + i), 1); mbar_init(bar + 8 * (B_EMPTY2 + i), 2); }
    mbar_init(bar + 8 * B_CSFULL, 3); mbar_init(bar + 8 * B_HRES, 1); mbar_init(bar + 8 * B_CDONE, 1); mbar_init(bar + 8 * B_XDONE, 8);
    mbar_init(bar + 8 * B_ADONE, 8); mbar_init(bar + 8 * (B_ADONE + 1), 8);
    asm volatile("fence.mbarrier_init.release.cluster;" ::: "memory");
    fence_async();
    for (int ch = 0; ch < 2; ch++) {
      mbar_expect_tx(bar + 8 * (B_KFULL + ch), 4080);
      bulk_g2s(sb + OFF_T0 + 2 * UT_SIZE + ch * KT_SIZE + 32, P.ssm_k + (size_t)(8 * c + ch) * S + 8, 4080, bar + 8 * (B_KFULL + ch));
    }
    for (int i = 0; i < 8; i++) {
      mbar_expect_tx(bar + 8 * (B_KVFULL + i), 2 * KV_STAGE);
      tma3d(sb + OFF_KVA + i * KV_STAGE, &P.tm_k, bar + 8 * (B_KVFULL + i), 8 * c, 32 * i - 1, 0);
      tma3d(sb + OFF_KVB + i * KV_STAGE, &P.tm_v, bar + 8 * (B_KVFULL + i), 8 * c, 32 * i - 1, 0);
    }
    for (int ch = 2; ch < 8; ch++) {
      mbar_expect_tx(bar + 8 * (B_KFULL + ch), 4080);
      bulk_g2s(sb + off_T(ch >> 1) + 2 * UT_SIZE + (ch & 1) * KT_SIZE + 32, P.ssm_k + (size_t)(8 * c + ch) * S + 8, 4080, bar + 8 * (B_KFULL + ch));
    }
  }
  __syncthreads();

  if (warp < 8) {
    const int wg = warp >> 2, w = warp & 3, g = lane >> 2, t = lane & 3;
    {
      const int row = 128 * m + 16 * j + 2 * warp;
      uint4 v[2][4];
#pragma unroll
      for (int a = 0; a < 2; a++)
#pragma unroll
        for (int k = 0; k < 4; k++) v[a][k] = __ldg((const uint4*)(P.x + (size_t)(row + a) * D) + lane + 32 * k);
#pragma unroll
      for (int a = 0; a < 2; a++) {
        uint32_t* hp = (uint32_t*)(g_h + (size_t)(row + a) * D) + lane;
        float t1 = 0.f;
#pragma unroll
        for (int k = 0; k < 4; k++) {
          hp[32 * k] = v[a][k].x; hp[128 + 32 * k] = v[a][k].y; hp[256 + 32 * k] = v[a][k].z; hp[384 + 32 * k] = v[a][k].w;
          t1 += (bflo(v[a][k].x) + bfhi(v[a][k].x)) + (bflo(v[a][k].y) + bfhi(v[a][k].y));
          t1 += (bflo(v[a][k].z) + bfhi(v[a][k].z)) + (bflo(v[a][k].w) + bfhi(v[a][k].w));
        }
#pragma unroll
        for (int o = 1; o < 32; o <<= 1) t1 += __shfl_xor_sync(0xffffffffu, t1, o);
        const float mu = t1 * (1.f / D);
        float t2 = 0.f;
#pragma unroll
        for (int k = 0; k < 4; k++) {
          const uint32_t vv[4] = {v[a][k].x, v[a][k].y, v[a][k].z, v[a][k].w};
#pragma unroll
          for (int e = 0; e < 4; e++) {
            const float lo = bflo(vv[e]) - mu, hi = bfhi(vv[e]) - mu;
            t2 = fmaf(lo, lo, fmaf(hi, hi, t2));
          }
        }
#pragma unroll
        for (int o = 1; o < 32; o <<= 1) t2 += __shfl_xor_sync(0xffffffffu, t2, o);
        const float rs = rsqrtf(t2 * (1.f / D) + 1e-5f);
        if (lane == 0) ((float2*)(smem + OFF_XS))[2 * warp + a] = make_float2(-mu * rs, rs);
      }
      __syncwarp();
      if (lane == 0) mbar_arrive(bar + 8 * B_XDONE);
      if (tid == 0) TS(22);
    }
#pragma unroll 1
    for (int r = 0; r < 4; r++) {
      float d[128];
      uint32_t a[2][4];
      const uint32_t tb = sb + off_T(r);
      const uint32_t ua = tb + wg * UT_SIZE + ((g & 1) ? 0 : UT_COPY) + ((g >> 1) + 8 * w + 8 - t) * 4;
      const uint64_t db = mkdesc(tb + 2 * UT_SIZE + wg * KT_SIZE, 16, 128, 0);
      const uint32_t yb = sb + off_Y(r) + wg * YBUF + w * YW;
      if (r == 3) mbar_wait(bar + 8 * B_ZDONE, 0);
      if (lane < 2 * w) sts128(yb + lane * 16, 0, 0, 0, 0);
      mbar_wait(bar + 8 * (B_KFULL + 2 * r + wg), 0);
      if (r == 0) mbar_wait(bar + 8 * B_UFULL, 0);
      if (tid == 0) TS(1 + r);
      lda(a[0], ua);
      Pass<0>::run(d, a, ua, db, yb + (2 * w + lane) * 16, bar + 8 * B_UFULL, r == 0);
      __syncwarp();
      if (lane == 0) mbar_arrive(bar + 8 * (B_YFULL + r));
    }
    if (tid == 0) TS(5);
    gemm1_tile<256>(sb, 0, wg, w, lane, 128 * m, 448 * j, sb + OFF_X);
    if (tid == 0) TS(6);
    gemm1_tile<192>(sb, 1, wg, w, lane, 128 * m, 448 * j + 256, sb + OFF_CSB2);
    if (tid == 0) TS(7);
    {
      float acc[64], res[64];
      const bool elect = (tid & 127) == 0;
      int s = 0, ph = 0, prev = 0;
#pragma unroll 1
      for (int kb = 0; kb < 56; kb++) {
        mbar_wait(bar + 8 * (B_FULL2 + s), ph);
        const uint32_t sa = sb + s * 32768;
        const uint64_t da = mkdesc(sa + wg * 8192, 16, 1024, 1), db = mkdesc(sa + 16384, 8192, 1024, 1);
        wg_fence();
#pragma unroll
        for (int kk = 0; kk < 4; kk++) wgmma_ss<128>(acc, da + kk * 2, db + kk * 128, (kb | kk) != 0);
        wg_commit();
        if (kb == 8) {
          mbar_wait(bar + 8 * B_HRES, 0);
          const uint32_t* b2p = (const uint32_t*)(P.b2 + 128 * j) + t;
#pragma unroll
          for (int h = 0; h < 2; h++) {
            const int row = 64 * wg + 16 * w + 8 * h + g;
            const uint32_t la = sb + OFF_X + row * 256 + t * 64;
            const int sw = (2 * row + (t >> 1)) & 3;
#pragma unroll
            for (int cc = 0; cc < 4; cc++) {
              const uint4 v = lds128(la + ((cc ^ sw) << 4));
              const uint32_t vv[4] = {v.x, v.y, v.z, v.w};
#pragma unroll
              for (int q = 0; q < 4; q++) {
                const int mu = 4 * cc + q;
                const uint32_t b = __ldg(b2p + 4 * mu);
                res[4 * mu + 2 * h] = bflo(vv[q]) + bflo(b);
                res[4 * mu + 2 * h + 1] = bfhi(vv[q]) + bfhi(b);
              }
            }
          }
        }
        wg_wait<1>();
        if (kb > 0 && elect) mbar_arrive(bar + 8 * (B_EMPTY2 + prev));
        prev = s;
        if (++s == 6) { s = 0; ph ^= 1; }
      }
      wg_wait<0>();
      rename<0, 64>(acc);
      if (tid == 0) TS(8);
      const int id = lane >> 3, row = 16 * w + (lane & 7) + 8 * (id & 1);
      const uint32_t ob = sb + OFF_X + wg * 16384 + row * 128;
#pragma unroll
      for (int mu = 0; mu < 16; mu += 2) {
        const uint32_t r0 = packbf(acc[4 * mu] + res[4 * mu], acc[4 * mu + 1] + res[4 * mu + 1]);
        const uint32_t r1 = packbf(acc[4 * mu + 2] + res[4 * mu + 2], acc[4 * mu + 3] + res[4 * mu + 3]);
        const uint32_t r2 = packbf(acc[4 * mu + 4] + res[4 * mu + 4], acc[4 * mu + 5] + res[4 * mu + 5]);
        const uint32_t r3 = packbf(acc[4 * mu + 6] + res[4 * mu + 6], acc[4 * mu + 7] + res[4 * mu + 7]);
        const int ch = (mu & 7) + (id >> 1);
        asm volatile("stmatrix.sync.aligned.m8n8.x4.shared.b16 [%0],{%1,%2,%3,%4};"
                     ::"r"(ob + (mu >> 3) * 8192 + ((ch ^ (row & 7)) << 4)), "r"(r0), "r"(r1), "r"(r2), "r"(r3) : "memory");
      }
      fence_async();
      bar_sync(3 + wg, 128);
      if (elect) {
        for (int b = 0; b < 2; b++)
          asm volatile("cp.async.bulk.tensor.2d.global.shared::cta.bulk_group [%0, {%2,%3}], [%1];"
                       ::"l"(&P.tm_out), "r"(sb + OFF_X + wg * 16384 + b * 8192), "r"(128 * j + 64 * b), "r"(128 * m + 64 * wg) : "memory");
        asm volatile("cp.async.bulk.commit_group;" ::: "memory");
        asm volatile("cp.async.bulk.wait_group.read 0;" ::: "memory");
        if (tid == 0) TS(9);
      }
    }
  } else {
    const uint32_t epoch = ldg_relaxed(g_aflag + NCTA + gi) + 1;
    if (warp == 8) {
      if (lane == 0) {
        prefetch_tmap(&P.tm_h); prefetch_tmap(&P.tm_w1); prefetch_tmap(&P.tm_act); prefetch_tmap(&P.tm_w2);
        prefetch_tmap(&P.tm_hres); prefetch_tmap(&P.tm_out);
        Publisher pub{bar, epoch, c, gi, 0};
        pub.wait(bar + 8 * (B_KVFULL + 7), 0);
        TS(10);
        prefetch_l2(P.w1 + (size_t)c * 8 * F, 8 * F * 2);
#pragma unroll 1
        for (int it = 0; it < 32; it++) {
          const int s = it & 3, kb = it & 15, tile = it >> 4;
          if (it == 0) pub.wait(bar + 8 * (B_ZDONE + 1), 0);
          else if (it == 2) pub.wait(bar + 8 * (B_ZDONE + 2), 0);
          else if (it == 3) pub.wait(bar + 8 * (B_YFULL + 3), 0);
          else if (it >= 4) pub.wait(bar + 8 * (B_EMPTY1 + s), ((it >> 2) - 1) & 1);
          if (it < 4) fence_async();
          const uint32_t sa = sb + s * 49152, fb = bar + 8 * (B_FULL1 + s);
          const int nb = tile ? 3 : 4, n0 = 448 * j + 256 * tile;
          mbar_expect_tx(fb, 16384 + nb * 8192);
          for (int i = 0; i < nb; i++) tma3d(sa + 16384 + i * 8192, &P.tm_w1, fb, n0 + 64 * i, 2 * (kb >> 2), 32 * (kb & 3));
          if (it < 16 && (it & 3) == 0) { pub.wait8(g_hflag + (it >> 2) * NCTA + 8 * m); TS(11 + (it >> 2)); }
          tma2d(sa, &P.tm_h, fb, 64 * kb, 128 * m);
          if (it == 8) prefetch_l2(P.w2 + (size_t)c * 28 * D, 28 * D * 2);
          if (it == 21) {
            mbar_expect_tx(bar + 8 * B_HRES, 32768);
            tma3d(sb + OFF_X, &P.tm_hres, bar + 8 * B_HRES, 32 * j, 0, 128 * m);
          }
        }
        int s = 0, ph = 1;
#pragma unroll 1
        for (int kb = 0; kb < 56; kb++) {
          if (kb < 6) { if (kb != 2 && kb != 5) pub.wait(bar + 8 * (B_EMPTY1 + (2 * kb + 1) / 3), 1); }
          else pub.wait(bar + 8 * (B_EMPTY2 + s), ph);
          const int col = kb < 32 ? 448 * (kb >> 2) + 64 * (kb & 3) : 448 * ((kb - 32) / 3) + 256 + 64 * ((kb - 32) % 3);
          const uint32_t sa = sb + s * 32768, fb = bar + 8 * (B_FULL2 + s);
          mbar_expect_tx(fb, 32768);
          tma5d(sa + 16384, &P.tm_w2, fb, 128 * j, col >> 5);
          tma5d(sa + 24576, &P.tm_w2, fb, 128 * j + 64, col >> 5);
          if ((kb & 31) == 0) { pub.wait8(g_aflag + (kb >> 5) * NCTA + 8 * m); TS(15 + (kb >> 5)); }
          tma2d(sa, &P.tm_act, fb, col, 128 * m);
          if (++s == 6) { s = 0; ph ^= 1; }
        }
      }
    } else {
      const int zw = warp - 9;
      if (zw == 2 && lane < 8) {
        const int ch = 8 * c + lane;
        uint4 v = __ldg((const uint4*)(P.ssm_k + (size_t)ch * S));
        const float k0 = bflo(v.x) + __bfloat162float(P.ssm_D[ch]);
        v.x = (v.x & 0xffff0000u) | (packbf(k0, 0.f) & 0xffffu);
        const uint32_t kt = sb + off_T(lane >> 1) + 2 * UT_SIZE + (lane & 1) * KT_SIZE;
        sts128(kt, 0, 0, 0, 0);
        sts128(kt + 16, v.x, v.y, v.z, v.w);
        fence_async();
        mbar_arrive(bar + 8 * (B_KFULL + lane));
      }
      {
        uint32_t W[4][4];
        const uint4* wp = (const uint4*)(P.shift_k + (size_t)32 * c);
#pragma unroll
        for (int p = 0; p < 4; p++) {
          const uint4 v = __ldg(wp + p);
          W[0][p] = __byte_perm(v.x, v.z, 0x5410); W[1][p] = __byte_perm(v.x, v.z, 0x7632);
          W[2][p] = __byte_perm(v.y, v.w, 0x5410); W[3][p] = __byte_perm(v.y, v.w, 0x7632);
        }
        if (zw == 0 && lane < 16) sts128(sb + off_T(lane >> 2) + (lane & 3) * UT_COPY, 0, 0, 0, 0);
#pragma unroll 1
        for (int st = zw; st < 8; st += 3) {
          mbar_wait(bar + 8 * (B_KVFULL + st), 0);
          const uint32_t ka = sb + OFF_KVA + st * KV_STAGE + lane * 16, va = sb + OFF_KVB + st * KV_STAGE + lane * 16;
          uint32_t u[9][4];
          uint4 k3 = lds128(ka + 4 * 528), k2 = lds128(ka + 5 * 528), k1 = lds128(ka + 6 * 528);
#pragma unroll
          for (int i = 0; i < 9; i++) {
            const uint32_t o = i == 0 ? 7 * 528 : (i - 1) * 528 + 16;
            const uint4 k0 = lds128(ka + o), v = lds128(va + o);
            u[i][0] = bmul2(bfma2(k0.x, W[0][0], bfma2(k1.x, W[1][0], bfma2(k2.x, W[2][0], bmul2(k3.x, W[3][0])))), v.x);
            u[i][1] = bmul2(bfma2(k0.y, W[0][1], bfma2(k1.y, W[1][1], bfma2(k2.y, W[2][1], bmul2(k3.y, W[3][1])))), v.y);
            u[i][2] = bmul2(bfma2(k0.z, W[0][2], bfma2(k1.z, W[1][2], bfma2(k2.z, W[2][2], bmul2(k3.z, W[3][2])))), v.z);
            u[i][3] = bmul2(bfma2(k0.w, W[0][3], bfma2(k1.w, W[1][3], bfma2(k2.w, W[2][3], bmul2(k3.w, W[3][3])))), v.w);
            k3 = k2; k2 = k1; k1 = k0;
          }
#pragma unroll
          for (int p = 0; p < 4; p++) {
            const uint32_t ta = sb + off_T(p) + 16 + (32 * st + lane) * 16;
#pragma unroll
            for (int e = 0; e < 2; e++) {
              const uint32_t sel = e ? 0x7632 : 0x5410;
              sts128(ta + e * UT_SIZE, __byte_perm(u[2][p], u[1][p], sel), __byte_perm(u[4][p], u[3][p], sel),
                     __byte_perm(u[6][p], u[5][p], sel), __byte_perm(u[8][p], u[7][p], sel));
              sts128(ta + e * UT_SIZE + UT_COPY, __byte_perm(u[1][p], u[0][p], sel), __byte_perm(u[3][p], u[2][p], sel),
                     __byte_perm(u[5][p], u[4][p], sel), __byte_perm(u[7][p], u[6][p], sel));
            }
          }
          __syncwarp();
          if (lane == 0) mbar_arrive(bar + 8 * (B_UFULL + st));
        }
      }
      const int q = lane & 3;
      const int row0 = 128 * m + 16 * j + 4 * q;
      float s1[4] = {0.f, 0.f, 0.f, 0.f}, s2[4] = {0.f, 0.f, 0.f, 0.f};
#pragma unroll 1
      for (int ev = 0; ev < 8; ev++) {
        const int r = (0xed90 >> (2 * ev)) & 3;
        if (((0x5104 >> (2 * ev)) & 3) == 0) {
          mbar_wait(bar + 8 * (B_YFULL + r), 0);
          const uint32_t yb = sb + off_Y(r) + lane * 8;
          uint32_t* zp = g_z + (size_t)(r * NCTA + c) * S + lane * 4;
#pragma unroll 2
          for (int task = zw; task < 16; task += 3) {
            float a[2][4];
#pragma unroll
            for (int e = 0; e < 2; e++) {
              const uint2 p0 = lds64(yb + e * YBUF + task * 256), p1 = lds64(yb + e * YBUF + YW + task * 256);
              const uint2 p2 = lds64(yb + e * YBUF + 2 * YW + task * 256), p3 = lds64(yb + e * YBUF + 3 * YW + task * 256);
              a[e][0] = (bflo(p0.x) + bflo(p1.x)) + (bflo(p2.x) + bflo(p3.x));
              a[e][1] = (bfhi(p0.x) + bfhi(p1.x)) + (bfhi(p2.x) + bfhi(p3.x));
              a[e][2] = (bflo(p0.y) + bflo(p1.y)) + (bflo(p2.y) + bflo(p3.y));
              a[e][3] = (bfhi(p0.y) + bfhi(p1.y)) + (bfhi(p2.y) + bfhi(p3.y));
            }
            stg128(zp + task * 128, packbf(a[0][0], a[1][0]), packbf(a[0][1], a[1][1]), packbf(a[0][2], a[1][2]), packbf(a[0][3], a[1][3]));
          }
          __syncwarp();
          if (lane == 0) mbar_arrive(bar + 8 * (B_ZDONE + r));
          if (tid == 288) TS(17 + r);
        } else {
          if (r == 0) mbar_wait(bar + 8 * B_XDONE, 0);
          const int ip = 8 * (2 - zw) + (lane >> 2);
          uint2 xv[3][4];
          uint4 zv[3][2];
          __nv_bfloat16* hp = g_h + (size_t)row0 * D + 256 * r + 4 * ip;
#pragma unroll
          for (int k = 0; k < 3; k++)
            if (k < 2 || zw > 0) {
#pragma unroll
              for (int a = 0; a < 4; a++) xv[k][a] = ldg_cg2(hp + a * D + 96 * k);
            }
          {
            int it = 0;
            while (true) {
              const uint4 f = ldg_acquire4(g_zflag + r * NCTA + 4 * lane);
              if (__all_sync(0xffffffffu, f.x == epoch && f.y == epoch && f.z == epoch && f.w == epoch)) break;
              if (++it > (1 << 21)) __trap();
            }
          }
          if (tid == 288) TS(27 + r);
          const uint32_t* zp = g_z + (size_t)(r * NCTA + 2 * ip) * S + row0;
#pragma unroll
          for (int k = 0; k < 3; k++)
            if (k < 2 || zw > 0) { zv[k][0] = ldg_cg4(zp + (size_t)48 * k * S); zv[k][1] = ldg_cg4(zp + (size_t)(48 * k + 1) * S); }
#pragma unroll
          for (int a = 0; a < 4; a++) {
            const float2 xs = ((const float2*)(smem + OFF_XS))[4 * q + a];
#pragma unroll
            for (int k = 0; k < 3; k++)
              if (k < 2 || zw > 0) {
                uint32_t o[2];
#pragma unroll
                for (int e = 0; e < 2; e++) {
                  const uint32_t xx = e ? xv[k][a].y : xv[k][a].x;
                  const uint32_t zz = a == 0 ? zv[k][e].x : a == 1 ? zv[k][e].y : a == 2 ? zv[k][e].z : zv[k][e].w;
                  const float x0 = bflo(xx), x1 = bfhi(xx);
                  o[e] = packbf(fmaf(fmaf(x0, xs.y, xs.x), bflo(zz), x0), fmaf(fmaf(x1, xs.y, xs.x), bfhi(zz), x1));
                  const float f0 = bflo(o[e]), f1 = bfhi(o[e]);
                  s1[a] += f0 + f1;
                  s2[a] = fmaf(f0, f0, fmaf(f1, f1, s2[a]));
                }
                stg64(hp + a * D + 96 * k, o[0], o[1]);
              }
          }
          if (r == 3) {
            float* red = (float*)(smem + OFF_RED);
#pragma unroll
            for (int a = 0; a < 4; a++) {
#pragma unroll
              for (int o = 4; o < 32; o <<= 1) {
                s1[a] += __shfl_xor_sync(0xffffffffu, s1[a], o);
                s2[a] += __shfl_xor_sync(0xffffffffu, s2[a], o);
              }
              if (lane < 4) { red[(zw * 16 + 4 * q + a) * 2] = s1[a]; red[(zw * 16 + 4 * q + a) * 2 + 1] = s2[a]; }
            }
            bar_sync(1, 96);
            if (zw == 0 && lane < 16) {
              const float mu = (red[2 * lane] + red[32 + 2 * lane] + red[64 + 2 * lane]) * (1.f / D);
              const float e2 = (red[2 * lane + 1] + red[33 + 2 * lane] + red[65 + 2 * lane]) * (1.f / D);
              const float rs = rsqrtf(fmaxf(fmaf(-mu, mu, e2), 0.f) + 1e-5f);
              g_hstat[128 * m + 16 * j + lane] = make_float2(-mu * rs, rs);
            }
          }
          __syncwarp();
          if (lane == 0) mbar_arrive(bar + 8 * (B_HDONE + r));
          if (tid == 288) TS(23 + r);
        }
      }
      if (m < 14) {
        float cs[8];
#pragma unroll
        for (int i = 0; i < 8; i++) cs[i] = 0.f;
        const __nv_bfloat16* wp = P.w1 + (size_t)(lane >> 2) * F + 448 * j + 32 * m + 8 * (lane & 3);
#pragma unroll 8
        for (int task = zw; task < 128; task += 3) {
          const uint4 v = __ldg((const uint4*)(wp + (size_t)task * 8 * F));
          cs[0] += bflo(v.x); cs[1] += bfhi(v.x); cs[2] += bflo(v.y); cs[3] += bfhi(v.y);
          cs[4] += bflo(v.z); cs[5] += bfhi(v.z); cs[6] += bflo(v.w); cs[7] += bfhi(v.w);
        }
#pragma unroll
        for (int i = 0; i < 8; i++) {
          cs[i] += __shfl_xor_sync(0xffffffffu, cs[i], 4);
          cs[i] += __shfl_xor_sync(0xffffffffu, cs[i], 8);
          cs[i] += __shfl_xor_sync(0xffffffffu, cs[i], 16);
        }
        float* red = (float*)(smem + OFF_CSB2);
        if (lane < 4) {
#pragma unroll
          for (int i = 0; i < 8; i++) red[zw * 32 + lane * 8 + i] = cs[i];
        }
        bar_sync(1, 96);
        if (zw == 0) {
          g_cs[448 * j + 32 * m + lane] = red[lane] + red[32 + lane] + red[64 + lane];
          __syncwarp();
        }
        bar_sync(1, 96);
      }
      if (tid == 288) mbar_arrive(bar + 8 * B_CDONE);
      {
        int it = 0;
        while (true) {
          const uint32_t v = lane < 14 ? ldg_acquire(g_cflag + 16 * j + lane) : epoch;
          if (__all_sync(0xffffffffu, v == epoch)) break;
          if (++it > (1 << 21)) __trap();
        }
        for (int i = zw * 32 + lane; i < 224; i += 96) {
          float2 cv;
          asm volatile("ld.global.cg.v2.f32 {%0,%1},[%2];" : "=f"(cv.x), "=f"(cv.y) : "l"(g_cs + 448 * j + 2 * i) : "memory");
          const uint32_t b = __ldg((const uint32_t*)(P.b1 + 448 * j) + i);
          const uint32_t dst = i < 128 ? sb + OFF_X + i * 16 : sb + OFF_CSB2 + (i - 128) * 16;
          sts128(dst, __float_as_uint(cv.x), __float_as_uint(cv.y), __float_as_uint(bflo(b)), __float_as_uint(bfhi(b)));
        }
        __syncwarp();
        if (lane == 0) mbar_arrive(bar + 8 * B_CSFULL);
        if (tid == 288) TS(21);
      }
    }
  }
}

typedef CUresult (*PFN_encode)(CUtensorMap*, CUtensorMapDataType, cuuint32_t, void*, const cuuint64_t*, const cuuint64_t*, const cuuint32_t*,
                               const cuuint32_t*, CUtensorMapInterleave, CUtensorMapSwizzle, CUtensorMapL2promotion, CUtensorMapFloatOOBfill);

void encode(PFN_encode enc, CUtensorMap* m, const void* ptr, int rank, const cuuint64_t* dims, const cuuint64_t* strides, const cuuint32_t* box,
            CUtensorMapSwizzle swz) {
  const cuuint32_t es[5] = {1, 1, 1, 1, 1};
  enc(m, CU_TENSOR_MAP_DATA_TYPE_BFLOAT16, rank, (void*)ptr, dims, strides, box, es, CU_TENSOR_MAP_INTERLEAVE_NONE, swz,
      CU_TENSOR_MAP_L2_PROMOTION_L2_128B, CU_TENSOR_MAP_FLOAT_OOB_FILL_NONE);
}

}

extern "C" void kernel_launch(void* const* d_in, const int* in_sizes, int n_in, void* d_out, int out_size) {
  static PFN_encode enc = nullptr;
  static void *p_h = nullptr, *p_act = nullptr;
  if (!enc) {
    cudaDriverEntryPointQueryResult qr;
    cudaGetDriverEntryPoint("cuTensorMapEncodeTiled", (void**)&enc, cudaEnableDefault, &qr);
    cudaGetSymbolAddress(&p_h, g_h);
    cudaGetSymbolAddress(&p_act, g_act);
    cudaFuncSetAttribute(fused_kernel, cudaFuncAttributeMaxDynamicSharedMemorySize, SMEM_BYTES);
  }
  Params P;
  P.x = (const __nv_bfloat16*)d_in[0];
  P.shift_k = (const __nv_bfloat16*)d_in[3];
  P.ssm_k = (const __nv_bfloat16*)d_in[4];
  P.ssm_D = (const __nv_bfloat16*)d_in[5];
  P.w1 = (const __nv_bfloat16*)d_in[7];
  P.b1 = (const __nv_bfloat16*)d_in[8];
  P.w2 = (const __nv_bfloat16*)d_in[9];
  P.b2 = (const __nv_bfloat16*)d_in[10];
  {
    const cuuint64_t dims[3] = {D, S / 8, 8}, str[2] = {8 * D * 2, D * 2};
    const cuuint32_t box[3] = {8, 33, 8};
    encode(enc, &P.tm_k, d_in[1], 3, dims, str, box, CU_TENSOR_MAP_SWIZZLE_NONE);
    encode(enc, &P.tm_v, d_in[2], 3, dims, str, box, CU_TENSOR_MAP_SWIZZLE_NONE);
  }
  {
    const cuuint64_t dims[2] = {D, S}, str[1] = {D * 2};
    const cuuint32_t box[2] = {64, 128}, boxo[2] = {64, 64};
    encode(enc, &P.tm_h, p_h, 2, dims, str, box, CU_TENSOR_MAP_SWIZZLE_128B);
    encode(enc, &P.tm_out, d_out, 2, dims, str, boxo, CU_TENSOR_MAP_SWIZZLE_128B);
  }
  {
    const cuuint64_t dims[3] = {F, 8, D / 8}, str[2] = {F * 2, 8 * F * 2};
    const cuuint32_t box[3] = {64, 2, 32};
    encode(enc, &P.tm_w1, P.w1, 3, dims, str, box, CU_TENSOR_MAP_SWIZZLE_128B);
  }
  {
    const cuuint64_t dims[2] = {F, S}, str[1] = {F * 2};
    const cuuint32_t box[2] = {64, 128};
    encode(enc, &P.tm_act, p_act, 2, dims, str, box, CU_TENSOR_MAP_SWIZZLE_128B);
  }
  {
    const cuuint64_t dims[5] = {D, 2, 4, 4, F / 32}, str[4] = {D * 2, 8 * D * 2, 2 * D * 2, 32 * D * 2};
    const cuuint32_t box[5] = {64, 2, 4, 4, 2};
    encode(enc, &P.tm_w2, P.w2, 5, dims, str, box, CU_TENSOR_MAP_SWIZZLE_128B);
  }
  {
    const cuuint64_t dims[3] = {256, 4, S}, str[2] = {512, D * 2};
    const cuuint32_t box[3] = {32, 4, 128};
    encode(enc, &P.tm_hres, p_h, 3, dims, str, box, CU_TENSOR_MAP_SWIZZLE_64B);
  }
  fused_kernel<<<NCTA, NTHREADS, SMEM_BYTES>>>(P);
}
```

```cpp
#include <cuda_runtime.h>
#include <cuda_bf16.h>
#include <cuda.h>
#include <stdint.h>

#define DBG_TS 0

namespace {

constexpr int S = 2048, D = 1024, F = 3584;
constexpr int NCTA = 128, NTHREADS = 384;

constexpr int UT_COPY = 1040 * 4;
constexpr int UT_SIZE = 2 * UT_COPY;
constexpr int KT_SIZE = 16 + 4096;
constexpr int T_SIZE = 2 * (UT_SIZE + KT_SIZE);
constexpr int KV_STAGE = 17 * 8 * 32;
constexpr int KV_SIZE = 8 * KV_STAGE;
constexpr int YW = 4096 + 96;
constexpr int YBUF = 4 * YW;
constexpr int OFF_T3 = 196608 - T_SIZE;
constexpr int OFF_KVB = (OFF_T3 - KV_SIZE) & ~127;
constexpr int OFF_T2 = OFF_KVB - T_SIZE;
constexpr int OFF_KVA = (OFF_T2 - KV_SIZE) & ~127;
constexpr int OFF_T1 = OFF_KVA - T_SIZE;
constexpr int OFF_T0 = OFF_T1 - T_SIZE;
constexpr int OFF_X = 196608;
constexpr int OFF_CSB2 = OFF_X + 32768;
constexpr int OFF_RED = OFF_X + 34304;
constexpr int OFF_BAR = OFF_X + 34816;
constexpr int SMEM_BYTES = 232448;
static_assert(OFF_T0 >= 0 && 2 * YBUF <= KV_SIZE && 2 * YBUF <= 34304, "smem map");
static_assert(OFF_T2 >= 98304, "stage 1 must only overlap T0,T1,KVA");
static_assert(OFF_T3 >= 147456, "stage 2 must not overlap T3");

enum {
  B_KVFULL = 0, B_KFULL = 8, B_UFULL = 16, B_YFULL = 24, B_ZDONE = 28, B_FULL1 = 32, B_EMPTY1 = 36,
  B_FULL2 = 40, B_EMPTY2 = 46, B_CSFULL = 52, B_HRES = 53, B_ADONE = 54, B_COUNT = 56
};

struct Params {
  CUtensorMap tm_k, tm_v, tm_h, tm_w1, tm_act, tm_w2, tm_hres, tm_out;
  const __nv_bfloat16 *x, *shift_k, *ssm_k, *ssm_D, *w1, *b1, *w2, *b2;
};

__device__ __align__(1024) uint32_t g_z[4 * NCTA * S];
__device__ __align__(1024) __nv_bfloat16 g_h[S * D];
__device__ __align__(1024) __nv_bfloat16 g_act[S * F];
__device__ __align__(128) float2 g_hstat[S];
__device__ __align__(128) float g_cs[F];
__device__ __align__(128) uint32_t g_hcnt[4 * 16 * 32];
__device__ __align__(128) uint32_t g_acnt[2 * 16 * 32];
__device__ __align__(128) uint32_t g_ccnt[8 * 32];
__device__ __align__(128) uint32_t g_epoch[NCTA];
#define TS(slot) do {} while (0)

template<int N> __device__ __forceinline__ void wgmma_rs(float* d, const uint32_t* a, uint64_t db, int sc);
template<int N> __device__ __forceinline__ void wgmma_ss(float* d, uint64_t da, uint64_t db, int sc);
template<> __device__ __forceinline__ void wgmma_rs<16>(float* d, const uint32_t* a, uint64_t db, int sc) {
  asm volatile("{.reg .pred p; setp.ne.b32 p, %13, 0;\n"
  "wgmma.mma_async.sync.aligned.m64n16k16.f32.bf16.bf16 {%0,%1,%2,%3,%4,%5,%6,%7}, {%8,%9,%10,%11}, %12, p, 1, 1, 0;}\n"
  : "+f"(d[0]),"+f"(d[1]),"+f"(d[2]),"+f"(d[3]),"+f"(d[4]),"+f"(d[5]),"+f"(d[6]),"+f"(d[7])
  : "r"(a[0]), "r"(a[1]), "r"(a[2]), "r"(a[3]), "l"(db), "r"(sc));
}
template<> __device__ __forceinline__ void wgmma_rs<32>(float* d, const uint32_t* a, uint64_t db, int sc) {
  asm volatile("{.reg .pred p; setp.ne.b32 p, %21, 0;\n"
  "wgmma.mma_async.sync.aligned.m64n32k16.f32.bf16.bf16 {%0,%1,%2,%3,%4,%5,%6,%7,%8,%9,%10,%11,%12,%13,%14,%15}, {%16,%17,%18,%19}, %20, p, 1, 1, 0;}\n"
  : "+f"(d[0]),"+f"(d[1]),"+f"(d[2]),"+f"(d[3]),"+f"(d[4]),"+f"(d[5]),"+f"(d[6]),"+f"(d[7]),"+f"(d[8]),"+f"(d[9]),"+f"(d[10]),"+f"(d[11]),"+f"(d[12]),"+f"(d[13]),"+f"(d[14]),"+f"(d[15])
  : "r"(a[0]), "r"(a[1]), "r"(a[2]), "r"(a[3]), "l"(db), "r"(sc));
}
template<> __device__ __forceinline__ void wgmma_rs<48>(float* d, const uint32_t* a, uint64_t db, int sc) {
  asm volatile("{.reg .pred p; setp.ne.b32 p, %29, 0;\n"
  "wgmma.mma_async.sync.aligned.m64n48k16.f32.bf16.bf16 {%0,%1,%2,%3,%4,%5,%6,%7,%8,%9,%10,%11,%12,%13,%14,%15,%16,%17,%18,%19,%20,%21,%22,%23}, {%24,%25,%26,%27}, %28, p, 1, 1, 0;}\n"
  : "+f"(d[0]),"+f"(d[1]),"+f"(d[2]),"+f"(d[3]),"+f"(d[4]),"+f"(d[5]),"+f"(d[6]),"+f"(d[7]),"+f"(d[8]),"+f"(d[9]),"+f"(d[10]),"+f"(d[11]),"+f"(d[12]),"+f"(d[13]),"+f"(d[14]),"+f"(d[15]),"+f"(d[16]),"+f"(d[17]),"+f"(d[18]),"+f"(d[19]),"+f"(d[20]),"+f"(d[21]),"+f"(d[22]),"+f"(d[23])
  : "r"(a[0]), "r"(a[1]), "r"(a[2]), "r"(a[3]), "l"(db), "r"(sc));
}
template<> __device__ __forceinline__ void wgmma_rs<64>(float* d, const uint32_t* a, uint64_t db, int sc) {
  asm volatile("{.reg .pred p; setp.ne.b32 p, %37, 0;\n"
  "wgmma.mma_async.sync.aligned.m64n64k16.f32.bf16.bf16 {%0,%1,%2,%3,%4,%5,%6,%7,%8,%9,%10,%11,%12,%13,%14,%15,%16,%17,%18,%19,%20,%21,%22,%23,%24,%25,%26,%27,%28,%29,%30,%31}, {%32,%33,%34,%35}, %36, p, 1, 1, 0;}\n"
  : "+f"(d[0]),"+f"(d[1]),"+f"(d[2]),"+f"(d[3]),"+f"(d[4]),"+f"(d[5]),"+f"(d[6]),"+f"(d[7]),"+f"(d[8]),"+f"(d[9]),"+f"(d[10]),"+f"(d[11]),"+f"(d[12]),"+f"(d[13]),"+f"(d[14]),"+f"(d[15]),"+f"(d[16]),"+f"(d[17]),"+f"(d[18]),"+f"(d[19]),"+f"(d[20]),"+f"(d[21]),"+f"(d[22]),"+f"(d[23]),"+f"(d[24]),"+f"(d[25]),"+f"(d[26]),"+f"(d[27]),"+f"(d[28]),"+f"(d[29]),"+f"(d[30]),"+f"(d[31])
  : "r"(a[0]), "r"(a[1]), "r"(a[2]), "r"(a[3]), "l"(db), "r"(sc));
}
template<> __device__ __forceinline__ void wgmma_rs<80>(float* d, const uint32_t* a, uint64_t db, int sc) {
  asm volatile("{.reg .pred p; setp.ne.b32 p, %45, 0;\n"
  "wgmma.mma_async.sync.aligned.m64n80k16.f32.bf16.bf16 {%0,%1,%2,%3,%4,%5,%6,%7,%8,%9,%10,%11,%12,%13,%14,%15,%16,%17,%18,%19,%20,%21,%22,%23,%24,%25,%26,%27,%28,%29,%30,%31,%32,%33,%34,%35,%36,%37,%38,%39}, {%40,%41,%42,%43}, %44, p, 1, 1, 0;}\n"
  : "+f"(d[0]),"+f"(d[1]),"+f"(d[2]),"+f"(d[3]),"+f"(d[4]),"+f"(d[5]),"+f"(d[6]),"+f"(d[7]),"+f"(d[8]),"+f"(d[9]),"+f"(d[10]),"+f"(d[11]),"+f"(d[12]),"+f"(d[13]),"+f"(d[14]),"+f"(d[15]),"+f"(d[16]),"+f"(d[17]),"+f"(d[18]),"+f"(d[19]),"+f"(d[20]),"+f"(d[21]),"+f"(d[22]),"+f"(d[23]),"+f"(d[24]),"+f"(d[25]),"+f"(d[26]),"+f"(d[27]),"+f"(d[28]),"+f"(d[29]),"+f"(d[30]),"+f"(d[31]),"+f"(d[32]),"+f"(d[33]),"+f"(d[34]),"+f"(d[35]),"+f"(d[36]),"+f"(d[37]),"+f"(d[38]),"+f"(d[39])
  : "r"(a[0]), "r"(a[1]), "r"(a[2]), "r"(a[3]), "l"(db), "r"(sc));
}
template<> __device__ __forceinline__ void wgmma_rs<96>(float* d, const uint32_t* a, uint64_t db, int sc) {
  asm volatile("{.reg .pred p; setp.ne.b32 p, %53, 0;\n"
  "wgmma.mma_async.sync.aligned.m64n96k16.f32.bf16.bf16 {%0,%1,%2,%3,%4,%5,%6,%7,%8,%9,%10,%11,%12,%13,%14,%15,%16,%17,%18,%19,%20,%21,%22,%23,%24,%25,%26,%27,%28,%29,%30,%31,%32,%33,%34,%35,%36,%37,%38,%39,%40,%41,%42,%43,%44,%45,%46,%47}, {%48,%49,%50,%51}, %52, p, 1, 1, 0;}\n"
  : "+f"(d[0]),"+f"(d[1]),"+f"(d[2]),"+f"(d[3]),"+f"(d[4]),"+f"(d[5]),"+f"(d[6]),"+f"(d[7]),"+f"(d[8]),"+f"(d[9]),"+f"(d[10]),"+f"(d[11]),"+f"(d[12]),"+f"(d[13]),"+f"(d[14]),"+f"(d[15]),"+f"(d[16]),"+f"(d[17]),"+f"(d[18]),"+f"(d[19]),"+f"(d[20]),"+f"(d[21]),"+f"(d[22]),"+f"(d[23]),"+f"(d[24]),"+f"(d[25]),"+f"(d[26]),"+f"(d[27]),"+f"(d[28]),"+f"(d[29]),"+f"(d[30]),"+f"(d[31]),"+f"(d[32]),"+f"(d[33]),"+f"(d[34]),"+f"(d[35]),"+f"(d[36]),"+f"(d[37]),"+f"(d[38]),"+f"(d[39]),"+f"(d[40]),"+f"(d[41]),"+f"(d[42]),"+f"(d[43]),"+f"(d[44]),"+f"(d[45]),"+f"(d[46]),"+f"(d[47])
  : "r"(a[0]), "r"(a[1]), "r"(a[2]), "r"(a[3]), "l"(db), "r"(sc));
}
template<> __device__ __forceinline__ void wgmma_rs<112>(float* d, const uint32_t* a, uint64_t db, int sc) {
  asm volatile("{.reg .pred p; setp.ne.b32 p, %61, 0;\n"
  "wgmma.mma_async.sync.aligned.m64n112k16.f32.bf16.bf16 {%0,%1,%2,%3,%4,%5,%6,%7,%8,%9,%10,%11,%12,%13,%14,%15,%16,%17,%18,%19,%20,%21,%22,%23,%24,%25,%26,%27,%28,%29,%30,%31,%32,%33,%34,%35,%36,%37,%38,%39,%40,%41,%42,%43,%44,%45,%46,%47,%48,%49,%50,%51,%52,%53,%54,%55}, {%56,%57,%58,%59}, %60, p, 1, 1, 0;}\n"
  : "+f"(d[0]),"+f"(d[1]),"+f"(d[2]),"+f"(d[3]),"+f"(d[4]),"+f"(d[5]),"+f"(d[6]),"+f"(d[7]),"+f"(d[8]),"+f"(d[9]),"+f"(d[10]),"+f"(d[11]),"+f"(d[12]),"+f"(d[13]),"+f"(d[14]),"+f"(d[15]),"+f"(d[16]),"+f"(d[17]),"+f"(d[18]),"+f"(d[19]),"+f"(d[20]),"+f"(d[21]),"+f"(d[22]),"+f"(d[23]),"+f"(d[24]),"+f"(d[25]),"+f"(d[26]),"+f"(d[27]),"+f"(d[28]),"+f"(d[29]),"+f"(d[30]),"+f"(d[31]),"+f"(d[32]),"+f"(d[33]),"+f"(d[34]),"+f"(d[35]),"+f"(d[36]),"+f"(d[37]),"+f"(d[38]),"+f"(d[39]),"+f"(d[40]),"+f"(d[41]),"+f"(d[42]),"+f"(d[43]),"+f"(d[44]),"+f"(d[45]),"+f"(d[46]),"+f"(d[47]),"+f"(d[48]),"+f"(d[49]),"+f"(d[50]),"+f"(d[51]),"+f"(d[52]),"+f"(d[53]),"+f"(d[54]),"+f"(d[55])
  : "r"(a[0]), "r"(a[1]), "r"(a[2]), "r"(a[3]), "l"(db), "r"(sc));
}
template<> __device__ __forceinline__ void wgmma_rs<128>(float* d, const uint32_t* a, uint64_t db, int sc) {
  asm volatile("{.reg .pred p; setp.ne.b32 p, %69, 0;\n"
  "wgmma.mma_async.sync.aligned.m64n128k16.f32.bf16.bf16 {%0,%1,%2,%3,%4,%5,%6,%7,%8,%9,%10,%11,%12,%13,%14,%15,%16,%17,%18,%19,%20,%21,%22,%23,%24,%25,%26,%27,%28,%29,%30,%31,%32,%33,%34,%35,%36,%37,%38,%39,%40,%41,%42,%43,%44,%45,%46,%47,%48,%49,%50,%51,%52,%53,%54,%55,%56,%57,%58,%59,%60,%61,%62,%63}, {%64,%65,%66,%67}, %68, p, 1, 1, 0;}\n"
  : "+f"(d[0]),"+f"(d[1]),"+f"(d[2]),"+f"(d[3]),"+f"(d[4]),"+f"(d[5]),"+f"(d[6]),"+f"(d[7]),"+f"(d[8]),"+f"(d[9]),"+f"(d[10]),"+f"(d[11]),"+f"(d[12]),"+f"(d[13]),"+f"(d[14]),"+f"(d[15]),"+f"(d[16]),"+f"(d[17]),"+f"(d[18]),"+f"(d[19]),"+f"(d[20]),"+f"(d[21]),"+f"(d[22]),"+f"(d[23]),"+f"(d[24]),"+f"(d[25]),"+f"(d[26]),"+f"(d[27]),"+f"(d[28]),"+f"(d[29]),"+f"(d[30]),"+f"(d[31]),"+f"(d[32]),"+f"(d[33]),"+f"(d[34]),"+f"(d[35]),"+f"(d[36]),"+f"(d[37]),"+f"(d[38]),"+f"(d[39]),"+f"(d[40]),"+f"(d[41]),"+f"(d[42]),"+f"(d[43]),"+f"(d[44]),"+f"(d[45]),"+f"(d[46]),"+f"(d[47]),"+f"(d[48]),"+f"(d[49]),"+f"(d[50]),"+f"(d[51]),"+f"(d[52]),"+f"(d[53]),"+f"(d[54]),"+f"(d[55]),"+f"(d[56]),"+f"(d[57]),"+f"(d[58]),"+f"(d[59]),"+f"(d[60]),"+f"(d[61]),"+f"(d[62]),"+f"(d[63])
  : "r"(a[0]), "r"(a[1]), "r"(a[2]), "r"(a[3]), "l"(db), "r"(sc));
}
template<> __device__ __forceinline__ void wgmma_rs<144>(float* d, const uint32_t* a, uint64_t db, int sc) {
  asm volatile("{.reg .pred p; setp.ne.b32 p, %77, 0;\n"
  "wgmma.mma_async.sync.aligned.m64n144k16.f32.bf16.bf16 {%0,%1,%2,%3,%4,%5,%6,%7,%8,%9,%10,%11,%12,%13,%14,%15,%16,%17,%18,%19,%20,%21,%22,%23,%24,%25,%26,%27,%28,%29,%30,%31,%32,%33,%34,%35,%36,%37,%38,%39,%40,%41,%42,%43,%44,%45,%46,%47,%48,%49,%50,%51,%52,%53,%54,%55,%56,%57,%58,%59,%60,%61,%62,%63,%64,%65,%66,%67,%68,%69,%70,%71}, {%72,%73,%74,%75}, %76, p, 1, 1, 0;}\n"
  : "+f"(d[0]),"+f"(d[1]),"+f"(d[2]),"+f"(d[3]),"+f"(d[4]),"+f"(d[5]),"+f"(d[6]),"+f"(d[7]),"+f"(d[8]),"+f"(d[9]),"+f"(d[10]),"+f"(d[11]),"+f"(d[12]),"+f"(d[13]),"+f"(d[14]),"+f"(d[15]),"+f"(d[16]),"+f"(d[17]),"+f"(d[18]),"+f"(d[19]),"+f"(d[20]),"+f"(d[21]),"+f"(d[22]),"+f"(d[23]),"+f"(d[24]),"+f"(d[25]),"+f"(d[26]),"+f"(d[27]),"+f"(d[28]),"+f"(d[29]),"+f"(d[30]),"+f"(d[31]),"+f"(d[32]),"+f"(d[33]),"+f"(d[34]),"+f"(d[35]),"+f"(d[36]),"+f"(d[37]),"+f"(d[38]),"+f"(d[39]),"+f"(d[40]),"+f"(d[41]),"+f"(d[42]),"+f"(d[43]),"+f"(d[44]),"+f"(d[45]),"+f"(d[46]),"+f"(d[47]),"+f"(d[48]),"+f"(d[49]),"+f"(d[50]),"+f"(d[51]),"+f"(d[52]),"+f"(d[53]),"+f"(d[54]),"+f"(d[55]),"+f"(d[56]),"+f"(d[57]),"+f"(d[58]),"+f"(d[59]),"+f"(d[60]),"+f"(d[61]),"+f"(d[62]),"+f"(d[63]),"+f"(d[64]),"+f"(d[65]),"+f"(d[66]),"+f"(d[67]),"+f"(d[68]),"+f"(d[69]),"+f"(d[70]),"+f"(d[71])
  : "r"(a[0]), "r"(a[1]), "r"(a[2]), "r"(a[3]), "l"(db), "r"(sc));
}
template<> __device__ __forceinline__ void wgmma_rs<160>(float* d, const uint32_t* a, uint64_t db, int sc) {
  asm volatile("{.reg .pred p; setp.ne.b32 p, %85, 0;\n"
  "wgmma.mma_async.sync.aligned.m64n160k16.f32.bf16.bf16 {%0,%1,%2,%3,%4,%5,%6,%7,%8,%9,%10,%11,%12,%13,%14,%15,%16,%17,%18,%19,%20,%21,%22,%23,%24,%25,%26,%27,%28,%29,%30,%31,%32,%33,%34,%35,%36,%37,%38,%39,%40,%41,%42,%43,%44,%45,%46,%47,%48,%49,%50,%51,%52,%53,%54,%55,%56,%57,%58,%59,%60,%61,%62,%63,%64,%65,%66,%67,%68,%69,%70,%71,%72,%73,%74,%75,%76,%77,%78,%79}, {%80,%81,%82,%83}, %84, p, 1, 1, 0;}\n"
  : "+f"(d[0]),"+f"(d[1]),"+f"(d[2]),"+f"(d[3]),"+f"(d[4]),"+f"(d[5]),"+f"(d[6]),"+f"(d[7]),"+f"(d[8]),"+f"(d[9]),"+f"(d[10]),"+f"(d[11]),"+f"(d[12]),"+f"(d[13]),"+f"(d[14]),"+f"(d[15]),"+f"(d[16]),"+f"(d[17]),"+f"(d[18]),"+f"(d[19]),"+f"(d[20]),"+f"(d[21]),"+f"(d[22]),"+f"(d[23]),"+f"(d[24]),"+f"(d[25]),"+f"(d[26]),"+f"(d[27]),"+f"(d[28]),"+f"(d[29]),"+f"(d[30]),"+f"(d[31]),"+f"(d[32]),"+f"(d[33]),"+f"(d[34]),"+f"(d[35]),"+f"(d[36]),"+f"(d[37]),"+f"(d[38]),"+f"(d[39]),"+f"(d[40]),"+f"(d[41]),"+f"(d[42]),"+f"(d[43]),"+f"(d[44]),"+f"(d[45]),"+f"(d[46]),"+f"(d[47]),"+f"(d[48]),"+f"(d[49]),"+f"(d[50]),"+f"(d[51]),"+f"(d[52]),"+f"(d[53]),"+f"(d[54]),"+f"(d[55]),"+f"(d[56]),"+f"(d[57]),"+f"(d[58]),"+f"(d[59]),"+f"(d[60]),"+f"(d[61]),"+f"(d[62]),"+f"(d[63]),"+f"(d[64]),"+f"(d[65]),"+f"(d[66]),"+f"(d[67]),"+f"(d[68]),"+f"(d[69]),"+f"(d[70]),"+f"(d[71]),"+f"(d[72]),"+f"(d[73]),"+f"(d[74]),"+f"(d[75]),"+f"(d[76]),"+f"(d[77]),"+f"(d[78]),"+f"(d[79])
  : "r"(a[0]), "r"(a[1]), "r"(a[2]), "r"(a[3]), "l"(db), "r"(sc));
}
template<> __device__ __forceinline__ void wgmma_rs<176>(float* d, const uint32_t* a, uint64_t db, int sc) {
  asm volatile("{.reg .pred p; setp.ne.b32 p, %93, 0;\n"
  "wgmma.mma_async.sync.aligned.m64n176k16.f32.bf16.bf16 {%0,%1,%2,%3,%4,%5,%6,%7,%8,%9,%10,%11,%12,%13,%14,%15,%16,%17,%18,%19,%20,%21,%22,%23,%24,%25,%26,%27,%28,%29,%30,%31,%32,%33,%34,%35,%36,%37,%38,%39,%40,%41,%42,%43,%44,%45,%46,%47,%48,%49,%50,%51,%52,%53,%54,%55,%56,%57,%58,%59,%60,%61,%62,%63,%64,%65,%66,%67,%68,%69,%70,%71,%72,%73,%74,%75,%76,%77,%78,%79,%80,%81,%82,%83,%84,%85,%86,%87}, {%88,%89,%90,%91}, %92, p, 1, 1, 0;}\n"
  : "+f"(d[0]),"+f"(d[1]),"+f"(d[2]),"+f"(d[3]),"+f"(d[4]),"+f"(d[5]),"+f"(d[6]),"+f"(d[7]),"+f"(d[8]),"+f"(d[9]),"+f"(d[10]),"+f"(d[11]),"+f"(d[12]),"+f"(d[13]),"+f"(d[14]),"+f"(d[15]),"+f"(d[16]),"+f"(d[17]),"+f"(d[18]),"+f"(d[19]),"+f"(d[20]),"+f"(d[21]),"+f"(d[22]),"+f"(d[23]),"+f"(d[24]),"+f"(d[25]),"+f"(d[26]),"+f"(d[27]),"+f"(d[28]),"+f"(d[29]),"+f"(d[30]),"+f"(d[31]),"+f"(d[32]),"+f"(d[33]),"+f"(d[34]),"+f"(d[35]),"+f"(d[36]),"+f"(d[37]),"+f"(d[38]),"+f"(d[39]),"+f"(d[40]),"+f"(d[41]),"+f"(d[42]),"+f"(d[43]),"+f"(d[44]),"+f"(d[45]),"+f"(d[46]),"+f"(d[47]),"+f"(d[48]),"+f"(d[49]),"+f"(d[50]),"+f"(d[51]),"+f"(d[52]),"+f"(d[53]),"+f"(d[54]),"+f"(d[55]),"+f"(d[56]),"+f"(d[57]),"+f"(d[58]),"+f"(d[59]),"+f"(d[60]),"+f"(d[61]),"+f"(d[62]),"+f"(d[63]),"+f"(d[64]),"+f"(d[65]),"+f"(d[66]),"+f"(d[67]),"+f"(d[68]),"+f"(d[69]),"+f"(d[70]),"+f"(d[71]),"+f"(d[72]),"+f"(d[73]),"+f"(d[74]),"+f"(d[75]),"+f"(d[76]),"+f"(d[77]),"+f"(d[78]),"+f"(d[79]),"+f"(d[80]),"+f"(d[81]),"+f"(d[82]),"+f"(d[83]),"+f"(d[84]),"+f"(d[85]),"+f"(d[86]),"+f"(d[87])
  : "r"(a[0]), "r"(a[1]), "r"(a[2]), "r"(a[3]), "l"(db), "r"(sc));
}
template<> __device__ __forceinline__ void wgmma_rs<192>(float* d, const uint32_t* a, uint64_t db, int sc) {
  asm volatile("{.reg .pred p; setp.ne.b32 p, %101, 0;\n"
  "wgmma.mma_async.sync.aligned.m64n192k16.f32.bf16.bf16 {%0,%1,%2,%3,%4,%5,%6,%7,%8,%9,%10,%11,%12,%13,%14,%15,%16,%17,%18,%19,%20,%21,%22,%23,%24,%25,%26,%27,%28,%29,%30,%31,%32,%33,%34,%35,%36,%37,%38,%39,%40,%41,%42,%43,%44,%45,%46,%47,%48,%49,%50,%51,%52,%53,%54,%55,%56,%57,%58,%59,%60,%61,%62,%63,%64,%65,%66,%67,%68,%69,%70,%71,%72,%73,%74,%75,%76,%77,%78,%79,%80,%81,%82,%83,%84,%85,%86,%87,%88,%89,%90,%91,%92,%93,%94,%95}, {%96,%97,%98,%99}, %100, p, 1, 1, 0;}\n"
  : "+f"(d[0]),"+f"(d[1]),"+f"(d[2]),"+f"(d[3]),"+f"(d[4]),"+f"(d[5]),"+f"(d[6]),"+f"(d[7]),"+f"(d[8]),"+f"(d[9]),"+f"(d[10]),"+f"(d[11]),"+f"(d[12]),"+f"(d[13]),"+f"(d[14]),"+f"(d[15]),"+f"(d[16]),"+f"(d[17]),"+f"(d[18]),"+f"(d[19]),"+f"(d[20]),"+f"(d[21]),"+f"(d[22]),"+f"(d[23]),"+f"(d[24]),"+f"(d[25]),"+f"(d[26]),"+f"(d[27]),"+f"(d[28]),"+f"(d[29]),"+f"(d[30]),"+f"(d[31]),"+f"(d[32]),"+f"(d[33]),"+f"(d[34]),"+f"(d[35]),"+f"(d[36]),"+f"(d[37]),"+f"(d[38]),"+f"(d[39]),"+f"(d[40]),"+f"(d[41]),"+f"(d[42]),"+f"(d[43]),"+f"(d[44]),"+f"(d[45]),"+f"(d[46]),"+f"(d[47]),"+f"(d[48]),"+f"(d[49]),"+f"(d[50]),"+f"(d[51]),"+f"(d[52]),"+f"(d[53]),"+f"(d[54]),"+f"(d[55]),"+f"(d[56]),"+f"(d[57]),"+f"(d[58]),"+f"(d[59]),"+f"(d[60]),"+f"(d[61]),"+f"(d[62]),"+f"(d[63]),"+f"(d[64]),"+f"(d[65]),"+f"(d[66]),"+f"(d[67]),"+f"(d[68]),"+f"(d[69]),"+f"(d[70]),"+f"(d[71]),"+f"(d[72]),"+f"(d[73]),"+f"(d[74]),"+f"(d[75]),"+f"(d[76]),"+f"(d[77]),"+f"(d[78]),"+f"(d[79]),"+f"(d[80]),"+f"(d[81]),"+f"(d[82]),"+f"(d[83]),"+f"(d[84]),"+f"(d[85]),"+f"(d[86]),"+f"(d[87]),"+f"(d[88]),"+f"(d[89]),"+f"(d[90]),"+f"(d[91]),"+f"(d[92]),"+f"(d[93]),"+f"(d[94]),"+f"(d[95])
  : "r"(a[0]), "r"(a[1]), "r"(a[2]), "r"(a[3]), "l"(db), "r"(sc));
}
template<> __device__ __forceinline__ void wgmma_rs<208>(float* d, const uint32_t* a, uint64_t db, int sc) {
  asm volatile("{.reg .pred p; setp.ne.b32 p, %109, 0;\n"
  "wgmma.mma_async.sync.aligned.m64n208k16.f32.bf16.bf16 {%0,%1,%2,%3,%4,%5,%6,%7,%8,%9,%10,%11,%12,%13,%14,%15,%16,%17,%18,%19,%20,%21,%22,%23,%24,%25,%26,%27,%28,%29,%30,%31,%32,%33,%34,%35,%36,%37,%38,%39,%40,%41,%42,%43,%44,%45,%46,%47,%48,%49,%50,%51,%52,%53,%54,%55,%56,%57,%58,%59,%60,%61,%62,%63,%64,%65,%66,%67,%68,%69,%70,%71,%72,%73,%74,%75,%76,%77,%78,%79,%80,%81,%82,%83,%84,%85,%86,%87,%88,%89,%90,%91,%92,%93,%94,%95,%96,%97,%98,%99,%100,%101,%102,%103}, {%104,%105,%106,%107}, %108, p, 1, 1, 0;}\n"
  : "+f"(d[0]),"+f"(d[1]),"+f"(d[2]),"+f"(d[3]),"+f"(d[4]),"+f"(d[5]),"+f"(d[6]),"+f"(d[7]),"+f"(d[8]),"+f"(d[9]),"+f"(d[10]),"+f"(d[11]),"+f"(d[12]),"+f"(d[13]),"+f"(d[14]),"+f"(d[15]),"+f"(d[16]),"+f"(d[17]),"+f"(d[18]),"+f"(d[19]),"+f"(d[20]),"+f"(d[21]),"+f"(d[22]),"+f"(d[23]),"+f"(d[24]),"+f"(d[25]),"+f"(d[26]),"+f"(d[27]),"+f"(d[28]),"+f"(d[29]),"+f"(d[30]),"+f"(d[31]),"+f"(d[32]),"+f"(d[33]),"+f"(d[34]),"+f"(d[35]),"+f"(d[36]),"+f"(d[37]),"+f"(d[38]),"+f"(d[39]),"+f"(d[40]),"+f"(d[41]),"+f"(d[42]),"+f"(d[43]),"+f"(d[44]),"+f"(d[45]),"+f"(d[46]),"+f"(d[47]),"+f"(d[48]),"+f"(d[49]),"+f"(d[50]),"+f"(d[51]),"+f"(d[52]),"+f"(d[53]),"+f"(d[54]),"+f"(d[55]),"+f"(d[56]),"+f"(d[57]),"+f"(d[58]),"+f"(d[59]),"+f"(d[60]),"+f"(d[61]),"+f"(d[62]),"+f"(d[63]),"+f"(d[64]),"+f"(d[65]),"+f"(d[66]),"+f"(d[67]),"+f"(d[68]),"+f"(d[69]),"+f"(d[70]),"+f"(d[71]),"+f"(d[72]),"+f"(d[73]),"+f"(d[74]),"+f"(d[75]),"+f"(d[76]),"+f"(d[77]),"+f"(d[78]),"+f"(d[79]),"+f"(d[80]),"+f"(d[81]),"+f"(d[82]),"+f"(d[83]),"+f"(d[84]),"+f"(d[85]),"+f"(d[86]),"+f"(d[87]),"+f"(d[88]),"+f"(d[89]),"+f"(d[90]),"+f"(d[91]),"+f"(d[92]),"+f"(d[93]),"+f"(d[94]),"+f"(d[95]),"+f"(d[96]),"+f"(d[97]),"+f"(d[98]),"+f"(d[99]),"+f"(d[100]),"+f"(d[101]),"+f"(d[102]),"+f"(d[103])
  : "r"(a[0]), "r"(a[1]), "r"(a[2]), "r"(a[3]), "l"(db), "r"(sc));
}
template<> __device__ __forceinline__ void wgmma_rs<224>(float* d, const uint32_t* a, uint64_t db, int sc) {
  asm volatile("{.reg .pred p; setp.ne.b32 p, %117, 0;\n"
  "wgmma.mma_async.sync.aligned.m64n224k16.f32.bf16.bf16 {%0,%1,%2,%3,%4,%5,%6,%7,%8,%9,%10,%11,%12,%13,%14,%15,%16,%17,%18,%19,%20,%21,%22,%23,%24,%25,%26,%27,%28,%29,%30,%31,%32,%33,%34,%35,%36,%37,%38,%39,%40,%41,%42,%43,%44,%45,%46,%47,%48,%49,%50,%51,%52,%53,%54,%55,%56,%57,%58,%59,%60,%61,%62,%63,%64,%65,%66,%67,%68,%69,%70,%71,%72,%73,%74,%75,%76,%77,%78,%79,%80,%81,%82,%83,%84,%85,%86,%87,%88,%89,%90,%91,%92,%93,%94,%95,%96,%97,%98,%99,%100,%101,%102,%103,%104,%105,%106,%107,%108,%109,%110,%111}, {%112,%113,%114,%115}, %116, p, 1, 1, 0;}\n"
  : "+f"(d[0]),"+f"(d[1]),"+f"(d[2]),"+f"(d[3]),"+f"(d[4]),"+f"(d[5]),"+f"(d[6]),"+f"(d[7]),"+f"(d[8]),"+f"(d[9]),"+f"(d[10]),"+f"(d[11]),"+f"(d[12]),"+f"(d[13]),"+f"(d[14]),"+f"(d[15]),"+f"(d[16]),"+f"(d[17]),"+f"(d[18]),"+f"(d[19]),"+f"(d[20]),"+f"(d[21]),"+f"(d[22]),"+f"(d[23]),"+f"(d[24]),"+f"(d[25]),"+f"(d[26]),"+f"(d[27]),"+f"(d[28]),"+f"(d[29]),"+f"(d[30]),"+f"(d[31]),"+f"(d[32]),"+f"(d[33]),"+f"(d[34]),"+f"(d[35]),"+f"(d[36]),"+f"(d[37]),"+f"(d[38]),"+f"(d[39]),"+f"(d[40]),"+f"(d[41]),"+f"(d[42]),"+f"(d[43]),"+f"(d[44]),"+f"(d[45]),"+f"(d[46]),"+f"(d[47]),"+f"(d[48]),"+f"(d[49]),"+f"(d[50]),"+f"(d[51]),"+f"(d[52]),"+f"(d[53]),"+f"(d[54]),"+f"(d[55]),"+f"(d[56]),"+f"(d[57]),"+f"(d[58]),"+f"(d[59]),"+f"(d[60]),"+f"(d[61]),"+f"(d[62]),"+f"(d[63]),"+f"(d[64]),"+f"(d[65]),"+f"(d[66]),"+f"(d[67]),"+f"(d[68]),"+f"(d[69]),"+f"(d[70]),"+f"(d[71]),"+f"(d[72]),"+f"(d[73]),"+f"(d[74]),"+f"(d[75]),"+f"(d[76]),"+f"(d[77]),"+f"(d[78]),"+f"(d[79]),"+f"(d[80]),"+f"(d[81]),"+f"(d[82]),"+f"(d[83]),"+f"(d[84]),"+f"(d[85]),"+f"(d[86]),"+f"(d[87]),"+f"(d[88]),"+f"(d[89]),"+f"(d[90]),"+f"(d[91]),"+f"(d[92]),"+f"(d[93]),"+f"(d[94]),"+f"(d[95]),"+f"(d[96]),"+f"(d[97]),"+f"(d[98]),"+f"(d[99]),"+f"(d[100]),"+f"(d[101]),"+f"(d[102]),"+f"(d[103]),"+f"(d[104]),"+f"(d[105]),"+f"(d[106]),"+f"(d[107]),"+f"(d[108]),"+f"(d[109]),"+f"(d[110]),"+f"(d[111])
  : "r"(a[0]), "r"(a[1]), "r"(a[2]), "r"(a[3]), "l"(db), "r"(sc));
}
template<> __device__ __forceinline__ void wgmma_rs<240>(float* d, const uint32_t* a, uint64_t db, int sc) {
  asm volatile("{.reg .pred p; setp.ne.b32 p, %125, 0;\n"
  "wgmma.mma_async.sync.aligned.m64n240k16.f32.bf16.bf16 {%0,%1,%2,%3,%4,%5,%6,%7,%8,%9,%10,%11,%12,%13,%14,%15,%16,%17,%18,%19,%20,%21,%22,%23,%24,%25,%26,%27,%28,%29,%30,%31,%32,%33,%34,%35,%36,%37,%38,%39,%40,%41,%42,%43,%44,%45,%46,%47,%48,%49,%50,%51,%52,%53,%54,%55,%56,%57,%58,%59,%60,%61,%62,%63,%64,%65,%66,%67,%68,%69,%70,%71,%72,%73,%74,%75,%76,%77,%78,%79,%80,%81,%82,%83,%84,%85,%86,%87,%88,%89,%90,%91,%92,%93,%94,%95,%96,%97,%98,%99,%100,%101,%102,%103,%104,%105,%106,%107,%108,%109,%110,%111,%112,%113,%114,%115,%116,%117,%118,%119}, {%120,%121,%122,%123}, %124, p, 1, 1, 0;}\n"
  : "+f"(d[0]),"+f"(d[1]),"+f"(d[2]),"+f"(d[3]),"+f"(d[4]),"+f"(d[5]),"+f"(d[6]),"+f"(d[7]),"+f"(d[8]),"+f"(d[9]),"+f"(d[10]),"+f"(d[11]),"+f"(d[12]),"+f"(d[13]),"+f"(d[14]),"+f"(d[15]),"+f"(d[16]),"+f"(d[17]),"+f"(d[18]),"+f"(d[19]),"+f"(d[20]),"+f"(d[21]),"+f"(d[22]),"+f"(d[23]),"+f"(d[24]),"+f"(d[25]),"+f"(d[26]),"+f"(d[27]),"+f"(d[28]),"+f"(d[29]),"+f"(d[30]),"+f"(d[31]),"+f"(d[32]),"+f"(d[33]),"+f"(d[34]),"+f"(d[35]),"+f"(d[36]),"+f"(d[37]),"+f"(d[38]),"+f"(d[39]),"+f"(d[40]),"+f"(d[41]),"+f"(d[42]),"+f"(d[43]),"+f"(d[44]),"+f"(d[45]),"+f"(d[46]),"+f"(d[47]),"+f"(d[48]),"+f"(d[49]),"+f"(d[50]),"+f"(d[51]),"+f"(d[52]),"+f"(d[53]),"+f"(d[54]),"+f"(d[55]),"+f"(d[56]),"+f"(d[57]),"+f"(d[58]),"+f"(d[59]),"+f"(d[60]),"+f"(d[61]),"+f"(d[62]),"+f"(d[63]),"+f"(d[64]),"+f"(d[65]),"+f"(d[66]),"+f"(d[67]),"+f"(d[68]),"+f"(d[69]),"+f"(d[70]),"+f"(d[71]),"+f"(d[72]),"+f"(d[73]),"+f"(d[74]),"+f"(d[75]),"+f"(d[76]),"+f"(d[77]),"+f"(d[78]),"+f"(d[79]),"+f"(d[80]),"+f"(d[81]),"+f"(d[82]),"+f"(d[83]),"+f"(d[84]),"+f"(d[85]),"+f"(d[86]),"+f"(d[87]),"+f"(d[88]),"+f"(d[89]),"+f"(d[90]),"+f"(d[91]),"+f"(d[92]),"+f"(d[93]),"+f"(d[94]),"+f"(d[95]),"+f"(d[96]),"+f"(d[97]),"+f"(d[98]),"+f"(d[99]),"+f"(d[100]),"+f"(d[101]),"+f"(d[102]),"+f"(d[103]),"+f"(d[104]),"+f"(d[105]),"+f"(d[106]),"+f"(d[107]),"+f"(d[108]),"+f"(d[109]),"+f"(d[110]),"+f"(d[111]),"+f"(d[112]),"+f"(d[113]),"+f"(d[114]),"+f"(d[115]),"+f"(d[116]),"+f"(d[117]),"+f"(d[118]),"+f"(d[119])
  : "r"(a[0]), "r"(a[1]), "r"(a[2]), "r"(a[3]), "l"(db), "r"(sc));
}
template<> __device__ __forceinline__ void wgmma_rs<256>(float* d, const uint32_t* a, uint64_t db, int sc) {
  asm volatile("{.reg .pred p; setp.ne.b32 p, %133, 0;\n"
  "wgmma.mma_async.sync.aligned.m64n256k16.f32.bf16.bf16 {%0,%1,%2,%3,%4,%5,%6,%7,%8,%9,%10,%11,%12,%13,%14,%15,%16,%17,%18,%19,%20,%21,%22,%23,%24,%25,%26,%27,%28,%29,%30,%31,%32,%33,%34,%35,%36,%37,%38,%39,%40,%41,%42,%43,%44,%45,%46,%47,%48,%49,%50,%51,%52,%53,%54,%55,%56,%57,%58,%59,%60,%61,%62,%63,%64,%65,%66,%67,%68,%69,%70,%71,%72,%73,%74,%75,%76,%77,%78,%79,%80,%81,%82,%83,%84,%85,%86,%87,%88,%89,%90,%91,%92,%93,%94,%95,%96,%97,%98,%99,%100,%101,%102,%103,%104,%105,%106,%107,%108,%109,%110,%111,%112,%113,%114,%115,%116,%117,%118,%119,%120,%121,%122,%123,%124,%125,%126,%127}, {%128,%129,%130,%131}, %132, p, 1, 1, 0;}\n"
  : "+f"(d[0]),"+f"(d[1]),"+f"(d[2]),"+f"(d[3]),"+f"(d[4]),"+f"(d[5]),"+f"(d[6]),"+f"(d[7]),"+f"(d[8]),"+f"(d[9]),"+f"(d[10]),"+f"(d[11]),"+f"(d[12]),"+f"(d[13]),"+f"(d[14]),"+f"(d[15]),"+f"(d[16]),"+f"(d[17]),"+f"(d[18]),"+f"(d[19]),"+f"(d[20]),"+f"(d[21]),"+f"(d[22]),"+f"(d[23]),"+f"(d[24]),"+f"(d[25]),"+f"(d[26]),"+f"(d[27]),"+f"(d[28]),"+f"(d[29]),"+f"(d[30]),"+f"(d[31]),"+f"(d[32]),"+f"(d[33]),"+f"(d[34]),"+f"(d[35]),"+f"(d[36]),"+f"(d[37]),"+f"(d[38]),"+f"(d[39]),"+f"(d[40]),"+f"(d[41]),"+f"(d[42]),"+f"(d[43]),"+f"(d[44]),"+f"(d[45]),"+f"(d[46]),"+f"(d[47]),"+f"(d[48]),"+f"(d[49]),"+f"(d[50]),"+f"(d[51]),"+f"(d[52]),"+f"(d[53]),"+f"(d[54]),"+f"(d[55]),"+f"(d[56]),"+f"(d[57]),"+f"(d[58]),"+f"(d[59]),"+f"(d[60]),"+f"(d[61]),"+f"(d[62]),"+f"(d[63]),"+f"(d[64]),"+f"(d[65]),"+f"(d[66]),"+f"(d[67]),"+f"(d[68]),"+f"(d[69]),"+f"(d[70]),"+f"(d[71]),"+f"(d[72]),"+f"(d[73]),"+f"(d[74]),"+f"(d[75]),"+f"(d[76]),"+f"(d[77]),"+f"(d[78]),"+f"(d[79]),"+f"(d[80]),"+f"(d[81]),"+f"(d[82]),"+f"(d[83]),"+f"(d[84]),"+f"(d[85]),"+f"(d[86]),"+f"(d[87]),"+f"(d[88]),"+f"(d[89]),"+f"(d[90]),"+f"(d[91]),"+f"(d[92]),"+f"(d[93]),"+f"(d[94]),"+f"(d[95]),"+f"(d[96]),"+f"(d[97]),"+f"(d[98]),"+f"(d[99]),"+f"(d[100]),"+f"(d[101]),"+f"(d[102]),"+f"(d[103]),"+f"(d[104]),"+f"(d[105]),"+f"(d[106]),"+f"(d[107]),"+f"(d[108]),"+f"(d[109]),"+f"(d[110]),"+f"(d[111]),"+f"(d[112]),"+f"(d[113]),"+f"(d[114]),"+f"(d[115]),"+f"(d[116]),"+f"(d[117]),"+f"(d[118]),"+f"(d[119]),"+f"(d[120]),"+f"(d[121]),"+f"(d[122]),"+f"(d[123]),"+f"(d[124]),"+f"(d[125]),"+f"(d[126]),"+f"(d[127])
  : "r"(a[0]), "r"(a[1]), "r"(a[2]), "r"(a[3]), "l"(db), "r"(sc));
}
template<> __device__ __forceinline__ void wgmma_ss<128>(float* d, uint64_t da, uint64_t db, int sc) {
  asm volatile("{.reg .pred p; setp.ne.b32 p, %66, 0;\n"
  "wgmma.mma_async.sync.aligned.m64n128k16.f32.bf16.bf16 {%0,%1,%2,%3,%4,%5,%6,%7,%8,%9,%10,%11,%12,%13,%14,%15,%16,%17,%18,%19,%20,%21,%22,%23,%24,%25,%26,%27,%28,%29,%30,%31,%32,%33,%34,%35,%36,%37,%38,%39,%40,%41,%42,%43,%44,%45,%46,%47,%48,%49,%50,%51,%52,%53,%54,%55,%56,%57,%58,%59,%60,%61,%62,%63}, %64, %65, p, 1, 1, 0, 1;}\n"
  : "+f"(d[0]),"+f"(d[1]),"+f"(d[2]),"+f"(d[3]),"+f"(d[4]),"+f"(d[5]),"+f"(d[6]),"+f"(d[7]),"+f"(d[8]),"+f"(d[9]),"+f"(d[10]),"+f"(d[11]),"+f"(d[12]),"+f"(d[13]),"+f"(d[14]),"+f"(d[15]),"+f"(d[16]),"+f"(d[17]),"+f"(d[18]),"+f"(d[19]),"+f"(d[20]),"+f"(d[21]),"+f"(d[22]),"+f"(d[23]),"+f"(d[24]),"+f"(d[25]),"+f"(d[26]),"+f"(d[27]),"+f"(d[28]),"+f"(d[29]),"+f"(d[30]),"+f"(d[31]),"+f"(d[32]),"+f"(d[33]),"+f"(d[34]),"+f"(d[35]),"+f"(d[36]),"+f"(d[37]),"+f"(d[38]),"+f"(d[39]),"+f"(d[40]),"+f"(d[41]),"+f"(d[42]),"+f"(d[43]),"+f"(d[44]),"+f"(d[45]),"+f"(d[46]),"+f"(d[47]),"+f"(d[48]),"+f"(d[49]),"+f"(d[50]),"+f"(d[51]),"+f"(d[52]),"+f"(d[53]),"+f"(d[54]),"+f"(d[55]),"+f"(d[56]),"+f"(d[57]),"+f"(d[58]),"+f"(d[59]),"+f"(d[60]),"+f"(d[61]),"+f"(d[62]),"+f"(d[63])
  : "l"(da), "l"(db), "r"(sc));
}
template<> __device__ __forceinline__ void wgmma_ss<192>(float* d, uint64_t da, uint64_t db, int sc) {
  asm volatile("{.reg .pred p; setp.ne.b32 p, %98, 0;\n"
  "wgmma.mma_async.sync.aligned.m64n192k16.f32.bf16.bf16 {%0,%1,%2,%3,%4,%5,%6,%7,%8,%9,%10,%11,%12,%13,%14,%15,%16,%17,%18,%19,%20,%21,%22,%23,%24,%25,%26,%27,%28,%29,%30,%31,%32,%33,%34,%35,%36,%37,%38,%39,%40,%41,%42,%43,%44,%45,%46,%47,%48,%49,%50,%51,%52,%53,%54,%55,%56,%57,%58,%59,%60,%61,%62,%63,%64,%65,%66,%67,%68,%69,%70,%71,%72,%73,%74,%75,%76,%77,%78,%79,%80,%81,%82,%83,%84,%85,%86,%87,%88,%89,%90,%91,%92,%93,%94,%95}, %96, %97, p, 1, 1, 0, 1;}\n"
  : "+f"(d[0]),"+f"(d[1]),"+f"(d[2]),"+f"(d[3]),"+f"(d[4]),"+f"(d[5]),"+f"(d[6]),"+f"(d[7]),"+f"(d[8]),"+f"(d[9]),"+f"(d[10]),"+f"(d[11]),"+f"(d[12]),"+f"(d[13]),"+f"(d[14]),"+f"(d[15]),"+f"(d[16]),"+f"(d[17]),"+f"(d[18]),"+f"(d[19]),"+f"(d[20]),"+f"(d[21]),"+f"(d[22]),"+f"(d[23]),"+f"(d[24]),"+f"(d[25]),"+f"(d[26]),"+f"(d[27]),"+f"(d[28]),"+f"(d[29]),"+f"(d[30]),"+f"(d[31]),"+f"(d[32]),"+f"(d[33]),"+f"(d[34]),"+f"(d[35]),"+f"(d[36]),"+f"(d[37]),"+f"(d[38]),"+f"(d[39]),"+f"(d[40]),"+f"(d[41]),"+f"(d[42]),"+f"(d[43]),"+f"(d[44]),"+f"(d[45]),"+f"(d[46]),"+f"(d[47]),"+f"(d[48]),"+f"(d[49]),"+f"(d[50]),"+f"(d[51]),"+f"(d[52]),"+f"(d[53]),"+f"(d[54]),"+f"(d[55]),"+f"(d[56]),"+f"(d[57]),"+f"(d[58]),"+f"(d[59]),"+f"(d[60]),"+f"(d[61]),"+f"(d[62]),"+f"(d[63]),"+f"(d[64]),"+f"(d[65]),"+f"(d[66]),"+f"(d[67]),"+f"(d[68]),"+f"(d[69]),"+f"(d[70]),"+f"(d[71]),"+f"(d[72]),"+f"(d[73]),"+f"(d[74]),"+f"(d[75]),"+f"(d[76]),"+f"(d[77]),"+f"(d[78]),"+f"(d[79]),"+f"(d[80]),"+f"(d[81]),"+f"(d[82]),"+f"(d[83]),"+f"(d[84]),"+f"(d[85]),"+f"(d[86]),"+f"(d[87]),"+f"(d[88]),"+f"(d[89]),"+f"(d[90]),"+f"(d[91]),"+f"(d[92]),"+f"(d[93]),"+f"(d[94]),"+f"(d[95])
  : "l"(da), "l"(db), "r"(sc));
}
template<> __device__ __forceinline__ void wgmma_ss<256>(float* d, uint64_t da, uint64_t db, int sc) {
  asm volatile("{.reg .pred p; setp.ne.b32 p, %130, 0;\n"
  "wgmma.mma_async.sync.aligned.m64n256k16.f32.bf16.bf16 {%0,%1,%2,%3,%4,%5,%6,%7,%8,%9,%10,%11,%12,%13,%14,%15,%16,%17,%18,%19,%20,%21,%22,%23,%24,%25,%26,%27,%28,%29,%30,%31,%32,%33,%34,%35,%36,%37,%38,%39,%40,%41,%42,%43,%44,%45,%46,%47,%48,%49,%50,%51,%52,%53,%54,%55,%56,%57,%58,%59,%60,%61,%62,%63,%64,%65,%66,%67,%68,%69,%70,%71,%72,%73,%74,%75,%76,%77,%78,%79,%80,%81,%82,%83,%84,%85,%86,%87,%88,%89,%90,%91,%92,%93,%94,%95,%96,%97,%98,%99,%100,%101,%102,%103,%104,%105,%106,%107,%108,%109,%110,%111,%112,%113,%114,%115,%116,%117,%118,%119,%120,%121,%122,%123,%124,%125,%126,%127}, %128, %129, p, 1, 1, 0, 1;}\n"
  : "+f"(d[0]),"+f"(d[1]),"+f"(d[2]),"+f"(d[3]),"+f"(d[4]),"+f"(d[5]),"+f"(d[6]),"+f"(d[7]),"+f"(d[8]),"+f"(d[9]),"+f"(d[10]),"+f"(d[11]),"+f"(d[12]),"+f"(d[13]),"+f"(d[14]),"+f"(d[15]),"+f"(d[16]),"+f"(d[17]),"+f"(d[18]),"+f"(d[19]),"+f"(d[20]),"+f"(d[21]),"+f"(d[22]),"+f"(d[23]),"+f"(d[24]),"+f"(d[25]),"+f"(d[26]),"+f"(d[27]),"+f"(d[28]),"+f"(d[29]),"+f"(d[30]),"+f"(d[31]),"+f"(d[32]),"+f"(d[33]),"+f"(d[34]),"+f"(d[35]),"+f"(d[36]),"+f"(d[37]),"+f"(d[38]),"+f"(d[39]),"+f"(d[40]),"+f"(d[41]),"+f"(d[42]),"+f"(d[43]),"+f"(d[44]),"+f"(d[45]),"+f"(d[46]),"+f"(d[47]),"+f"(d[48]),"+f"(d[49]),"+f"(d[50]),"+f"(d[51]),"+f"(d[52]),"+f"(d[53]),"+f"(d[54]),"+f"(d[55]),"+f"(d[56]),"+f"(d[57]),"+f"(d[58]),"+f"(d[59]),"+f"(d[60]),"+f"(d[61]),"+f"(d[62]),"+f"(d[63]),"+f"(d[64]),"+f"(d[65]),"+f"(d[66]),"+f"(d[67]),"+f"(d[68]),"+f"(d[69]),"+f"(d[70]),"+f"(d[71]),"+f"(d[72]),"+f"(d[73]),"+f"(d[74]),"+f"(d[75]),"+f"(d[76]),"+f"(d[77]),"+f"(d[78]),"+f"(d[79]),"+f"(d[80]),"+f"(d[81]),"+f"(d[82]),"+f"(d[83]),"+f"(d[84]),"+f"(d[85]),"+f"(d[86]),"+f"(d[87]),"+f"(d[88]),"+f"(d[89]),"+f"(d[90]),"+f"(d[91]),"+f"(d[92]),"+f"(d[93]),"+f"(d[94]),"+f"(d[95]),"+f"(d[96]),"+f"(d[97]),"+f"(d[98]),"+f"(d[99]),"+f"(d[100]),"+f"(d[101]),"+f"(d[102]),"+f"(d[103]),"+f"(d[104]),"+f"(d[105]),"+f"(d[106]),"+f"(d[107]),"+f"(d[108]),"+f"(d[109]),"+f"(d[110]),"+f"(d[111]),"+f"(d[112]),"+f"(d[113]),"+f"(d[114]),"+f"(d[115]),"+f"(d[116]),"+f"(d[117]),"+f"(d[118]),"+f"(d[119]),"+f"(d[120]),"+f"(d[121]),"+f"(d[122]),"+f"(d[123]),"+f"(d[124]),"+f"(d[125]),"+f"(d[126]),"+f"(d[127])
  : "l"(da), "l"(db), "r"(sc));
}

__device__ __forceinline__ void wg_fence() { asm volatile("wgmma.fence.sync.aligned;" ::: "memory"); }
__device__ __forceinline__ void wg_commit() { asm volatile("wgmma.commit_group.sync.aligned;" ::: "memory"); }
template <int N> __device__ __forceinline__ void wg_wait() { asm volatile("wgmma.wait_group.sync.aligned %0;" ::"n"(N) : "memory"); }
__device__ __forceinline__ uint64_t mkdesc(uint32_t addr, uint32_t lbo, uint32_t sbo, uint32_t swz) {
  return (uint64_t)((addr & 0x3FFFF) >> 4) | ((uint64_t)(lbo >> 4) << 16) | ((uint64_t)(sbo >> 4) << 32) | ((uint64_t)swz << 62);
}
__device__ __forceinline__ void mbar_init(uint32_t a, uint32_t c) { asm volatile("mbarrier.init.shared.b64 [%0], %1;" ::"r"(a), "r"(c) : "memory"); }
__device__ __forceinline__ void mbar_expect_tx(uint32_t a, uint32_t b) { asm volatile("mbarrier.arrive.expect_tx.shared.b64 _, [%0], %1;" ::"r"(a), "r"(b) : "memory"); }
__device__ __forceinline__ void mbar_arrive(uint32_t a) { asm volatile("mbarrier.arrive.shared.b64 _, [%0];" ::"r"(a) : "memory"); }
__device__ __forceinline__ void mbar_wait(uint32_t a, uint32_t parity) {
  uint32_t done;
  int it = 0;
  do {
    asm volatile("{.reg .pred p; mbarrier.try_wait.parity.shared.b64 p, [%1], %2; selp.u32 %0,1,0,p;}" : "=r"(done) : "r"(a), "r"(parity) : "memory");
    if (++it > (1 << 20)) __trap();
  } while (!done);
}
__device__ __forceinline__ void tma2d(uint32_t dst, const CUtensorMap* m, uint32_t bar, int c0, int c1) {
  asm volatile("cp.async.bulk.tensor.2d.shared::cluster.global.mbarrier::complete_tx::bytes [%0], [%1, {%3,%4}], [%2];"
               ::"r"(dst), "l"(m), "r"(bar), "r"(c0), "r"(c1) : "memory");
}
__device__ __forceinline__ void tma3d(uint32_t dst, const CUtensorMap* m, uint32_t bar, int c0, int c1, int c2) {
  asm volatile("cp.async.bulk.tensor.3d.shared::cluster.global.mbarrier::complete_tx::bytes [%0], [%1, {%3,%4,%5}], [%2];"
               ::"r"(dst), "l"(m), "r"(bar), "r"(c0), "r"(c1), "r"(c2) : "memory");
}
__device__ __forceinline__ void tma5d(uint32_t dst, const CUtensorMap* m, uint32_t bar, int c0, int c4) {
  asm volatile("cp.async.bulk.tensor.5d.shared::cluster.global.mbarrier::complete_tx::bytes [%0], [%1, {%3,%5,%5,%5,%4}], [%2];"
               ::"r"(dst), "l"(m), "r"(bar), "r"(c0), "r"(c4), "r"(0) : "memory");
}
__device__ __forceinline__ void bulk_g2s(uint32_t dst, const void* src, uint32_t bytes, uint32_t bar) {
  asm volatile("cp.async.bulk.shared::cluster.global.mbarrier::complete_tx::bytes [%0], [%1], %2, [%3];"
               ::"r"(dst), "l"(src), "r"(bytes), "r"(bar) : "memory");
}
__device__ __forceinline__ void prefetch_l2(const void* src, uint32_t bytes) {
  asm volatile("cp.async.bulk.prefetch.L2.global [%0], %1;" ::"l"(src), "r"(bytes) : "memory");
}
__device__ __forceinline__ void prefetch_tmap(const CUtensorMap* m) { asm volatile("prefetch.tensormap [%0];" ::"l"(m) : "memory"); }
__device__ __forceinline__ void fence_async_smem() { asm volatile("fence.proxy.async.shared::cta;" ::: "memory"); }
__device__ __forceinline__ void fence_async_global() { asm volatile("fence.proxy.async.global;" ::: "memory"); }
__device__ __forceinline__ void bar_sync(int id, int n) { asm volatile("bar.sync %0, %1;" ::"r"(id), "r"(n) : "memory"); }
__device__ __forceinline__ uint32_t lds32(uint32_t a) { uint32_t v; asm volatile("ld.volatile.shared.b32 %0,[%1];" : "=r"(v) : "r"(a)); return v; }
__device__ __forceinline__ uint2 lds64(uint32_t a) { uint2 v; asm volatile("ld.shared.v2.b32 {%0,%1},[%2];" : "=r"(v.x), "=r"(v.y) : "r"(a) : "memory"); return v; }
__device__ __forceinline__ uint4 lds128(uint32_t a) { uint4 v; asm volatile("ld.shared.v4.b32 {%0,%1,%2,%3},[%4];" : "=r"(v.x), "=r"(v.y), "=r"(v.z), "=r"(v.w) : "r"(a) : "memory"); return v; }
__device__ __forceinline__ float4 lds128f(uint32_t a) { float4 v; asm volatile("ld.shared.v4.f32 {%0,%1,%2,%3},[%4];" : "=f"(v.x), "=f"(v.y), "=f"(v.z), "=f"(v.w) : "r"(a) : "memory"); return v; }
__device__ __forceinline__ void sts128(uint32_t a, uint32_t x, uint32_t y, uint32_t z, uint32_t w) { asm volatile("st.shared.v4.b32 [%0],{%1,%2,%3,%4};" ::"r"(a), "r"(x), "r"(y), "r"(z), "r"(w) : "memory"); }
__device__ __forceinline__ uint32_t packbf(float lo, float hi) { uint32_t r; asm("cvt.rn.bf16x2.f32 %0, %1, %2;" : "=r"(r) : "f"(hi), "f"(lo)); return r; }
__device__ __forceinline__ uint32_t packbf_relu(float lo, float hi) { uint32_t r; asm("cvt.rn.relu.bf16x2.f32 %0, %1, %2;" : "=r"(r) : "f"(hi), "f"(lo)); return r; }
__device__ __forceinline__ uint32_t bmul2(uint32_t a, uint32_t b) { uint32_t r; asm("mul.rn.bf16x2 %0, %1, %2;" : "=r"(r) : "r"(a), "r"(b)); return r; }
__device__ __forceinline__ uint32_t bfma2(uint32_t a, uint32_t b, uint32_t c) { uint32_t r; asm("fma.rn.bf16x2 %0, %1, %2, %3;" : "=r"(r) : "r"(a), "r"(b), "r"(c)); return r; }
__device__ __forceinline__ float bflo(uint32_t v) { return __uint_as_float(v << 16); }
__device__ __forceinline__ float bfhi(uint32_t v) { return __uint_as_float(v & 0xffff0000u); }
__device__ __forceinline__ uint32_t ldg_relaxed(const uint32_t* p) { uint32_t v; asm volatile("ld.relaxed.gpu.global.b32 %0,[%1];" : "=r"(v) : "l"(p) : "memory"); return v; }
__device__ __forceinline__ void stg128(void* p, uint32_t x, uint32_t y, uint32_t z, uint32_t w) { asm volatile("st.global.v4.b32 [%0],{%1,%2,%3,%4};" ::"l"(p), "r"(x), "r"(y), "r"(z), "r"(w) : "memory"); }
__device__ __forceinline__ void stg64(void* p, uint32_t x, uint32_t y) { asm volatile("st.global.v2.b32 [%0],{%1,%2};" ::"l"(p), "r"(x), "r"(y) : "memory"); }
__device__ __forceinline__ uint4 ldg_relaxed4(const uint32_t* p) { uint4 v; asm volatile("ld.relaxed.gpu.global.v4.b32 {%0,%1,%2,%3},[%4];" : "=r"(v.x), "=r"(v.y), "=r"(v.z), "=r"(v.w) : "l"(p) : "memory"); return v; }
__device__ __forceinline__ void stg_relaxed4(uint32_t* p, uint32_t x, uint32_t y, uint32_t z, uint32_t w) { asm volatile("st.relaxed.gpu.global.v4.b32 [%0],{%1,%2,%3,%4};" ::"l"(p), "r"(x), "r"(y), "r"(z), "r"(w) : "memory"); }
__device__ __forceinline__ void signal(uint32_t* cnt) { asm volatile("red.release.gpu.global.add.u32 [%0], 1;" ::"l"(cnt) : "memory"); }
__device__ __forceinline__ void wait_count(const uint32_t* cnt, uint32_t target) {
  int it = 0;
  while (true) {
    uint32_t v;
    asm volatile("ld.acquire.gpu.global.b32 %0,[%1];" : "=r"(v) : "l"(cnt) : "memory");
    if ((int)(v - target) >= 0) break;
    __nanosleep(32);
    if (++it > (1 << 21)) __trap();
  }
}
__device__ __forceinline__ void mbar_wait_cluster(uint32_t a, uint32_t parity) {
  uint32_t done;
  int it = 0;
  do {
    asm volatile("{.reg .pred p; mbarrier.try_wait.parity.acquire.cluster.shared::cta.b64 p, [%1], %2; selp.u32 %0,1,0,p;}" : "=r"(done) : "r"(a), "r"(parity) : "memory");
    if (++it > (1 << 20)) __trap();
  } while (!done);
}
__device__ __forceinline__ void st_async128(uint32_t a, uint32_t bar, uint32_t x, uint32_t y, uint32_t z, uint32_t w) {
  asm volatile("st.async.weak.shared::cluster.mbarrier::complete_tx::bytes.v4.b32 [%0],{%2,%3,%4,%5},[%1];" ::"r"(a), "r"(bar), "r"(x), "r"(y), "r"(z), "r"(w) : "memory");
}

template <int LO, int HI> __device__ __forceinline__ void rename(float* d) {
#pragma unroll
  for (int i = LO; i < HI; i++) { float e; asm volatile("mov.b32 %0, %1;" : "=f"(e) : "f"(d[i])); d[i] = e; }
}
template <int M> __device__ __forceinline__ void drain4(const float* d, uint32_t ya) {
  uint32_t r[4];
#pragma unroll
  for (int q = 0; q < 4; q++) {
    const int mu = M + q;
    float v0 = d[4 * mu], v1 = d[4 * mu + 1];
    if (mu > 0) { v0 += d[4 * mu - 2]; v1 += d[4 * mu - 1]; }
    r[q] = packbf(v0, v1);
  }
  asm volatile("stmatrix.sync.aligned.m8n8.x4.trans.shared.b16 [%0],{%1,%2,%3,%4};" ::"r"(ya + M * 128), "r"(r[0]), "r"(r[1]), "r"(r[2]), "r"(r[3]) : "memory");
}
__device__ __forceinline__ void lda(uint32_t* a, uint32_t ua) { a[0] = lds32(ua); a[1] = lds32(ua + 128); a[2] = lds32(ua - 16); a[3] = lds32(ua + 112); }
template <int P> struct Pass {
  static __device__ __forceinline__ void run(float* d, uint32_t (*a)[4], uint32_t ua, uint64_t db, uint32_t ya, uint32_t ubar, bool first) {
    if constexpr (P > 0) rename<8 * (P - 1), 128>(d);
    wg_fence();
    wgmma_rs<256 - 16 * P>(d + 8 * P, a[P & 1], db, P != 0);
    wg_commit();
    if constexpr (P < 15) {
      if constexpr (P & 1) { if (first) mbar_wait_cluster(ubar + 8 * ((P + 1) / 2), 0); }
      lda(a[(P + 1) & 1], ua + (P + 1) * 256);
    }
    if constexpr (P >= 2 && (P & 1) == 0) drain4<2 * P - 4>(d, ya);
    wg_wait<0>();
    if constexpr (P < 15) Pass<P + 1>::run(d, a, ua, db, ya, ubar, first);
    else { rename<120, 128>(d); drain4<28>(d, ya); }
  }
};

__device__ __forceinline__ uint32_t off_T(int r) { return r == 0 ? OFF_T0 : r == 1 ? OFF_T1 : r == 2 ? OFF_T2 : OFF_T3; }
__device__ __forceinline__ uint32_t off_Y(int r) { return r == 1 ? OFF_KVA : r == 2 ? OFF_KVB : OFF_X; }

template <int NT>
__device__ __forceinline__ void gemm1_tile(uint32_t sb, int tile, int wg, int w, int lane, int row0, int n0, uint32_t csb) {
  const uint32_t bar = sb + OFF_BAR;
  float acc[NT / 2];
  const bool elect = (threadIdx.x & 127) == 0;
#pragma unroll 1
  for (int kb = 0; kb < 16; kb++) {
    const int s = kb & 3;
    mbar_wait(bar + 8 * (B_FULL1 + s), (kb >> 2) & 1);
    const uint32_t sa = sb + s * 49152;
    const uint64_t da = mkdesc(sa + wg * 8192, 16, 1024, 1), db = mkdesc(sa + 16384, 8192, 1024, 1);
    wg_fence();
#pragma unroll
    for (int kk = 0; kk < 4; kk++) wgmma_ss<NT>(acc, da + kk * 2, db + kk * 128, (kb | kk) != 0);
    wg_commit();
    wg_wait<1>();
    if (kb > 0 && elect) mbar_arrive(bar + 8 * (B_EMPTY1 + ((kb - 1) & 3)));
  }
  const int g = lane >> 2, t = lane & 3;
  const int r0 = row0 + 64 * wg + 16 * w + g;
  float2 st0, st1;
  asm volatile("ld.global.cg.v2.f32 {%0,%1},[%2];" : "=f"(st0.x), "=f"(st0.y) : "l"(g_hstat + r0) : "memory");
  asm volatile("ld.global.cg.v2.f32 {%0,%1},[%2];" : "=f"(st1.x), "=f"(st1.y) : "l"(g_hstat + r0 + 8) : "memory");
  if (tile == 0) mbar_wait(bar + 8 * B_CSFULL, 0);
  wg_wait<0>();
  rename<0, NT / 2>(acc);
  if (elect) mbar_arrive(bar + 8 * (B_EMPTY1 + 3));
  __nv_bfloat16* p0 = g_act + (size_t)r0 * F + n0 + 8 * t;
  __nv_bfloat16* p1 = p0 + 8 * F;
#pragma unroll
  for (int J = 0; J < NT / 32; J++) {
    uint32_t o0[4], o1[4];
#pragma unroll
    for (int jj = 0; jj < 4; jj++) {
      const int mu = 4 * J + jj;
      const float4 c = lds128f(csb + (4 * mu + t) * 16);
      const float a0 = fmaf(acc[4 * mu + 0], st0.y, fmaf(st0.x, c.x, c.z));
      const float a1 = fmaf(acc[4 * mu + 1], st0.y, fmaf(st0.x, c.y, c.w));
      const float a2 = fmaf(acc[4 * mu + 2], st1.y, fmaf(st1.x, c.x, c.z));
      const float a3 = fmaf(acc[4 * mu + 3], st1.y, fmaf(st1.x, c.y, c.w));
      const uint32_t u0 = packbf_relu(a0, a1), u1 = packbf_relu(a2, a3);
      o0[jj] = bmul2(u0, u0);
      o1[jj] = bmul2(u1, u1);
    }
    stg128(p0 + 32 * J, o0[0], o0[1], o0[2], o0[3]);
    stg128(p1 + 32 * J, o1[0], o1[1], o1[2], o1[3]);
  }
  fence_async_global();
  __syncwarp();
  if (lane == 0) mbar_arrive(bar + 8 * (B_ADONE + tile));
}

__global__ void __cluster_dims__(2, 1, 1) __launch_bounds__(NTHREADS, 1) fused_kernel(const __grid_constant__ Params P) {
  extern __shared__ __align__(1024) unsigned char smem[];
  const uint32_t sb = (uint32_t)__cvta_generic_to_shared(smem);
  const uint32_t bar = sb + OFF_BAR;
  const int tid = threadIdx.x, warp = tid >> 5, lane = tid & 31;
  const int c = blockIdx.x, m = c & 15, j = c >> 4;

  if (tid == 256) {
    TS(0);
    prefetch_tmap(&P.tm_k); prefetch_tmap(&P.tm_v);
    for (int i = 0; i < 8; i++) { mbar_init(bar + 8 * (B_KVFULL + i), 1); mbar_init(bar + 8 * (B_KFULL + i), 2); mbar_init(bar + 8 * (B_UFULL + i), 1); }
    for (int i = 0; i < 4; i++) { mbar_init(bar + 8 * (B_YFULL + i), 8); mbar_init(bar + 8 * (B_ZDONE + i), 3); mbar_init(bar + 8 * (B_FULL1 + i), 1); mbar_init(bar + 8 * (B_EMPTY1 + i), 2); }
    for (int i = 0; i < 6; i++) { mbar_init(bar + 8 * (B_FULL2 + i), 1); mbar_init(bar + 8 * (B_EMPTY2 + i), 2); }
    mbar_init(bar + 8 * B_CSFULL, 3); mbar_init(bar + 8 * B_HRES, 1);
    mbar_init(bar + 8 * B_ADONE, 8); mbar_init(bar + 8 * (B_ADONE + 1), 8);
    for (int i = 0; i < 8; i++) mbar_expect_tx(bar + 8 * (B_UFULL + i), 8192);
    asm volatile("fence.mbarrier_init.release.cluster;" ::: "memory");
    fence_async_smem();
    for (int i = 0; i < 2; i++) {
      mbar_expect_tx(bar + 8 * (B_KVFULL + i), 2 * KV_STAGE);
      tma3d(sb + OFF_KVA + i * KV_STAGE, &P.tm_k, bar + 8 * (B_KVFULL + i), 8 * (c & ~1), 32 * i + 16 * (c & 1) - 1, 0);
      tma3d(sb + OFF_KVB + i * KV_STAGE, &P.tm_v, bar + 8 * (B_KVFULL + i), 8 * (c & ~1), 32 * i + 16 * (c & 1) - 1, 0);
      mbar_expect_tx(bar + 8 * (B_KFULL + i), 4080);
      bulk_g2s(sb + OFF_T0 + 2 * UT_SIZE + i * KT_SIZE + 32, P.ssm_k + (size_t)(8 * c + i) * S + 8, 4080, bar + 8 * (B_KFULL + i));
    }
  }
  if (tid < 16) sts128(sb + off_T(tid >> 2) + (tid & 3) * UT_COPY, 0, 0, 0, 0);
  __syncthreads();
  asm volatile("barrier.cluster.arrive.relaxed.aligned;" ::: "memory");

  if (warp < 8) {
    asm volatile("barrier.cluster.wait.aligned;" ::: "memory");
    const int wg = warp >> 2, w = warp & 3, g = lane >> 2, t = lane & 3;
#pragma unroll 1
    for (int r = 0; r < 4; r++) {
      float d[128];
      uint32_t a[2][4];
      const uint32_t tb = sb + off_T(r);
      const uint32_t ua = tb + wg * UT_SIZE + ((g & 1) ? 0 : UT_COPY) + ((g >> 1) + 8 * w + 8 - t) * 4;
      const uint64_t db = mkdesc(tb + 2 * UT_SIZE + wg * KT_SIZE, 16, 128, 0);
      const uint32_t yb = sb + off_Y(r) + wg * YBUF + w * YW;
      if (r == 3) mbar_wait(bar + 8 * B_ZDONE, 0);
      if (lane < 2 * w) sts128(yb + lane * 16, 0, 0, 0, 0);
      mbar_wait(bar + 8 * (B_KFULL + 2 * r + wg), 0);
      if (r == 0) mbar_wait_cluster(bar + 8 * B_UFULL, 0);
      if (tid == 0) TS(1 + r);
      lda(a[0], ua);
      Pass<0>::run(d, a, ua, db, yb + (2 * w + lane) * 16, bar + 8 * B_UFULL, r == 0);
      __syncwarp();
      if (lane == 0) mbar_arrive(bar + 8 * (B_YFULL + r));
    }
    if (tid == 0) TS(5);
    gemm1_tile<256>(sb, 0, wg, w, lane, 128 * m, 448 * j, sb + OFF_X);
    if (tid == 0) TS(6);
    gemm1_tile<192>(sb, 1, wg, w, lane, 128 * m, 448 * j + 256, sb + OFF_CSB2);
    if (tid == 0) TS(7);
    {
      float acc[64], res[64];
      const bool elect = (tid & 127) == 0;
      int s = 0, ph = 0, prev = 0;
#pragma unroll 1
      for (int kb = 0; kb < 56; kb++) {
        mbar_wait(bar + 8 * (B_FULL2 + s), ph);
        const uint32_t sa = sb + s * 32768;
        const uint64_t da = mkdesc(sa + wg * 8192, 16, 1024, 1), db = mkdesc(sa + 16384, 8192, 1024, 1);
        wg_fence();
#pragma unroll
        for (int kk = 0; kk < 4; kk++) wgmma_ss<128>(acc, da + kk * 2, db + kk * 128, (kb | kk) != 0);
        wg_commit();
        if (kb == 8) {
          mbar_wait(bar + 8 * B_HRES, 0);
          const uint32_t* b2p = (const uint32_t*)(P.b2 + 128 * j) + t;
#pragma unroll
          for (int h = 0; h < 2; h++) {
            const int row = 64 * wg + 16 * w + 8 * h + g;
            const uint32_t la = sb + OFF_X + row * 256 + t * 64;
            const int sw = (2 * row + (t >> 1)) & 3;
#pragma unroll
            for (int cc = 0; cc < 4; cc++) {
              const uint4 v = lds128(la + ((cc ^ sw) << 4));
              const uint32_t vv[4] = {v.x, v.y, v.z, v.w};
#pragma unroll
              for (int q = 0; q < 4; q++) {
                const int mu = 4 * cc + q;
                const uint32_t b = __ldg(b2p + 4 * mu);
                res[4 * mu + 2 * h] = bflo(vv[q]) + bflo(b);
                res[4 * mu + 2 * h + 1] = bfhi(vv[q]) + bfhi(b);
              }
            }
          }
        }
        wg_wait<1>();
        if (kb > 0 && elect) mbar_arrive(bar + 8 * (B_EMPTY2 + prev));
        prev = s;
        if (++s == 6) { s = 0; ph ^= 1; }
      }
      wg_wait<0>();
      rename<0, 64>(acc);
      if (tid == 0) TS(8);
      const int id = lane >> 3, row = 16 * w + (lane & 7) + 8 * (id & 1);
      const uint32_t ob = sb + OFF_X + wg * 16384 + row * 128;
#pragma unroll
      for (int mu = 0; mu < 16; mu += 2) {
        const uint32_t r0 = packbf(acc[4 * mu] + res[4 * mu], acc[4 * mu + 1] + res[4 * mu + 1]);
        const uint32_t r1 = packbf(acc[4 * mu + 2] + res[4 * mu + 2], acc[4 * mu + 3] + res[4 * mu + 3]);
        const uint32_t r2 = packbf(acc[4 * mu + 4] + res[4 * mu + 4], acc[4 * mu + 5] + res[4 * mu + 5]);
        const uint32_t r3 = packbf(acc[4 * mu + 6] + res[4 * mu + 6], acc[4 * mu + 7] + res[4 * mu + 7]);
        const int ch = (mu & 7) + (id >> 1);
        asm volatile("stmatrix.sync.aligned.m8n8.x4.shared.b16 [%0],{%1,%2,%3,%4};"
                     ::"r"(ob + (mu >> 3) * 8192 + ((ch ^ (row & 7)) << 4)), "r"(r0), "r"(r1), "r"(r2), "r"(r3) : "memory");
      }
      fence_async_smem();
      bar_sync(3 + wg, 128);
      if (elect) {
        for (int b = 0; b < 2; b++)
          asm volatile("cp.async.bulk.tensor.2d.global.shared::cta.bulk_group [%0, {%2,%3}], [%1];"
                       ::"l"(&P.tm_out), "r"(sb + OFF_X + wg * 16384 + b * 8192), "r"(128 * j + 64 * b), "r"(128 * m + 64 * wg) : "memory");
        asm volatile("cp.async.bulk.commit_group;" ::: "memory");
        asm volatile("cp.async.bulk.wait_group.read 0;" ::: "memory");
        if (tid == 0) TS(9);
      }
    }
  } else {
    const uint32_t epoch = ldg_relaxed(g_epoch + c) + 1;
    if (warp == 8) {
      if (lane == 0) {
        for (int i = 2; i < 8; i++) {
          mbar_expect_tx(bar + 8 * (B_KVFULL + i), 2 * KV_STAGE);
          tma3d(sb + OFF_KVA + i * KV_STAGE, &P.tm_k, bar + 8 * (B_KVFULL + i), 8 * (c & ~1), 32 * i + 16 * (c & 1) - 1, 0);
          tma3d(sb + OFF_KVB + i * KV_STAGE, &P.tm_v, bar + 8 * (B_KVFULL + i), 8 * (c & ~1), 32 * i + 16 * (c & 1) - 1, 0);
        }
        for (int ch = 2; ch < 8; ch++) {
          if (ch == 4) prefetch_l2(P.x + (size_t)(128 * m + 16 * j) * D, 16 * D * 2);
          mbar_expect_tx(bar + 8 * (B_KFULL + ch), 4080);
          bulk_g2s(sb + off_T(ch >> 1) + 2 * UT_SIZE + (ch & 1) * KT_SIZE + 32, P.ssm_k + (size_t)(8 * c + ch) * S + 8, 4080, bar + 8 * (B_KFULL + ch));
        }
      }
      asm volatile("barrier.cluster.wait.aligned;" ::: "memory");
      if (lane == 0) {
        prefetch_tmap(&P.tm_h); prefetch_tmap(&P.tm_w1); prefetch_tmap(&P.tm_act); prefetch_tmap(&P.tm_w2);
        prefetch_tmap(&P.tm_hres); prefetch_tmap(&P.tm_out);
        mbar_wait(bar + 8 * (B_KVFULL + 7), 0);
        TS(10);
        mbar_wait(bar + 8 * (B_KFULL + 7), 0);
        TS(31);
        prefetch_l2(P.w1 + (size_t)c * 8 * F, 8 * F * 2);
#pragma unroll 1
        for (int it = 0; it < 32; it++) {
          const int s = it & 3, kb = it & 15, tile = it >> 4;
          if (it == 0) mbar_wait(bar + 8 * (B_ZDONE + 1), 0);
          else if (it == 2) mbar_wait(bar + 8 * (B_ZDONE + 2), 0);
          else if (it == 3) mbar_wait(bar + 8 * (B_YFULL + 3), 0);
          else if (it >= 4) mbar_wait(bar + 8 * (B_EMPTY1 + s), ((it >> 2) - 1) & 1);
          if (it < 4) fence_async_smem();
          const uint32_t sa = sb + s * 49152, fb = bar + 8 * (B_FULL1 + s);
          const int nb = tile ? 3 : 4, n0 = 448 * j + 256 * tile;
          mbar_expect_tx(fb, 16384 + nb * 8192);
          for (int i = 0; i < nb; i++) tma3d(sa + 16384 + i * 8192, &P.tm_w1, fb, n0 + 64 * i, 2 * (kb >> 2), 32 * (kb & 3));
          if (it < 16 && (it & 3) == 0) { wait_count(g_hcnt + ((it >> 2) * 16 + m) * 32, epoch * 24); fence_async_global(); TS(11 + (it >> 2)); }
          tma2d(sa, &P.tm_h, fb, 64 * kb, 128 * m);
          if (it == 8) prefetch_l2(P.w2 + (size_t)c * 28 * D, 28 * D * 2);
          if (it == 21) {
            mbar_expect_tx(bar + 8 * B_HRES, 32768);
            tma3d(sb + OFF_X, &P.tm_hres, bar + 8 * B_HRES, 32 * j, 0, 128 * m);
          }
        }
        int s = 0, ph = 1;
#pragma unroll 1
        for (int kb = 0; kb < 56; kb++) {
          if (kb < 6) { if (kb != 2 && kb != 5) mbar_wait(bar + 8 * (B_EMPTY1 + (2 * kb + 1) / 3), 1); }
          else mbar_wait(bar + 8 * (B_EMPTY2 + s), ph);
          const int col = kb < 32 ? 448 * (kb >> 2) + 64 * (kb & 3) : 448 * ((kb - 32) / 3) + 256 + 64 * ((kb - 32) % 3);
          const uint32_t sa = sb + s * 32768, fb = bar + 8 * (B_FULL2 + s);
          mbar_expect_tx(fb, 32768);
          tma5d(sa + 16384, &P.tm_w2, fb, 128 * j, col >> 5);
          tma5d(sa + 24576, &P.tm_w2, fb, 128 * j + 64, col >> 5);
          if ((kb & 31) == 0) { wait_count(g_acnt + ((kb >> 5) * 16 + m) * 32, epoch * 8); fence_async_global(); TS(15 + (kb >> 5)); }
          tma2d(sa, &P.tm_act, fb, col, 128 * m);
          if (++s == 6) { s = 0; ph ^= 1; }
        }
      }
    } else {
      const int zw = warp - 9;
      if (zw == 2 && lane < 8) {
        const int ch = 8 * c + lane;
        uint4 v = __ldg((const uint4*)(P.ssm_k + (size_t)ch * S));
        const float k0 = bflo(v.x) + __bfloat162float(P.ssm_D[ch]);
        v.x = (v.x & 0xffff0000u) | (packbf(k0, 0.f) & 0xffffu);
        const uint32_t kt = sb + off_T(lane >> 1) + 2 * UT_SIZE + (lane & 1) * KT_SIZE;
        sts128(kt, 0, 0, 0, 0);
        sts128(kt + 16, v.x, v.y, v.z, v.w);
        fence_async_smem();
        mbar_arrive(bar + 8 * (B_KFULL + lane));
      }
      {
        uint32_t W[4][4];
        const uint4* wp = (const uint4*)(P.shift_k + (size_t)32 * ((c & ~1) + (lane & 1)));
#pragma unroll
        for (int p = 0; p < 4; p++) {
          const uint4 v = __ldg(wp + p);
          W[0][p] = __byte_perm(v.x, v.z, 0x5410); W[1][p] = __byte_perm(v.x, v.z, 0x7632);
          W[2][p] = __byte_perm(v.y, v.w, 0x5410); W[3][p] = __byte_perm(v.y, v.w, 0x7632);
        }
        uint32_t rb;
        asm volatile("mapa.shared::cluster.u32 %0, %1, %2;" : "=r"(rb) : "r"(sb), "r"(lane & 1));
        asm volatile("barrier.cluster.wait.aligned;" ::: "memory");
#pragma unroll 1
        for (int st = zw; st < 8; st += 3) {
          mbar_wait(bar + 8 * (B_KVFULL + st), 0);
          const uint32_t ka = sb + OFF_KVA + st * KV_STAGE + lane * 16, va = sb + OFF_KVB + st * KV_STAGE + lane * 16;
          uint32_t u[9][4];
          uint4 k3 = lds128(ka + 4 * 544), k2 = lds128(ka + 5 * 544), k1 = lds128(ka + 6 * 544);
#pragma unroll
          for (int i = 0; i < 9; i++) {
            const uint32_t o = i == 0 ? 7 * 544 : (i - 1) * 544 + 32;
            const uint4 k0 = lds128(ka + o), v = lds128(va + o);
            u[i][0] = bmul2(bfma2(k0.x, W[0][0], bfma2(k1.x, W[1][0], bfma2(k2.x, W[2][0], bmul2(k3.x, W[3][0])))), v.x);
            u[i][1] = bmul2(bfma2(k0.y, W[0][1], bfma2(k1.y, W[1][1], bfma2(k2.y, W[2][1], bmul2(k3.y, W[3][1])))), v.y);
            u[i][2] = bmul2(bfma2(k0.z, W[0][2], bfma2(k1.z, W[1][2], bfma2(k2.z, W[2][2], bmul2(k3.z, W[3][2])))), v.z);
            u[i][3] = bmul2(bfma2(k0.w, W[0][3], bfma2(k1.w, W[1][3], bfma2(k2.w, W[2][3], bmul2(k3.w, W[3][3])))), v.w);
            k3 = k2; k2 = k1; k1 = k0;
          }
          const uint32_t ub = rb + OFF_BAR + 8 * (B_UFULL + st);
#pragma unroll
          for (int p = 0; p < 4; p++) {
            const uint32_t ta = rb + off_T(p) + 16 + (32 * st + 16 * (c & 1) + (lane >> 1)) * 16;
#pragma unroll
            for (int e = 0; e < 2; e++) {
              const uint32_t sel = e ? 0x7632 : 0x5410;
              st_async128(ta + e * UT_SIZE, ub, __byte_perm(u[2][p], u[1][p], sel), __byte_perm(u[4][p], u[3][p], sel),
                          __byte_perm(u[6][p], u[5][p], sel), __byte_perm(u[8][p], u[7][p], sel));
              st_async128(ta + e * UT_SIZE + UT_COPY, ub, __byte_perm(u[1][p], u[0][p], sel), __byte_perm(u[3][p], u[2][p], sel),
                          __byte_perm(u[5][p], u[4][p], sel), __byte_perm(u[7][p], u[6][p], sel));
            }
          }
        }
      }
      if (tid == 288) TS(43);
      const int q = lane & 3, ip = 8 * (2 - zw) + (lane >> 2);
      const int row0 = 128 * m + 16 * j + 4 * q;
      float* red = (float*)(smem + OFF_RED);
      uint4 xr[3][4][2];
#pragma unroll
      for (int k = 0; k < 3; k++)
#pragma unroll
        for (int a = 0; a < 4; a++)
#pragma unroll
          for (int e = 0; e < 2; e++)
            xr[k][a][e] = (k < 2 || zw > 0) ? __ldg((const uint4*)(P.x + (size_t)(row0 + a) * D) + 2 * ip + 48 * k + e) : make_uint4(0, 0, 0, 0);
      float s1[4], s2[4], nm[4], rs[4];
      auto row_stats = [&]() {
#pragma unroll
        for (int a = 0; a < 4; a++) {
#pragma unroll
          for (int o = 4; o < 32; o <<= 1) {
            s1[a] += __shfl_xor_sync(0xffffffffu, s1[a], o);
            s2[a] += __shfl_xor_sync(0xffffffffu, s2[a], o);
          }
          if (lane < 4) { red[(zw * 16 + 4 * q + a) * 2] = s1[a]; red[(zw * 16 + 4 * q + a) * 2 + 1] = s2[a]; }
        }
        bar_sync(1, 96);
#pragma unroll
        for (int a = 0; a < 4; a++) {
          const int i = 2 * (4 * q + a);
          const float mu = (red[i] + red[32 + i] + red[64 + i]) * (1.f / D);
          const float e2 = (red[i + 1] + red[33 + i] + red[65 + i]) * (1.f / D);
          rs[a] = rsqrtf(fmaxf(fmaf(-mu, mu, e2), 0.f) + 1e-5f);
          nm[a] = -mu * rs[a];
          s1[a] = 0.f; s2[a] = 0.f;
        }
      };
#pragma unroll 1
      for (int ev = 0; ev < 8; ev++) {
        const int r = (0xed90 >> (2 * ev)) & 3;
        if (((0x5104 >> (2 * ev)) & 3) == 0) {
          mbar_wait(bar + 8 * (B_YFULL + r), 0);
          const uint32_t yb = sb + off_Y(r) + lane * 8;
          uint32_t* zp = g_z + (size_t)(r * NCTA + c) * S + lane * 4;
#pragma unroll 2
          for (int task = zw; task < 16; task += 3) {
            float a[2][4];
#pragma unroll
            for (int e = 0; e < 2; e++) {
              const uint2 p0 = lds64(yb + e * YBUF + task * 256), p1 = lds64(yb + e * YBUF + YW + task * 256);
              const uint2 p2 = lds64(yb + e * YBUF + 2 * YW + task * 256), p3 = lds64(yb + e * YBUF + 3 * YW + task * 256);
              a[e][0] = (bflo(p0.x) + bflo(p1.x)) + (bflo(p2.x) + bflo(p3.x));
              a[e][1] = (bfhi(p0.x) + bfhi(p1.x)) + (bfhi(p2.x) + bfhi(p3.x));
              a[e][2] = (bflo(p0.y) + bflo(p1.y)) + (bflo(p2.y) + bflo(p3.y));
              a[e][3] = (bfhi(p0.y) + bfhi(p1.y)) + (bfhi(p2.y) + bfhi(p3.y));
            }
            stg_relaxed4(zp + task * 128, max(packbf(a[0][0], a[1][0]), 1u), max(packbf(a[0][1], a[1][1]), 1u),
                         max(packbf(a[0][2], a[1][2]), 1u), max(packbf(a[0][3], a[1][3]), 1u));
          }
          __syncwarp();
          if (lane == 0) mbar_arrive(bar + 8 * (B_ZDONE + r));
          if (tid == 288) TS(17 + r);
        } else {
          if (r == 0) {
#pragma unroll
            for (int a = 0; a < 4; a++) {
              float t1 = 0.f, t2 = 0.f;
#pragma unroll
              for (int k = 0; k < 3; k++)
#pragma unroll
                for (int e = 0; e < 2; e++) {
                  const uint32_t vv[4] = {xr[k][a][e].x, xr[k][a][e].y, xr[k][a][e].z, xr[k][a][e].w};
#pragma unroll
                  for (int i = 0; i < 4; i++) {
                    const float lo = bflo(vv[i]), hi = bfhi(vv[i]);
                    t1 += lo + hi;
                    t2 = fmaf(lo, lo, fmaf(hi, hi, t2));
                  }
                }
              s1[a] = t1; s2[a] = t2;
            }
            row_stats();
            if (tid == 288) TS(22);
          }
          uint4 zv[3][2];
          uint32_t* zp = g_z + (size_t)(r * NCTA + 2 * ip) * S + row0;
          {
            int it = 0;
            while (true) {
              uint32_t lo = 1;
#pragma unroll
              for (int k = 0; k < 3; k++)
                if (k < 2 || zw > 0) {
#pragma unroll
                  for (int e = 0; e < 2; e++) zv[k][e] = ldg_relaxed4(zp + (size_t)(48 * k + e) * S);
                }
#pragma unroll
              for (int k = 0; k < 3; k++)
                if (k < 2 || zw > 0) {
#pragma unroll
                  for (int e = 0; e < 2; e++) lo = min(min(lo, min(zv[k][e].x, zv[k][e].y)), min(zv[k][e].z, zv[k][e].w));
                }
              if (__all_sync(0xffffffffu, lo != 0)) break;
              __nanosleep(64);
              if (++it > (1 << 20)) __trap();
            }
          }
          if (tid == 288) TS(27 + r);
          __nv_bfloat16* hp = g_h + (size_t)row0 * D + 256 * r + 4 * ip;
#pragma unroll
          for (int a = 0; a < 4; a++) {
#pragma unroll
            for (int k = 0; k < 3; k++)
              if (k < 2 || zw > 0) {
                uint32_t o[2];
#pragma unroll
                for (int e = 0; e < 2; e++) {
                  const uint32_t xx = xr[k][a][e].x;
                  const uint32_t zz = a == 0 ? zv[k][e].x : a == 1 ? zv[k][e].y : a == 2 ? zv[k][e].z : zv[k][e].w;
                  const float x0 = bflo(xx), x1 = bfhi(xx);
                  o[e] = packbf(fmaf(fmaf(x0, rs[a], nm[a]), bflo(zz), x0), fmaf(fmaf(x1, rs[a], nm[a]), bfhi(zz), x1));
                  const float f0 = bflo(o[e]), f1 = bfhi(o[e]);
                  s1[a] += f0 + f1;
                  s2[a] = fmaf(f0, f0, fmaf(f1, f1, s2[a]));
                }
                stg64(hp + a * D + 96 * k, o[0], o[1]);
              }
          }
          if (r == 3) {
            row_stats();
            if (zw == 0 && lane < 4) {
#pragma unroll
              for (int a = 0; a < 4; a++) g_hstat[row0 + a] = make_float2(nm[a], rs[a]);
            }
          }
          fence_async_global();
          __syncwarp();
          if (tid == 288) TS(23 + r);
          if (lane == 0) signal(g_hcnt + (r * 16 + m) * 32);
          if (tid == 288) TS(32 + r);
#pragma unroll
          for (int k = 0; k < 3; k++) {
#pragma unroll
            for (int e = 0; e < 2; e++) {
              if (k < 2 || zw > 0) stg_relaxed4(zp + (size_t)(48 * k + e) * S, 0, 0, 0, 0);
#pragma unroll
              for (int a = 0; a < 4; a++) { xr[k][a][e].x = xr[k][a][e].y; xr[k][a][e].y = xr[k][a][e].z; xr[k][a][e].z = xr[k][a][e].w; }
            }
          }
        }
      }
      if (m < 14) {
        float cs[8];
#pragma unroll
        for (int i = 0; i < 8; i++) cs[i] = 0.f;
        const __nv_bfloat16* wp = P.w1 + (size_t)(lane >> 2) * F + 448 * j + 32 * m + 8 * (lane & 3);
#pragma unroll 16
        for (int task = zw; task < 128; task += 3) {
          const uint4 v = __ldg((const uint4*)(wp + (size_t)task * 8 * F));
          cs[0] += bflo(v.x); cs[1] += bfhi(v.x); cs[2] += bflo(v.y); cs[3] += bfhi(v.y);
          cs[4] += bflo(v.z); cs[5] += bfhi(v.z); cs[6] += bflo(v.w); cs[7] += bfhi(v.w);
        }
#pragma unroll
        for (int i = 0; i < 8; i++) {
          cs[i] += __shfl_xor_sync(0xffffffffu, cs[i], 4);
          cs[i] += __shfl_xor_sync(0xffffffffu, cs[i], 8);
          cs[i] += __shfl_xor_sync(0xffffffffu, cs[i], 16);
        }
        float* red2 = (float*)(smem + OFF_CSB2);
        if (lane < 4) {
#pragma unroll
          for (int i = 0; i < 8; i++) red2[zw * 32 + lane * 8 + i] = cs[i];
        }
        bar_sync(1, 96);
        if (zw == 0) {
          g_cs[448 * j + 32 * m + lane] = red2[lane] + red2[32 + lane] + red2[64 + lane];
          __syncwarp();
          if (lane == 0) signal(g_ccnt + j * 32);
        }
      }
      if (tid == 288) wait_count(g_ccnt + j * 32, epoch * 14);
      bar_sync(1, 96);
      for (int i = zw * 32 + lane; i < 224; i += 96) {
        float2 cv;
        asm volatile("ld.global.cg.v2.f32 {%0,%1},[%2];" : "=f"(cv.x), "=f"(cv.y) : "l"(g_cs + 448 * j + 2 * i) : "memory");
        const uint32_t b = __ldg((const uint32_t*)(P.b1 + 448 * j) + i);
        const uint32_t dst = i < 128 ? sb + OFF_X + i * 16 : sb + OFF_CSB2 + (i - 128) * 16;
        sts128(dst, __float_as_uint(cv.x), __float_as_uint(cv.y), __float_as_uint(bflo(b)), __float_as_uint(bfhi(b)));
      }
      __syncwarp();
      if (lane == 0) mbar_arrive(bar + 8 * B_CSFULL);
      if (tid == 288) {
        TS(21);
        for (int tile = 0; tile < 2; tile++) {
          mbar_wait(bar + 8 * (B_ADONE + tile), 0);
          signal(g_acnt + (tile * 16 + m) * 32);
          TS(41 + tile);
        }
        g_epoch[c] = epoch;
      }
    }
  }
}

typedef CUresult (*PFN_encode)(CUtensorMap*, CUtensorMapDataType, cuuint32_t, void*, const cuuint64_t*, const cuuint64_t*, const cuuint32_t*,
                               const cuuint32_t*, CUtensorMapInterleave, CUtensorMapSwizzle, CUtensorMapL2promotion, CUtensorMapFloatOOBfill);

void encode(PFN_encode enc, CUtensorMap* m, const void* ptr, int rank, const cuuint64_t* dims, const cuuint64_t* strides, const cuuint32_t* box,
            CUtensorMapSwizzle swz) {
  const cuuint32_t es[5] = {1, 1, 1, 1, 1};
  enc(m, CU_TENSOR_MAP_DATA_TYPE_BFLOAT16, rank, (void*)ptr, dims, strides, box, es, CU_TENSOR_MAP_INTERLEAVE_NONE, swz,
      CU_TENSOR_MAP_L2_PROMOTION_L2_128B, CU_TENSOR_MAP_FLOAT_OOB_FILL_NONE);
}

}

extern "C" void kernel_launch(void* const* d_in, const int* in_sizes, int n_in, void* d_out, int out_size) {
  static PFN_encode enc = nullptr;
  static void *p_h = nullptr, *p_act = nullptr;
  if (!enc) {
    cudaDriverEntryPointQueryResult qr;
    cudaGetDriverEntryPoint("cuTensorMapEncodeTiled", (void**)&enc, cudaEnableDefault, &qr);
    cudaGetSymbolAddress(&p_h, g_h);
    cudaGetSymbolAddress(&p_act, g_act);
    cudaFuncSetAttribute(fused_kernel, cudaFuncAttributeMaxDynamicSharedMemorySize, SMEM_BYTES);
  }
  Params P;
  P.x = (const __nv_bfloat16*)d_in[0];
  P.shift_k = (const __nv_bfloat16*)d_in[3];
  P.ssm_k = (const __nv_bfloat16*)d_in[4];
  P.ssm_D = (const __nv_bfloat16*)d_in[5];
  P.w1 = (const __nv_bfloat16*)d_in[7];
  P.b1 = (const __nv_bfloat16*)d_in[8];
  P.w2 = (const __nv_bfloat16*)d_in[9];
  P.b2 = (const __nv_bfloat16*)d_in[10];
  {
    const cuuint64_t dims[3] = {D, S / 8, 8}, str[2] = {8 * D * 2, D * 2};
    const cuuint32_t box[3] = {16, 17, 8};
    encode(enc, &P.tm_k, d_in[1], 3, dims, str, box, CU_TENSOR_MAP_SWIZZLE_NONE);
    encode(enc, &P.tm_v, d_in[2], 3, dims, str, box, CU_TENSOR_MAP_SWIZZLE_NONE);
  }
  {
    const cuuint64_t dims[2] = {D, S}, str[1] = {D * 2};
    const cuuint32_t box[2] = {64, 128}, boxo[2] = {64, 64};
    encode(enc, &P.tm_h, p_h, 2, dims, str, box, CU_TENSOR_MAP_SWIZZLE_128B);
    encode(enc, &P.tm_out, d_out, 2, dims, str, boxo, CU_TENSOR_MAP_SWIZZLE_128B);
  }
  {
    const cuuint64_t dims[3] = {F, 8, D / 8}, str[2] = {F * 2, 8 * F * 2};
    const cuuint32_t box[3] = {64, 2, 32};
    encode(enc, &P.tm_w1, P.w1, 3, dims, str, box, CU_TENSOR_MAP_SWIZZLE_128B);
  }
  {
    const cuuint64_t dims[2] = {F, S}, str[1] = {F * 2};
    const cuuint32_t box[2] = {64, 128};
    encode(enc, &P.tm_act, p_act, 2, dims, str, box, CU_TENSOR_MAP_SWIZZLE_128B);
  }
  {
    const cuuint64_t dims[5] = {D, 2, 4, 4, F / 32}, str[4] = {D * 2, 8 * D * 2, 2 * D * 2, 32 * D * 2};
    const cuuint32_t box[5] = {64, 2, 4, 4, 2};
    encode(enc, &P.tm_w2, P.w2, 5, dims, str, box, CU_TENSOR_MAP_SWIZZLE_128B);
  }
  {
    const cuuint64_t dims[3] = {256, 4, S}, str[2] = {512, D * 2};
    const cuuint32_t box[3] = {32, 4, 128};
    encode(enc, &P.tm_hres, p_h, 3, dims, str, box, CU_TENSOR_MAP_SWIZZLE_64B);
  }
  fused_kernel<<<NCTA, NTHREADS, SMEM_BYTES>>>(P);
}
```

```cpp
#include <cuda_runtime.h>
#include <cuda_bf16.h>
#include <cuda.h>
#include <stdint.h>

#define DBG_TS 0

#define KV_GATE 5

namespace {

constexpr int S = 2048, D = 1024, F = 3584;
constexpr int NCTA = 128, NTHREADS = 384;

constexpr int UT_COPY = 1040 * 4;
constexpr int UT_SIZE = 2 * UT_COPY;
constexpr int KT_SIZE = 16 + 4096;
constexpr int T_SIZE = 2 * (UT_SIZE + KT_SIZE);
constexpr int KV_STAGE = 17 * 8 * 32;
constexpr int KV_SIZE = 8 * KV_STAGE;
constexpr int YW = 4096 + 96;
constexpr int YBUF = 4 * YW;
constexpr int OFF_T3 = 196608 - T_SIZE;
constexpr int OFF_KVB = (OFF_T3 - KV_SIZE) & ~127;
constexpr int OFF_T2 = OFF_KVB - T_SIZE;
constexpr int OFF_KVA = (OFF_T2 - KV_SIZE) & ~127;
constexpr int OFF_T1 = OFF_KVA - T_SIZE;
constexpr int OFF_T0 = OFF_T1 - T_SIZE;
constexpr int OFF_X = 196608;
constexpr int OFF_CSB2 = OFF_X + 32768;
constexpr int OFF_RED = OFF_X + 34304;
constexpr int OFF_XS = OFF_X + 34688;
constexpr int OFF_BAR = OFF_X + 34816;
constexpr int SMEM_BYTES = 232448;
static_assert(OFF_T0 >= 0 && 2 * YBUF <= KV_SIZE && 2 * YBUF <= 34304, "smem map");
static_assert(OFF_T2 >= 98304, "stage 1 must only overlap T0,T1,KVA");
static_assert(OFF_T3 >= 147456, "stage 2 must not overlap T3");

enum {
  B_KVFULL = 0, B_KFULL = 8, B_UFULL = 16, B_YFULL = 24, B_ZDONE = 28, B_FULL1 = 32, B_EMPTY1 = 36,
  B_FULL2 = 40, B_EMPTY2 = 46, B_CSFULL = 52, B_HRES = 53, B_ADONE = 54, B_XDONE = 56, B_COUNT = 57
};

struct Params {
  CUtensorMap tm_k, tm_v, tm_h, tm_w1, tm_act, tm_w2, tm_hres, tm_out;
  const __nv_bfloat16 *x, *shift_k, *ssm_k, *ssm_D, *w1, *b1, *w2, *b2;
};

__device__ __align__(1024) uint32_t g_z[4 * NCTA * S];
__device__ __align__(1024) __nv_bfloat16 g_h[S * D];
__device__ __align__(1024) __nv_bfloat16 g_act[S * F];
__device__ __align__(128) float2 g_hstat[S];
__device__ __align__(128) float g_cs[F];
__device__ __align__(128) uint32_t g_hcnt[4 * 16 * 32];
__device__ __align__(128) uint32_t g_acnt[2 * 16 * 32];
__device__ __align__(128) uint32_t g_ccnt[8 * 32];
__device__ __align__(128) uint32_t g_epoch[NCTA];
#define TS(slot) do {} while (0)

template<int N> __device__ __forceinline__ void wgmma_rs(float* d, const uint32_t* a, uint64_t db, int sc);
template<int N> __device__ __forceinline__ void wgmma_ss(float* d, uint64_t da, uint64_t db, int sc);
template<> __device__ __forceinline__ void wgmma_rs<16>(float* d, const uint32_t* a, uint64_t db, int sc) {
  asm volatile("{.reg .pred p; setp.ne.b32 p, %13, 0;\n"
  "wgmma.mma_async.sync.aligned.m64n16k16.f32.bf16.bf16 {%0,%1,%2,%3,%4,%5,%6,%7}, {%8,%9,%10,%11}, %12, p, 1, 1, 0;}\n"
  : "+f"(d[0]),"+f"(d[1]),"+f"(d[2]),"+f"(d[3]),"+f"(d[4]),"+f"(d[5]),"+f"(d[6]),"+f"(d[7])
  : "r"(a[0]), "r"(a[1]), "r"(a[2]), "r"(a[3]), "l"(db), "r"(sc));
}
template<> __device__ __forceinline__ void wgmma_rs<32>(float* d, const uint32_t* a, uint64_t db, int sc) {
  asm volatile("{.reg .pred p; setp.ne.b32 p, %21, 0;\n"
  "wgmma.mma_async.sync.aligned.m64n32k16.f32.bf16.bf16 {%0,%1,%2,%3,%4,%5,%6,%7,%8,%9,%10,%11,%12,%13,%14,%15}, {%16,%17,%18,%19}, %20, p, 1, 1, 0;}\n"
  : "+f"(d[0]),"+f"(d[1]),"+f"(d[2]),"+f"(d[3]),"+f"(d[4]),"+f"(d[5]),"+f"(d[6]),"+f"(d[7]),"+f"(d[8]),"+f"(d[9]),"+f"(d[10]),"+f"(d[11]),"+f"(d[12]),"+f"(d[13]),"+f"(d[14]),"+f"(d[15])
  : "r"(a[0]), "r"(a[1]), "r"(a[2]), "r"(a[3]), "l"(db), "r"(sc));
}
template<> __device__ __forceinline__ void wgmma_rs<48>(float* d, const uint32_t* a, uint64_t db, int sc) {
  asm volatile("{.reg .pred p; setp.ne.b32 p, %29, 0;\n"
  "wgmma.mma_async.sync.aligned.m64n48k16.f32.bf16.bf16 {%0,%1,%2,%3,%4,%5,%6,%7,%8,%9,%10,%11,%12,%13,%14,%15,%16,%17,%18,%19,%20,%21,%22,%23}, {%24,%25,%26,%27}, %28, p, 1, 1, 0;}\n"
  : "+f"(d[0]),"+f"(d[1]),"+f"(d[2]),"+f"(d[3]),"+f"(d[4]),"+f"(d[5]),"+f"(d[6]),"+f"(d[7]),"+f"(d[8]),"+f"(d[9]),"+f"(d[10]),"+f"(d[11]),"+f"(d[12]),"+f"(d[13]),"+f"(d[14]),"+f"(d[15]),"+f"(d[16]),"+f"(d[17]),"+f"(d[18]),"+f"(d[19]),"+f"(d[20]),"+f"(d[21]),"+f"(d[22]),"+f"(d[23])
  : "r"(a[0]), "r"(a[1]), "r"(a[2]), "r"(a[3]), "l"(db), "r"(sc));
}
template<> __device__ __forceinline__ void wgmma_rs<64>(float* d, const uint32_t* a, uint64_t db, int sc) {
  asm volatile("{.reg .pred p; setp.ne.b32 p, %37, 0;\n"
  "wgmma.mma_async.sync.aligned.m64n64k16.f32.bf16.bf16 {%0,%1,%2,%3,%4,%5,%6,%7,%8,%9,%10,%11,%12,%13,%14,%15,%16,%17,%18,%19,%20,%21,%22,%23,%24,%25,%26,%27,%28,%29,%30,%31}, {%32,%33,%34,%35}, %36, p, 1, 1, 0;}\n"
  : "+f"(d[0]),"+f"(d[1]),"+f"(d[2]),"+f"(d[3]),"+f"(d[4]),"+f"(d[5]),"+f"(d[6]),"+f"(d[7]),"+f"(d[8]),"+f"(d[9]),"+f"(d[10]),"+f"(d[11]),"+f"(d[12]),"+f"(d[13]),"+f"(d[14]),"+f"(d[15]),"+f"(d[16]),"+f"(d[17]),"+f"(d[18]),"+f"(d[19]),"+f"(d[20]),"+f"(d[21]),"+f"(d[22]),"+f"(d[23]),"+f"(d[24]),"+f"(d[25]),"+f"(d[26]),"+f"(d[27]),"+f"(d[28]),"+f"(d[29]),"+f"(d[30]),"+f"(d[31])
  : "r"(a[0]), "r"(a[1]), "r"(a[2]), "r"(a[3]), "l"(db), "r"(sc));
}
template<> __device__ __forceinline__ void wgmma_rs<80>(float* d, const uint32_t* a, uint64_t db, int sc) {
  asm volatile("{.reg .pred p; setp.ne.b32 p, %45, 0;\n"
  "wgmma.mma_async.sync.aligned.m64n80k16.f32.bf16.bf16 {%0,%1,%2,%3,%4,%5,%6,%7,%8,%9,%10,%11,%12,%13,%14,%15,%16,%17,%18,%19,%20,%21,%22,%23,%24,%25,%26,%27,%28,%29,%30,%31,%32,%33,%34,%35,%36,%37,%38,%39}, {%40,%41,%42,%43}, %44, p, 1, 1, 0;}\n"
  : "+f"(d[0]),"+f"(d[1]),"+f"(d[2]),"+f"(d[3]),"+f"(d[4]),"+f"(d[5]),"+f"(d[6]),"+f"(d[7]),"+f"(d[8]),"+f"(d[9]),"+f"(d[10]),"+f"(d[11]),"+f"(d[12]),"+f"(d[13]),"+f"(d[14]),"+f"(d[15]),"+f"(d[16]),"+f"(d[17]),"+f"(d[18]),"+f"(d[19]),"+f"(d[20]),"+f"(d[21]),"+f"(d[22]),"+f"(d[23]),"+f"(d[24]),"+f"(d[25]),"+f"(d[26]),"+f"(d[27]),"+f"(d[28]),"+f"(d[29]),"+f"(d[30]),"+f"(d[31]),"+f"(d[32]),"+f"(d[33]),"+f"(d[34]),"+f"(d[35]),"+f"(d[36]),"+f"(d[37]),"+f"(d[38]),"+f"(d[39])
  : "r"(a[0]), "r"(a[1]), "r"(a[2]), "r"(a[3]), "l"(db), "r"(sc));
}
template<> __device__ __forceinline__ void wgmma_rs<96>(float* d, const uint32_t* a, uint64_t db, int sc) {
  asm volatile("{.reg .pred p; setp.ne.b32 p, %53, 0;\n"
  "wgmma.mma_async.sync.aligned.m64n96k16.f32.bf16.bf16 {%0,%1,%2,%3,%4,%5,%6,%7,%8,%9,%10,%11,%12,%13,%14,%15,%16,%17,%18,%19,%20,%21,%22,%23,%24,%25,%26,%27,%28,%29,%30,%31,%32,%33,%34,%35,%36,%37,%38,%39,%40,%41,%42,%43,%44,%45,%46,%47}, {%48,%49,%50,%51}, %52, p, 1, 1, 0;}\n"
  : "+f"(d[0]),"+f"(d[1]),"+f"(d[2]),"+f"(d[3]),"+f"(d[4]),"+f"(d[5]),"+f"(d[6]),"+f"(d[7]),"+f"(d[8]),"+f"(d[9]),"+f"(d[10]),"+f"(d[11]),"+f"(d[12]),"+f"(d[13]),"+f"(d[14]),"+f"(d[15]),"+f"(d[16]),"+f"(d[17]),"+f"(d[18]),"+f"(d[19]),"+f"(d[20]),"+f"(d[21]),"+f"(d[22]),"+f"(d[23]),"+f"(d[24]),"+f"(d[25]),"+f"(d[26]),"+f"(d[27]),"+f"(d[28]),"+f"(d[29]),"+f"(d[30]),"+f"(d[31]),"+f"(d[32]),"+f"(d[33]),"+f"(d[34]),"+f"(d[35]),"+f"(d[36]),"+f"(d[37]),"+f"(d[38]),"+f"(d[39]),"+f"(d[40]),"+f"(d[41]),"+f"(d[42]),"+f"(d[43]),"+f"(d[44]),"+f"(d[45]),"+f"(d[46]),"+f"(d[47])
  : "r"(a[0]), "r"(a[1]), "r"(a[2]), "r"(a[3]), "l"(db), "r"(sc));
}
template<> __device__ __forceinline__ void wgmma_rs<112>(float* d, const uint32_t* a, uint64_t db, int sc) {
  asm volatile("{.reg .pred p; setp.ne.b32 p, %61, 0;\n"
  "wgmma.mma_async.sync.aligned.m64n112k16.f32.bf16.bf16 {%0,%1,%2,%3,%4,%5,%6,%7,%8,%9,%10,%11,%12,%13,%14,%15,%16,%17,%18,%19,%20,%21,%22,%23,%24,%25,%26,%27,%28,%29,%30,%31,%32,%33,%34,%35,%36,%37,%38,%39,%40,%41,%42,%43,%44,%45,%46,%47,%48,%49,%50,%51,%52,%53,%54,%55}, {%56,%57,%58,%59}, %60, p, 1, 1, 0;}\n"
  : "+f"(d[0]),"+f"(d[1]),"+f"(d[2]),"+f"(d[3]),"+f"(d[4]),"+f"(d[5]),"+f"(d[6]),"+f"(d[7]),"+f"(d[8]),"+f"(d[9]),"+f"(d[10]),"+f"(d[11]),"+f"(d[12]),"+f"(d[13]),"+f"(d[14]),"+f"(d[15]),"+f"(d[16]),"+f"(d[17]),"+f"(d[18]),"+f"(d[19]),"+f"(d[20]),"+f"(d[21]),"+f"(d[22]),"+f"(d[23]),"+f"(d[24]),"+f"(d[25]),"+f"(d[26]),"+f"(d[27]),"+f"(d[28]),"+f"(d[29]),"+f"(d[30]),"+f"(d[31]),"+f"(d[32]),"+f"(d[33]),"+f"(d[34]),"+f"(d[35]),"+f"(d[36]),"+f"(d[37]),"+f"(d[38]),"+f"(d[39]),"+f"(d[40]),"+f"(d[41]),"+f"(d[42]),"+f"(d[43]),"+f"(d[44]),"+f"(d[45]),"+f"(d[46]),"+f"(d[47]),"+f"(d[48]),"+f"(d[49]),"+f"(d[50]),"+f"(d[51]),"+f"(d[52]),"+f"(d[53]),"+f"(d[54]),"+f"(d[55])
  : "r"(a[0]), "r"(a[1]), "r"(a[2]), "r"(a[3]), "l"(db), "r"(sc));
}
template<> __device__ __forceinline__ void wgmma_rs<128>(float* d, const uint32_t* a, uint64_t db, int sc) {
  asm volatile("{.reg .pred p; setp.ne.b32 p, %69, 0;\n"
  "wgmma.mma_async.sync.aligned.m64n128k16.f32.bf16.bf16 {%0,%1,%2,%3,%4,%5,%6,%7,%8,%9,%10,%11,%12,%13,%14,%15,%16,%17,%18,%19,%20,%21,%22,%23,%24,%25,%26,%27,%28,%29,%30,%31,%32,%33,%34,%35,%36,%37,%38,%39,%40,%41,%42,%43,%44,%45,%46,%47,%48,%49,%50,%51,%52,%53,%54,%55,%56,%57,%58,%59,%60,%61,%62,%63}, {%64,%65,%66,%67}, %68, p, 1, 1, 0;}\n"
  : "+f"(d[0]),"+f"(d[1]),"+f"(d[2]),"+f"(d[3]),"+f"(d[4]),"+f"(d[5]),"+f"(d[6]),"+f"(d[7]),"+f"(d[8]),"+f"(d[9]),"+f"(d[10]),"+f"(d[11]),"+f"(d[12]),"+f"(d[13]),"+f"(d[14]),"+f"(d[15]),"+f"(d[16]),"+f"(d[17]),"+f"(d[18]),"+f"(d[19]),"+f"(d[20]),"+f"(d[21]),"+f"(d[22]),"+f"(d[23]),"+f"(d[24]),"+f"(d[25]),"+f"(d[26]),"+f"(d[27]),"+f"(d[28]),"+f"(d[29]),"+f"(d[30]),"+f"(d[31]),"+f"(d[32]),"+f"(d[33]),"+f"(d[34]),"+f"(d[35]),"+f"(d[36]),"+f"(d[37]),"+f"(d[38]),"+f"(d[39]),"+f"(d[40]),"+f"(d[41]),"+f"(d[42]),"+f"(d[43]),"+f"(d[44]),"+f"(d[45]),"+f"(d[46]),"+f"(d[47]),"+f"(d[48]),"+f"(d[49]),"+f"(d[50]),"+f"(d[51]),"+f"(d[52]),"+f"(d[53]),"+f"(d[54]),"+f"(d[55]),"+f"(d[56]),"+f"(d[57]),"+f"(d[58]),"+f"(d[59]),"+f"(d[60]),"+f"(d[61]),"+f"(d[62]),"+f"(d[63])
  : "r"(a[0]), "r"(a[1]), "r"(a[2]), "r"(a[3]), "l"(db), "r"(sc));
}
template<> __device__ __forceinline__ void wgmma_rs<144>(float* d, const uint32_t* a, uint64_t db, int sc) {
  asm volatile("{.reg .pred p; setp.ne.b32 p, %77, 0;\n"
  "wgmma.mma_async.sync.aligned.m64n144k16.f32.bf16.bf16 {%0,%1,%2,%3,%4,%5,%6,%7,%8,%9,%10,%11,%12,%13,%14,%15,%16,%17,%18,%19,%20,%21,%22,%23,%24,%25,%26,%27,%28,%29,%30,%31,%32,%33,%34,%35,%36,%37,%38,%39,%40,%41,%42,%43,%44,%45,%46,%47,%48,%49,%50,%51,%52,%53,%54,%55,%56,%57,%58,%59,%60,%61,%62,%63,%64,%65,%66,%67,%68,%69,%70,%71}, {%72,%73,%74,%75}, %76, p, 1, 1, 0;}\n"
  : "+f"(d[0]),"+f"(d[1]),"+f"(d[2]),"+f"(d[3]),"+f"(d[4]),"+f"(d[5]),"+f"(d[6]),"+f"(d[7]),"+f"(d[8]),"+f"(d[9]),"+f"(d[10]),"+f"(d[11]),"+f"(d[12]),"+f"(d[13]),"+f"(d[14]),"+f"(d[15]),"+f"(d[16]),"+f"(d[17]),"+f"(d[18]),"+f"(d[19]),"+f"(d[20]),"+f"(d[21]),"+f"(d[22]),"+f"(d[23]),"+f"(d[24]),"+f"(d[25]),"+f"(d[26]),"+f"(d[27]),"+f"(d[28]),"+f"(d[29]),"+f"(d[30]),"+f"(d[31]),"+f"(d[32]),"+f"(d[33]),"+f"(d[34]),"+f"(d[35]),"+f"(d[36]),"+f"(d[37]),"+f"(d[38]),"+f"(d[39]),"+f"(d[40]),"+f"(d[41]),"+f"(d[42]),"+f"(d[43]),"+f"(d[44]),"+f"(d[45]),"+f"(d[46]),"+f"(d[47]),"+f"(d[48]),"+f"(d[49]),"+f"(d[50]),"+f"(d[51]),"+f"(d[52]),"+f"(d[53]),"+f"(d[54]),"+f"(d[55]),"+f"(d[56]),"+f"(d[57]),"+f"(d[58]),"+f"(d[59]),"+f"(d[60]),"+f"(d[61]),"+f"(d[62]),"+f"(d[63]),"+f"(d[64]),"+f"(d[65]),"+f"(d[66]),"+f"(d[67]),"+f"(d[68]),"+f"(d[69]),"+f"(d[70]),"+f"(d[71])
  : "r"(a[0]), "r"(a[1]), "r"(a[2]), "r"(a[3]), "l"(db), "r"(sc));
}
template<> __device__ __forceinline__ void wgmma_rs<160>(float* d, const uint32_t* a, uint64_t db, int sc) {
  asm volatile("{.reg .pred p; setp.ne.b32 p, %85, 0;\n"
  "wgmma.mma_async.sync.aligned.m64n160k16.f32.bf16.bf16 {%0,%1,%2,%3,%4,%5,%6,%7,%8,%9,%10,%11,%12,%13,%14,%15,%16,%17,%18,%19,%20,%21,%22,%23,%24,%25,%26,%27,%28,%29,%30,%31,%32,%33,%34,%35,%36,%37,%38,%39,%40,%41,%42,%43,%44,%45,%46,%47,%48,%49,%50,%51,%52,%53,%54,%55,%56,%57,%58,%59,%60,%61,%62,%63,%64,%65,%66,%67,%68,%69,%70,%71,%72,%73,%74,%75,%76,%77,%78,%79}, {%80,%81,%82,%83}, %84, p, 1, 1, 0;}\n"
  : "+f"(d[0]),"+f"(d[1]),"+f"(d[2]),"+f"(d[3]),"+f"(d[4]),"+f"(d[5]),"+f"(d[6]),"+f"(d[7]),"+f"(d[8]),"+f"(d[9]),"+f"(d[10]),"+f"(d[11]),"+f"(d[12]),"+f"(d[13]),"+f"(d[14]),"+f"(d[15]),"+f"(d[16]),"+f"(d[17]),"+f"(d[18]),"+f"(d[19]),"+f"(d[20]),"+f"(d[21]),"+f"(d[22]),"+f"(d[23]),"+f"(d[24]),"+f"(d[25]),"+f"(d[26]),"+f"(d[27]),"+f"(d[28]),"+f"(d[29]),"+f"(d[30]),"+f"(d[31]),"+f"(d[32]),"+f"(d[33]),"+f"(d[34]),"+f"(d[35]),"+f"(d[36]),"+f"(d[37]),"+f"(d[38]),"+f"(d[39]),"+f"(d[40]),"+f"(d[41]),"+f"(d[42]),"+f"(d[43]),"+f"(d[44]),"+f"(d[45]),"+f"(d[46]),"+f"(d[47]),"+f"(d[48]),"+f"(d[49]),"+f"(d[50]),"+f"(d[51]),"+f"(d[52]),"+f"(d[53]),"+f"(d[54]),"+f"(d[55]),"+f"(d[56]),"+f"(d[57]),"+f"(d[58]),"+f"(d[59]),"+f"(d[60]),"+f"(d[61]),"+f"(d[62]),"+f"(d[63]),"+f"(d[64]),"+f"(d[65]),"+f"(d[66]),"+f"(d[67]),"+f"(d[68]),"+f"(d[69]),"+f"(d[70]),"+f"(d[71]),"+f"(d[72]),"+f"(d[73]),"+f"(d[74]),"+f"(d[75]),"+f"(d[76]),"+f"(d[77]),"+f"(d[78]),"+f"(d[79])
  : "r"(a[0]), "r"(a[1]), "r"(a[2]), "r"(a[3]), "l"(db), "r"(sc));
}
template<> __device__ __forceinline__ void wgmma_rs<176>(float* d, const uint32_t* a, uint64_t db, int sc) {
  asm volatile("{.reg .pred p; setp.ne.b32 p, %93, 0;\n"
  "wgmma.mma_async.sync.aligned.m64n176k16.f32.bf16.bf16 {%0,%1,%2,%3,%4,%5,%6,%7,%8,%9,%10,%11,%12,%13,%14,%15,%16,%17,%18,%19,%20,%21,%22,%23,%24,%25,%26,%27,%28,%29,%30,%31,%32,%33,%34,%35,%36,%37,%38,%39,%40,%41,%42,%43,%44,%45,%46,%47,%48,%49,%50,%51,%52,%53,%54,%55,%56,%57,%58,%59,%60,%61,%62,%63,%64,%65,%66,%67,%68,%69,%70,%71,%72,%73,%74,%75,%76,%77,%78,%79,%80,%81,%82,%83,%84,%85,%86,%87}, {%88,%89,%90,%91}, %92, p, 1, 1, 0;}\n"
  : "+f"(d[0]),"+f"(d[1]),"+f"(d[2]),"+f"(d[3]),"+f"(d[4]),"+f"(d[5]),"+f"(d[6]),"+f"(d[7]),"+f"(d[8]),"+f"(d[9]),"+f"(d[10]),"+f"(d[11]),"+f"(d[12]),"+f"(d[13]),"+f"(d[14]),"+f"(d[15]),"+f"(d[16]),"+f"(d[17]),"+f"(d[18]),"+f"(d[19]),"+f"(d[20]),"+f"(d[21]),"+f"(d[22]),"+f"(d[23]),"+f"(d[24]),"+f"(d[25]),"+f"(d[26]),"+f"(d[27]),"+f"(d[28]),"+f"(d[29]),"+f"(d[30]),"+f"(d[31]),"+f"(d[32]),"+f"(d[33]),"+f"(d[34]),"+f"(d[35]),"+f"(d[36]),"+f"(d[37]),"+f"(d[38]),"+f"(d[39]),"+f"(d[40]),"+f"(d[41]),"+f"(d[42]),"+f"(d[43]),"+f"(d[44]),"+f"(d[45]),"+f"(d[46]),"+f"(d[47]),"+f"(d[48]),"+f"(d[49]),"+f"(d[50]),"+f"(d[51]),"+f"(d[52]),"+f"(d[53]),"+f"(d[54]),"+f"(d[55]),"+f"(d[56]),"+f"(d[57]),"+f"(d[58]),"+f"(d[59]),"+f"(d[60]),"+f"(d[61]),"+f"(d[62]),"+f"(d[63]),"+f"(d[64]),"+f"(d[65]),"+f"(d[66]),"+f"(d[67]),"+f"(d[68]),"+f"(d[69]),"+f"(d[70]),"+f"(d[71]),"+f"(d[72]),"+f"(d[73]),"+f"(d[74]),"+f"(d[75]),"+f"(d[76]),"+f"(d[77]),"+f"(d[78]),"+f"(d[79]),"+f"(d[80]),"+f"(d[81]),"+f"(d[82]),"+f"(d[83]),"+f"(d[84]),"+f"(d[85]),"+f"(d[86]),"+f"(d[87])
  : "r"(a[0]), "r"(a[1]), "r"(a[2]), "r"(a[3]), "l"(db), "r"(sc));
}
template<> __device__ __forceinline__ void wgmma_rs<192>(float* d, const uint32_t* a, uint64_t db, int sc) {
  asm volatile("{.reg .pred p; setp.ne.b32 p, %101, 0;\n"
  "wgmma.mma_async.sync.aligned.m64n192k16.f32.bf16.bf16 {%0,%1,%2,%3,%4,%5,%6,%7,%8,%9,%10,%11,%12,%13,%14,%15,%16,%17,%18,%19,%20,%21,%22,%23,%24,%25,%26,%27,%28,%29,%30,%31,%32,%33,%34,%35,%36,%37,%38,%39,%40,%41,%42,%43,%44,%45,%46,%47,%48,%49,%50,%51,%52,%53,%54,%55,%56,%57,%58,%59,%60,%61,%62,%63,%64,%65,%66,%67,%68,%69,%70,%71,%72,%73,%74,%75,%76,%77,%78,%79,%80,%81,%82,%83,%84,%85,%86,%87,%88,%89,%90,%91,%92,%93,%94,%95}, {%96,%97,%98,%99}, %100, p, 1, 1, 0;}\n"
  : "+f"(d[0]),"+f"(d[1]),"+f"(d[2]),"+f"(d[3]),"+f"(d[4]),"+f"(d[5]),"+f"(d[6]),"+f"(d[7]),"+f"(d[8]),"+f"(d[9]),"+f"(d[10]),"+f"(d[11]),"+f"(d[12]),"+f"(d[13]),"+f"(d[14]),"+f"(d[15]),"+f"(d[16]),"+f"(d[17]),"+f"(d[18]),"+f"(d[19]),"+f"(d[20]),"+f"(d[21]),"+f"(d[22]),"+f"(d[23]),"+f"(d[24]),"+f"(d[25]),"+f"(d[26]),"+f"(d[27]),"+f"(d[28]),"+f"(d[29]),"+f"(d[30]),"+f"(d[31]),"+f"(d[32]),"+f"(d[33]),"+f"(d[34]),"+f"(d[35]),"+f"(d[36]),"+f"(d[37]),"+f"(d[38]),"+f"(d[39]),"+f"(d[40]),"+f"(d[41]),"+f"(d[42]),"+f"(d[43]),"+f"(d[44]),"+f"(d[45]),"+f"(d[46]),"+f"(d[47]),"+f"(d[48]),"+f"(d[49]),"+f"(d[50]),"+f"(d[51]),"+f"(d[52]),"+f"(d[53]),"+f"(d[54]),"+f"(d[55]),"+f"(d[56]),"+f"(d[57]),"+f"(d[58]),"+f"(d[59]),"+f"(d[60]),"+f"(d[61]),"+f"(d[62]),"+f"(d[63]),"+f"(d[64]),"+f"(d[65]),"+f"(d[66]),"+f"(d[67]),"+f"(d[68]),"+f"(d[69]),"+f"(d[70]),"+f"(d[71]),"+f"(d[72]),"+f"(d[73]),"+f"(d[74]),"+f"(d[75]),"+f"(d[76]),"+f"(d[77]),"+f"(d[78]),"+f"(d[79]),"+f"(d[80]),"+f"(d[81]),"+f"(d[82]),"+f"(d[83]),"+f"(d[84]),"+f"(d[85]),"+f"(d[86]),"+f"(d[87]),"+f"(d[88]),"+f"(d[89]),"+f"(d[90]),"+f"(d[91]),"+f"(d[92]),"+f"(d[93]),"+f"(d[94]),"+f"(d[95])
  : "r"(a[0]), "r"(a[1]), "r"(a[2]), "r"(a[3]), "l"(db), "r"(sc));
}
template<> __device__ __forceinline__ void wgmma_rs<208>(float* d, const uint32_t* a, uint64_t db, int sc) {
  asm volatile("{.reg .pred p; setp.ne.b32 p, %109, 0;\n"
  "wgmma.mma_async.sync.aligned.m64n208k16.f32.bf16.bf16 {%0,%1,%2,%3,%4,%5,%6,%7,%8,%9,%10,%11,%12,%13,%14,%15,%16,%17,%18,%19,%20,%21,%22,%23,%24,%25,%26,%27,%28,%29,%30,%31,%32,%33,%34,%35,%36,%37,%38,%39,%40,%41,%42,%43,%44,%45,%46,%47,%48,%49,%50,%51,%52,%53,%54,%55,%56,%57,%58,%59,%60,%61,%62,%63,%64,%65,%66,%67,%68,%69,%70,%71,%72,%73,%74,%75,%76,%77,%78,%79,%80,%81,%82,%83,%84,%85,%86,%87,%88,%89,%90,%91,%92,%93,%94,%95,%96,%97,%98,%99,%100,%101,%102,%103}, {%104,%105,%106,%107}, %108, p, 1, 1, 0;}\n"
  : "+f"(d[0]),"+f"(d[1]),"+f"(d[2]),"+f"(d[3]),"+f"(d[4]),"+f"(d[5]),"+f"(d[6]),"+f"(d[7]),"+f"(d[8]),"+f"(d[9]),"+f"(d[10]),"+f"(d[11]),"+f"(d[12]),"+f"(d[13]),"+f"(d[14]),"+f"(d[15]),"+f"(d[16]),"+f"(d[17]),"+f"(d[18]),"+f"(d[19]),"+f"(d[20]),"+f"(d[21]),"+f"(d[22]),"+f"(d[23]),"+f"(d[24]),"+f"(d[25]),"+f"(d[26]),"+f"(d[27]),"+f"(d[28]),"+f"(d[29]),"+f"(d[30]),"+f"(d[31]),"+f"(d[32]),"+f"(d[33]),"+f"(d[34]),"+f"(d[35]),"+f"(d[36]),"+f"(d[37]),"+f"(d[38]),"+f"(d[39]),"+f"(d[40]),"+f"(d[41]),"+f"(d[42]),"+f"(d[43]),"+f"(d[44]),"+f"(d[45]),"+f"(d[46]),"+f"(d[47]),"+f"(d[48]),"+f"(d[49]),"+f"(d[50]),"+f"(d[51]),"+f"(d[52]),"+f"(d[53]),"+f"(d[54]),"+f"(d[55]),"+f"(d[56]),"+f"(d[57]),"+f"(d[58]),"+f"(d[59]),"+f"(d[60]),"+f"(d[61]),"+f"(d[62]),"+f"(d[63]),"+f"(d[64]),"+f"(d[65]),"+f"(d[66]),"+f"(d[67]),"+f"(d[68]),"+f"(d[69]),"+f"(d[70]),"+f"(d[71]),"+f"(d[72]),"+f"(d[73]),"+f"(d[74]),"+f"(d[75]),"+f"(d[76]),"+f"(d[77]),"+f"(d[78]),"+f"(d[79]),"+f"(d[80]),"+f"(d[81]),"+f"(d[82]),"+f"(d[83]),"+f"(d[84]),"+f"(d[85]),"+f"(d[86]),"+f"(d[87]),"+f"(d[88]),"+f"(d[89]),"+f"(d[90]),"+f"(d[91]),"+f"(d[92]),"+f"(d[93]),"+f"(d[94]),"+f"(d[95]),"+f"(d[96]),"+f"(d[97]),"+f"(d[98]),"+f"(d[99]),"+f"(d[100]),"+f"(d[101]),"+f"(d[102]),"+f"(d[103])
  : "r"(a[0]), "r"(a[1]), "r"(a[2]), "r"(a[3]), "l"(db), "r"(sc));
}
template<> __device__ __forceinline__ void wgmma_rs<224>(float* d, const uint32_t* a, uint64_t db, int sc) {
  asm volatile("{.reg .pred p; setp.ne.b32 p, %117, 0;\n"
  "wgmma.mma_async.sync.aligned.m64n224k16.f32.bf16.bf16 {%0,%1,%2,%3,%4,%5,%6,%7,%8,%9,%10,%11,%12,%13,%14,%15,%16,%17,%18,%19,%20,%21,%22,%23,%24,%25,%26,%27,%28,%29,%30,%31,%32,%33,%34,%35,%36,%37,%38,%39,%40,%41,%42,%43,%44,%45,%46,%47,%48,%49,%50,%51,%52,%53,%54,%55,%56,%57,%58,%59,%60,%61,%62,%63,%64,%65,%66,%67,%68,%69,%70,%71,%72,%73,%74,%75,%76,%77,%78,%79,%80,%81,%82,%83,%84,%85,%86,%87,%88,%89,%90,%91,%92,%93,%94,%95,%96,%97,%98,%99,%100,%101,%102,%103,%104,%105,%106,%107,%108,%109,%110,%111}, {%112,%113,%114,%115}, %116, p, 1, 1, 0;}\n"
  : "+f"(d[0]),"+f"(d[1]),"+f"(d[2]),"+f"(d[3]),"+f"(d[4]),"+f"(d[5]),"+f"(d[6]),"+f"(d[7]),"+f"(d[8]),"+f"(d[9]),"+f"(d[10]),"+f"(d[11]),"+f"(d[12]),"+f"(d[13]),"+f"(d[14]),"+f"(d[15]),"+f"(d[16]),"+f"(d[17]),"+f"(d[18]),"+f"(d[19]),"+f"(d[20]),"+f"(d[21]),"+f"(d[22]),"+f"(d[23]),"+f"(d[24]),"+f"(d[25]),"+f"(d[26]),"+f"(d[27]),"+f"(d[28]),"+f"(d[29]),"+f"(d[30]),"+f"(d[31]),"+f"(d[32]),"+f"(d[33]),"+f"(d[34]),"+f"(d[35]),"+f"(d[36]),"+f"(d[37]),"+f"(d[38]),"+f"(d[39]),"+f"(d[40]),"+f"(d[41]),"+f"(d[42]),"+f"(d[43]),"+f"(d[44]),"+f"(d[45]),"+f"(d[46]),"+f"(d[47]),"+f"(d[48]),"+f"(d[49]),"+f"(d[50]),"+f"(d[51]),"+f"(d[52]),"+f"(d[53]),"+f"(d[54]),"+f"(d[55]),"+f"(d[56]),"+f"(d[57]),"+f"(d[58]),"+f"(d[59]),"+f"(d[60]),"+f"(d[61]),"+f"(d[62]),"+f"(d[63]),"+f"(d[64]),"+f"(d[65]),"+f"(d[66]),"+f"(d[67]),"+f"(d[68]),"+f"(d[69]),"+f"(d[70]),"+f"(d[71]),"+f"(d[72]),"+f"(d[73]),"+f"(d[74]),"+f"(d[75]),"+f"(d[76]),"+f"(d[77]),"+f"(d[78]),"+f"(d[79]),"+f"(d[80]),"+f"(d[81]),"+f"(d[82]),"+f"(d[83]),"+f"(d[84]),"+f"(d[85]),"+f"(d[86]),"+f"(d[87]),"+f"(d[88]),"+f"(d[89]),"+f"(d[90]),"+f"(d[91]),"+f"(d[92]),"+f"(d[93]),"+f"(d[94]),"+f"(d[95]),"+f"(d[96]),"+f"(d[97]),"+f"(d[98]),"+f"(d[99]),"+f"(d[100]),"+f"(d[101]),"+f"(d[102]),"+f"(d[103]),"+f"(d[104]),"+f"(d[105]),"+f"(d[106]),"+f"(d[107]),"+f"(d[108]),"+f"(d[109]),"+f"(d[110]),"+f"(d[111])
  : "r"(a[0]), "r"(a[1]), "r"(a[2]), "r"(a[3]), "l"(db), "r"(sc));
}
template<> __device__ __forceinline__ void wgmma_rs<240>(float* d, const uint32_t* a, uint64_t db, int sc) {
  asm volatile("{.reg .pred p; setp.ne.b32 p, %125, 0;\n"
  "wgmma.mma_async.sync.aligned.m64n240k16.f32.bf16.bf16 {%0,%1,%2,%3,%4,%5,%6,%7,%8,%9,%10,%11,%12,%13,%14,%15,%16,%17,%18,%19,%20,%21,%22,%23,%24,%25,%26,%27,%28,%29,%30,%31,%32,%33,%34,%35,%36,%37,%38,%39,%40,%41,%42,%43,%44,%45,%46,%47,%48,%49,%50,%51,%52,%53,%54,%55,%56,%57,%58,%59,%60,%61,%62,%63,%64,%65,%66,%67,%68,%69,%70,%71,%72,%73,%74,%75,%76,%77,%78,%79,%80,%81,%82,%83,%84,%85,%86,%87,%88,%89,%90,%91,%92,%93,%94,%95,%96,%97,%98,%99,%100,%101,%102,%103,%104,%105,%106,%107,%108,%109,%110,%111,%112,%113,%114,%115,%116,%117,%118,%119}, {%120,%121,%122,%123}, %124, p, 1, 1, 0;}\n"
  : "+f"(d[0]),"+f"(d[1]),"+f"(d[2]),"+f"(d[3]),"+f"(d[4]),"+f"(d[5]),"+f"(d[6]),"+f"(d[7]),"+f"(d[8]),"+f"(d[9]),"+f"(d[10]),"+f"(d[11]),"+f"(d[12]),"+f"(d[13]),"+f"(d[14]),"+f"(d[15]),"+f"(d[16]),"+f"(d[17]),"+f"(d[18]),"+f"(d[19]),"+f"(d[20]),"+f"(d[21]),"+f"(d[22]),"+f"(d[23]),"+f"(d[24]),"+f"(d[25]),"+f"(d[26]),"+f"(d[27]),"+f"(d[28]),"+f"(d[29]),"+f"(d[30]),"+f"(d[31]),"+f"(d[32]),"+f"(d[33]),"+f"(d[34]),"+f"(d[35]),"+f"(d[36]),"+f"(d[37]),"+f"(d[38]),"+f"(d[39]),"+f"(d[40]),"+f"(d[41]),"+f"(d[42]),"+f"(d[43]),"+f"(d[44]),"+f"(d[45]),"+f"(d[46]),"+f"(d[47]),"+f"(d[48]),"+f"(d[49]),"+f"(d[50]),"+f"(d[51]),"+f"(d[52]),"+f"(d[53]),"+f"(d[54]),"+f"(d[55]),"+f"(d[56]),"+f"(d[57]),"+f"(d[58]),"+f"(d[59]),"+f"(d[60]),"+f"(d[61]),"+f"(d[62]),"+f"(d[63]),"+f"(d[64]),"+f"(d[65]),"+f"(d[66]),"+f"(d[67]),"+f"(d[68]),"+f"(d[69]),"+f"(d[70]),"+f"(d[71]),"+f"(d[72]),"+f"(d[73]),"+f"(d[74]),"+f"(d[75]),"+f"(d[76]),"+f"(d[77]),"+f"(d[78]),"+f"(d[79]),"+f"(d[80]),"+f"(d[81]),"+f"(d[82]),"+f"(d[83]),"+f"(d[84]),"+f"(d[85]),"+f"(d[86]),"+f"(d[87]),"+f"(d[88]),"+f"(d[89]),"+f"(d[90]),"+f"(d[91]),"+f"(d[92]),"+f"(d[93]),"+f"(d[94]),"+f"(d[95]),"+f"(d[96]),"+f"(d[97]),"+f"(d[98]),"+f"(d[99]),"+f"(d[100]),"+f"(d[101]),"+f"(d[102]),"+f"(d[103]),"+f"(d[104]),"+f"(d[105]),"+f"(d[106]),"+f"(d[107]),"+f"(d[108]),"+f"(d[109]),"+f"(d[110]),"+f"(d[111]),"+f"(d[112]),"+f"(d[113]),"+f"(d[114]),"+f"(d[115]),"+f"(d[116]),"+f"(d[117]),"+f"(d[118]),"+f"(d[119])
  : "r"(a[0]), "r"(a[1]), "r"(a[2]), "r"(a[3]), "l"(db), "r"(sc));
}
template<> __device__ __forceinline__ void wgmma_rs<256>(float* d, const uint32_t* a, uint64_t db, int sc) {
  asm volatile("{.reg .pred p; setp.ne.b32 p, %133, 0;\n"
  "wgmma.mma_async.sync.aligned.m64n256k16.f32.bf16.bf16 {%0,%1,%2,%3,%4,%5,%6,%7,%8,%9,%10,%11,%12,%13,%14,%15,%16,%17,%18,%19,%20,%21,%22,%23,%24,%25,%26,%27,%28,%29,%30,%31,%32,%33,%34,%35,%36,%37,%38,%39,%40,%41,%42,%43,%44,%45,%46,%47,%48,%49,%50,%51,%52,%53,%54,%55,%56,%57,%58,%59,%60,%61,%62,%63,%64,%65,%66,%67,%68,%69,%70,%71,%72,%73,%74,%75,%76,%77,%78,%79,%80,%81,%82,%83,%84,%85,%86,%87,%88,%89,%90,%91,%92,%93,%94,%95,%96,%97,%98,%99,%100,%101,%102,%103,%104,%105,%106,%107,%108,%109,%110,%111,%112,%113,%114,%115,%116,%117,%118,%119,%120,%121,%122,%123,%124,%125,%126,%127}, {%128,%129,%130,%131}, %132, p, 1, 1, 0;}\n"
  : "+f"(d[0]),"+f"(d[1]),"+f"(d[2]),"+f"(d[3]),"+f"(d[4]),"+f"(d[5]),"+f"(d[6]),"+f"(d[7]),"+f"(d[8]),"+f"(d[9]),"+f"(d[10]),"+f"(d[11]),"+f"(d[12]),"+f"(d[13]),"+f"(d[14]),"+f"(d[15]),"+f"(d[16]),"+f"(d[17]),"+f"(d[18]),"+f"(d[19]),"+f"(d[20]),"+f"(d[21]),"+f"(d[22]),"+f"(d[23]),"+f"(d[24]),"+f"(d[25]),"+f"(d[26]),"+f"(d[27]),"+f"(d[28]),"+f"(d[29]),"+f"(d[30]),"+f"(d[31]),"+f"(d[32]),"+f"(d[33]),"+f"(d[34]),"+f"(d[35]),"+f"(d[36]),"+f"(d[37]),"+f"(d[38]),"+f"(d[39]),"+f"(d[40]),"+f"(d[41]),"+f"(d[42]),"+f"(d[43]),"+f"(d[44]),"+f"(d[45]),"+f"(d[46]),"+f"(d[47]),"+f"(d[48]),"+f"(d[49]),"+f"(d[50]),"+f"(d[51]),"+f"(d[52]),"+f"(d[53]),"+f"(d[54]),"+f"(d[55]),"+f"(d[56]),"+f"(d[57]),"+f"(d[58]),"+f"(d[59]),"+f"(d[60]),"+f"(d[61]),"+f"(d[62]),"+f"(d[63]),"+f"(d[64]),"+f"(d[65]),"+f"(d[66]),"+f"(d[67]),"+f"(d[68]),"+f"(d[69]),"+f"(d[70]),"+f"(d[71]),"+f"(d[72]),"+f"(d[73]),"+f"(d[74]),"+f"(d[75]),"+f"(d[76]),"+f"(d[77]),"+f"(d[78]),"+f"(d[79]),"+f"(d[80]),"+f"(d[81]),"+f"(d[82]),"+f"(d[83]),"+f"(d[84]),"+f"(d[85]),"+f"(d[86]),"+f"(d[87]),"+f"(d[88]),"+f"(d[89]),"+f"(d[90]),"+f"(d[91]),"+f"(d[92]),"+f"(d[93]),"+f"(d[94]),"+f"(d[95]),"+f"(d[96]),"+f"(d[97]),"+f"(d[98]),"+f"(d[99]),"+f"(d[100]),"+f"(d[101]),"+f"(d[102]),"+f"(d[103]),"+f"(d[104]),"+f"(d[105]),"+f"(d[106]),"+f"(d[107]),"+f"(d[108]),"+f"(d[109]),"+f"(d[110]),"+f"(d[111]),"+f"(d[112]),"+f"(d[113]),"+f"(d[114]),"+f"(d[115]),"+f"(d[116]),"+f"(d[117]),"+f"(d[118]),"+f"(d[119]),"+f"(d[120]),"+f"(d[121]),"+f"(d[122]),"+f"(d[123]),"+f"(d[124]),"+f"(d[125]),"+f"(d[126]),"+f"(d[127])
  : "r"(a[0]), "r"(a[1]), "r"(a[2]), "r"(a[3]), "l"(db), "r"(sc));
}
template<> __device__ __forceinline__ void wgmma_ss<128>(float* d, uint64_t da, uint64_t db, int sc) {
  asm volatile("{.reg .pred p; setp.ne.b32 p, %66, 0;\n"
  "wgmma.mma_async.sync.aligned.m64n128k16.f32.bf16.bf16 {%0,%1,%2,%3,%4,%5,%6,%7,%8,%9,%10,%11,%12,%13,%14,%15,%16,%17,%18,%19,%20,%21,%22,%23,%24,%25,%26,%27,%28,%29,%30,%31,%32,%33,%34,%35,%36,%37,%38,%39,%40,%41,%42,%43,%44,%45,%46,%47,%48,%49,%50,%51,%52,%53,%54,%55,%56,%57,%58,%59,%60,%61,%62,%63}, %64, %65, p, 1, 1, 0, 1;}\n"
  : "+f"(d[0]),"+f"(d[1]),"+f"(d[2]),"+f"(d[3]),"+f"(d[4]),"+f"(d[5]),"+f"(d[6]),"+f"(d[7]),"+f"(d[8]),"+f"(d[9]),"+f"(d[10]),"+f"(d[11]),"+f"(d[12]),"+f"(d[13]),"+f"(d[14]),"+f"(d[15]),"+f"(d[16]),"+f"(d[17]),"+f"(d[18]),"+f"(d[19]),"+f"(d[20]),"+f"(d[21]),"+f"(d[22]),"+f"(d[23]),"+f"(d[24]),"+f"(d[25]),"+f"(d[26]),"+f"(d[27]),"+f"(d[28]),"+f"(d[29]),"+f"(d[30]),"+f"(d[31]),"+f"(d[32]),"+f"(d[33]),"+f"(d[34]),"+f"(d[35]),"+f"(d[36]),"+f"(d[37]),"+f"(d[38]),"+f"(d[39]),"+f"(d[40]),"+f"(d[41]),"+f"(d[42]),"+f"(d[43]),"+f"(d[44]),"+f"(d[45]),"+f"(d[46]),"+f"(d[47]),"+f"(d[48]),"+f"(d[49]),"+f"(d[50]),"+f"(d[51]),"+f"(d[52]),"+f"(d[53]),"+f"(d[54]),"+f"(d[55]),"+f"(d[56]),"+f"(d[57]),"+f"(d[58]),"+f"(d[59]),"+f"(d[60]),"+f"(d[61]),"+f"(d[62]),"+f"(d[63])
  : "l"(da), "l"(db), "r"(sc));
}
template<> __device__ __forceinline__ void wgmma_ss<192>(float* d, uint64_t da, uint64_t db, int sc) {
  asm volatile("{.reg .pred p; setp.ne.b32 p, %98, 0;\n"
  "wgmma.mma_async.sync.aligned.m64n192k16.f32.bf16.bf16 {%0,%1,%2,%3,%4,%5,%6,%7,%8,%9,%10,%11,%12,%13,%14,%15,%16,%17,%18,%19,%20,%21,%22,%23,%24,%25,%26,%27,%28,%29,%30,%31,%32,%33,%34,%35,%36,%37,%38,%39,%40,%41,%42,%43,%44,%45,%46,%47,%48,%49,%50,%51,%52,%53,%54,%55,%56,%57,%58,%59,%60,%61,%62,%63,%64,%65,%66,%67,%68,%69,%70,%71,%72,%73,%74,%75,%76,%77,%78,%79,%80,%81,%82,%83,%84,%85,%86,%87,%88,%89,%90,%91,%92,%93,%94,%95}, %96, %97, p, 1, 1, 0, 1;}\n"
  : "+f"(d[0]),"+f"(d[1]),"+f"(d[2]),"+f"(d[3]),"+f"(d[4]),"+f"(d[5]),"+f"(d[6]),"+f"(d[7]),"+f"(d[8]),"+f"(d[9]),"+f"(d[10]),"+f"(d[11]),"+f"(d[12]),"+f"(d[13]),"+f"(d[14]),"+f"(d[15]),"+f"(d[16]),"+f"(d[17]),"+f"(d[18]),"+f"(d[19]),"+f"(d[20]),"+f"(d[21]),"+f"(d[22]),"+f"(d[23]),"+f"(d[24]),"+f"(d[25]),"+f"(d[26]),"+f"(d[27]),"+f"(d[28]),"+f"(d[29]),"+f"(d[30]),"+f"(d[31]),"+f"(d[32]),"+f"(d[33]),"+f"(d[34]),"+f"(d[35]),"+f"(d[36]),"+f"(d[37]),"+f"(d[38]),"+f"(d[39]),"+f"(d[40]),"+f"(d[41]),"+f"(d[42]),"+f"(d[43]),"+f"(d[44]),"+f"(d[45]),"+f"(d[46]),"+f"(d[47]),"+f"(d[48]),"+f"(d[49]),"+f"(d[50]),"+f"(d[51]),"+f"(d[52]),"+f"(d[53]),"+f"(d[54]),"+f"(d[55]),"+f"(d[56]),"+f"(d[57]),"+f"(d[58]),"+f"(d[59]),"+f"(d[60]),"+f"(d[61]),"+f"(d[62]),"+f"(d[63]),"+f"(d[64]),"+f"(d[65]),"+f"(d[66]),"+f"(d[67]),"+f"(d[68]),"+f"(d[69]),"+f"(d[70]),"+f"(d[71]),"+f"(d[72]),"+f"(d[73]),"+f"(d[74]),"+f"(d[75]),"+f"(d[76]),"+f"(d[77]),"+f"(d[78]),"+f"(d[79]),"+f"(d[80]),"+f"(d[81]),"+f"(d[82]),"+f"(d[83]),"+f"(d[84]),"+f"(d[85]),"+f"(d[86]),"+f"(d[87]),"+f"(d[88]),"+f"(d[89]),"+f"(d[90]),"+f"(d[91]),"+f"(d[92]),"+f"(d[93]),"+f"(d[94]),"+f"(d[95])
  : "l"(da), "l"(db), "r"(sc));
}
template<> __device__ __forceinline__ void wgmma_ss<256>(float* d, uint64_t da, uint64_t db, int sc) {
  asm volatile("{.reg .pred p; setp.ne.b32 p, %130, 0;\n"
  "wgmma.mma_async.sync.aligned.m64n256k16.f32.bf16.bf16 {%0,%1,%2,%3,%4,%5,%6,%7,%8,%9,%10,%11,%12,%13,%14,%15,%16,%17,%18,%19,%20,%21,%22,%23,%24,%25,%26,%27,%28,%29,%30,%31,%32,%33,%34,%35,%36,%37,%38,%39,%40,%41,%42,%43,%44,%45,%46,%47,%48,%49,%50,%51,%52,%53,%54,%55,%56,%57,%58,%59,%60,%61,%62,%63,%64,%65,%66,%67,%68,%69,%70,%71,%72,%73,%74,%75,%76,%77,%78,%79,%80,%81,%82,%83,%84,%85,%86,%87,%88,%89,%90,%91,%92,%93,%94,%95,%96,%97,%98,%99,%100,%101,%102,%103,%104,%105,%106,%107,%108,%109,%110,%111,%112,%113,%114,%115,%116,%117,%118,%119,%120,%121,%122,%123,%124,%125,%126,%127}, %128, %129, p, 1, 1, 0, 1;}\n"
  : "+f"(d[0]),"+f"(d[1]),"+f"(d[2]),"+f"(d[3]),"+f"(d[4]),"+f"(d[5]),"+f"(d[6]),"+f"(d[7]),"+f"(d[8]),"+f"(d[9]),"+f"(d[10]),"+f"(d[11]),"+f"(d[12]),"+f"(d[13]),"+f"(d[14]),"+f"(d[15]),"+f"(d[16]),"+f"(d[17]),"+f"(d[18]),"+f"(d[19]),"+f"(d[20]),"+f"(d[21]),"+f"(d[22]),"+f"(d[23]),"+f"(d[24]),"+f"(d[25]),"+f"(d[26]),"+f"(d[27]),"+f"(d[28]),"+f"(d[29]),"+f"(d[30]),"+f"(d[31]),"+f"(d[32]),"+f"(d[33]),"+f"(d[34]),"+f"(d[35]),"+f"(d[36]),"+f"(d[37]),"+f"(d[38]),"+f"(d[39]),"+f"(d[40]),"+f"(d[41]),"+f"(d[42]),"+f"(d[43]),"+f"(d[44]),"+f"(d[45]),"+f"(d[46]),"+f"(d[47]),"+f"(d[48]),"+f"(d[49]),"+f"(d[50]),"+f"(d[51]),"+f"(d[52]),"+f"(d[53]),"+f"(d[54]),"+f"(d[55]),"+f"(d[56]),"+f"(d[57]),"+f"(d[58]),"+f"(d[59]),"+f"(d[60]),"+f"(d[61]),"+f"(d[62]),"+f"(d[63]),"+f"(d[64]),"+f"(d[65]),"+f"(d[66]),"+f"(d[67]),"+f"(d[68]),"+f"(d[69]),"+f"(d[70]),"+f"(d[71]),"+f"(d[72]),"+f"(d[73]),"+f"(d[74]),"+f"(d[75]),"+f"(d[76]),"+f"(d[77]),"+f"(d[78]),"+f"(d[79]),"+f"(d[80]),"+f"(d[81]),"+f"(d[82]),"+f"(d[83]),"+f"(d[84]),"+f"(d[85]),"+f"(d[86]),"+f"(d[87]),"+f"(d[88]),"+f"(d[89]),"+f"(d[90]),"+f"(d[91]),"+f"(d[92]),"+f"(d[93]),"+f"(d[94]),"+f"(d[95]),"+f"(d[96]),"+f"(d[97]),"+f"(d[98]),"+f"(d[99]),"+f"(d[100]),"+f"(d[101]),"+f"(d[102]),"+f"(d[103]),"+f"(d[104]),"+f"(d[105]),"+f"(d[106]),"+f"(d[107]),"+f"(d[108]),"+f"(d[109]),"+f"(d[110]),"+f"(d[111]),"+f"(d[112]),"+f"(d[113]),"+f"(d[114]),"+f"(d[115]),"+f"(d[116]),"+f"(d[117]),"+f"(d[118]),"+f"(d[119]),"+f"(d[120]),"+f"(d[121]),"+f"(d[122]),"+f"(d[123]),"+f"(d[124]),"+f"(d[125]),"+f"(d[126]),"+f"(d[127])
  : "l"(da), "l"(db), "r"(sc));
}

__device__ __forceinline__ void wg_fence() { asm volatile("wgmma.fence.sync.aligned;" ::: "memory"); }
__device__ __forceinline__ void wg_commit() { asm volatile("wgmma.commit_group.sync.aligned;" ::: "memory"); }
template <int N> __device__ __forceinline__ void wg_wait() { asm volatile("wgmma.wait_group.sync.aligned %0;" ::"n"(N) : "memory"); }
__device__ __forceinline__ uint64_t mkdesc(uint32_t addr, uint32_t lbo, uint32_t sbo, uint32_t swz) {
  return (uint64_t)((addr & 0x3FFFF) >> 4) | ((uint64_t)(lbo >> 4) << 16) | ((uint64_t)(sbo >> 4) << 32) | ((uint64_t)swz << 62);
}
__device__ __forceinline__ void mbar_init(uint32_t a, uint32_t c) { asm volatile("mbarrier.init.shared.b64 [%0], %1;" ::"r"(a), "r"(c) : "memory"); }
__device__ __forceinline__ void mbar_expect_tx(uint32_t a, uint32_t b) { asm volatile("mbarrier.arrive.expect_tx.shared.b64 _, [%0], %1;" ::"r"(a), "r"(b) : "memory"); }
__device__ __forceinline__ void mbar_arrive(uint32_t a) { asm volatile("mbarrier.arrive.shared.b64 _, [%0];" ::"r"(a) : "memory"); }
__device__ __forceinline__ void mbar_wait(uint32_t a, uint32_t parity) {
  asm volatile("{.reg .pred p; .reg .u32 n; mov.u32 n, 0;\n"
               "W: mbarrier.try_wait.parity.shared.b64 p, [%0], %1;\n"
               "@p bra.uni E; add.u32 n, n, 1; setp.lt.u32 p, n, 0x100000; @p bra.uni W; trap;\n"
               "E: }" ::"r"(a), "r"(parity) : "memory");
}
__device__ __forceinline__ void tma2d(uint32_t dst, const CUtensorMap* m, uint32_t bar, int c0, int c1) {
  asm volatile("cp.async.bulk.tensor.2d.shared::cluster.global.mbarrier::complete_tx::bytes [%0], [%1, {%3,%4}], [%2];"
               ::"r"(dst), "l"(m), "r"(bar), "r"(c0), "r"(c1) : "memory");
}
__device__ __forceinline__ void tma3d(uint32_t dst, const CUtensorMap* m, uint32_t bar, int c0, int c1, int c2) {
  asm volatile("cp.async.bulk.tensor.3d.shared::cluster.global.mbarrier::complete_tx::bytes [%0], [%1, {%3,%4,%5}], [%2];"
               ::"r"(dst), "l"(m), "r"(bar), "r"(c0), "r"(c1), "r"(c2) : "memory");
}
__device__ __forceinline__ void tma5d(uint32_t dst, const CUtensorMap* m, uint32_t bar, int c0, int c4) {
  asm volatile("cp.async.bulk.tensor.5d.shared::cluster.global.mbarrier::complete_tx::bytes [%0], [%1, {%3,%5,%5,%5,%4}], [%2];"
               ::"r"(dst), "l"(m), "r"(bar), "r"(c0), "r"(c4), "r"(0) : "memory");
}
__device__ __forceinline__ void bulk_g2s(uint32_t dst, const void* src, uint32_t bytes, uint32_t bar) {
  asm volatile("cp.async.bulk.shared::cluster.global.mbarrier::complete_tx::bytes [%0], [%1], %2, [%3];"
               ::"r"(dst), "l"(src), "r"(bytes), "r"(bar) : "memory");
}
__device__ __forceinline__ void prefetch_l2(const void* src, uint32_t bytes) {
  asm volatile("cp.async.bulk.prefetch.L2.global [%0], %1;" ::"l"(src), "r"(bytes) : "memory");
}
__device__ __forceinline__ void prefetch_tmap(const CUtensorMap* m) { asm volatile("prefetch.tensormap [%0];" ::"l"(m) : "memory"); }
__device__ __forceinline__ void fence_async_smem() { asm volatile("fence.proxy.async.shared::cta;" ::: "memory"); }
__device__ __forceinline__ void fence_async_global() { asm volatile("fence.proxy.async.global;" ::: "memory"); }
__device__ __forceinline__ void bar_sync(int id, int n) { asm volatile("bar.sync %0, %1;" ::"r"(id), "r"(n) : "memory"); }
__device__ __forceinline__ uint32_t lds32(uint32_t a) { uint32_t v; asm volatile("ld.volatile.shared.b32 %0,[%1];" : "=r"(v) : "r"(a)); return v; }
__device__ __forceinline__ uint2 lds64(uint32_t a) { uint2 v; asm volatile("ld.shared.v2.b32 {%0,%1},[%2];" : "=r"(v.x), "=r"(v.y) : "r"(a) : "memory"); return v; }
__device__ __forceinline__ uint4 lds128(uint32_t a) { uint4 v; asm volatile("ld.shared.v4.b32 {%0,%1,%2,%3},[%4];" : "=r"(v.x), "=r"(v.y), "=r"(v.z), "=r"(v.w) : "r"(a) : "memory"); return v; }
__device__ __forceinline__ float4 lds128f(uint32_t a) { float4 v; asm volatile("ld.shared.v4.f32 {%0,%1,%2,%3},[%4];" : "=f"(v.x), "=f"(v.y), "=f"(v.z), "=f"(v.w) : "r"(a) : "memory"); return v; }
__device__ __forceinline__ void sts128(uint32_t a, uint32_t x, uint32_t y, uint32_t z, uint32_t w) { asm volatile("st.shared.v4.b32 [%0],{%1,%2,%3,%4};" ::"r"(a), "r"(x), "r"(y), "r"(z), "r"(w) : "memory"); }
__device__ __forceinline__ uint32_t packbf(float lo, float hi) { uint32_t r; asm("cvt.rn.bf16x2.f32 %0, %1, %2;" : "=r"(r) : "f"(hi), "f"(lo)); return r; }
__device__ __forceinline__ uint32_t packbf_relu(float lo, float hi) { uint32_t r; asm("cvt.rn.relu.bf16x2.f32 %0, %1, %2;" : "=r"(r) : "f"(hi), "f"(lo)); return r; }
__device__ __forceinline__ uint32_t bmul2(uint32_t a, uint32_t b) { uint32_t r; asm("mul.rn.bf16x2 %0, %1, %2;" : "=r"(r) : "r"(a), "r"(b)); return r; }
__device__ __forceinline__ uint32_t bfma2(uint32_t a, uint32_t b, uint32_t c) { uint32_t r; asm("fma.rn.bf16x2 %0, %1, %2, %3;" : "=r"(r) : "r"(a), "r"(b), "r"(c)); return r; }
__device__ __forceinline__ float bflo(uint32_t v) { return __uint_as_float(v << 16); }
__device__ __forceinline__ float bfhi(uint32_t v) { return __uint_as_float(v & 0xffff0000u); }
__device__ __forceinline__ uint32_t ldg_relaxed(const uint32_t* p) { uint32_t v; asm volatile("ld.relaxed.gpu.global.b32 %0,[%1];" : "=r"(v) : "l"(p) : "memory"); return v; }
__device__ __forceinline__ void stg128(void* p, uint32_t x, uint32_t y, uint32_t z, uint32_t w) { asm volatile("st.global.v4.b32 [%0],{%1,%2,%3,%4};" ::"l"(p), "r"(x), "r"(y), "r"(z), "r"(w) : "memory"); }
__device__ __forceinline__ void stg64(void* p, uint32_t x, uint32_t y) { asm volatile("st.global.v2.b32 [%0],{%1,%2};" ::"l"(p), "r"(x), "r"(y) : "memory"); }
__device__ __forceinline__ uint4 ldg_relaxed4(const uint32_t* p) { uint4 v; asm volatile("ld.relaxed.gpu.global.v4.b32 {%0,%1,%2,%3},[%4];" : "=r"(v.x), "=r"(v.y), "=r"(v.z), "=r"(v.w) : "l"(p) : "memory"); return v; }
__device__ __forceinline__ void stg_relaxed4(uint32_t* p, uint32_t x, uint32_t y, uint32_t z, uint32_t w) { asm volatile("st.relaxed.gpu.global.v4.b32 [%0],{%1,%2,%3,%4};" ::"l"(p), "r"(x), "r"(y), "r"(z), "r"(w) : "memory"); }
__device__ __forceinline__ void signal(uint32_t* cnt) { asm volatile("red.release.gpu.global.add.u32 [%0], 1;" ::"l"(cnt) : "memory"); }
__device__ __forceinline__ void wait_count(const uint32_t* cnt, uint32_t target) {
  int it = 0;
  while (true) {
    uint32_t v;
    asm volatile("ld.acquire.gpu.global.b32 %0,[%1];" : "=r"(v) : "l"(cnt) : "memory");
    if ((int)(v - target) >= 0) break;
    __nanosleep(32);
    if (++it > (1 << 21)) __trap();
  }
}
__device__ __forceinline__ void mbar_wait_cluster(uint32_t a, uint32_t parity) {
  asm volatile("{.reg .pred p; .reg .u32 n; mov.u32 n, 0;\n"
               "W: mbarrier.try_wait.parity.acquire.cluster.shared::cta.b64 p, [%0], %1;\n"
               "@p bra.uni E; add.u32 n, n, 1; setp.lt.u32 p, n, 0x100000; @p bra.uni W; trap;\n"
               "E: }" ::"r"(a), "r"(parity) : "memory");
}
__device__ __forceinline__ void st_async128(uint32_t a, uint32_t bar, uint32_t x, uint32_t y, uint32_t z, uint32_t w) {
  asm volatile("st.async.weak.shared::cluster.mbarrier::complete_tx::bytes.v4.b32 [%0],{%2,%3,%4,%5},[%1];" ::"r"(a), "r"(bar), "r"(x), "r"(y), "r"(z), "r"(w) : "memory");
}

template <int LO, int HI> __device__ __forceinline__ void rename(float* d) {
#pragma unroll
  for (int i = LO; i < HI; i++) { float e; asm volatile("mov.b32 %0, %1;" : "=f"(e) : "f"(d[i])); d[i] = e; }
}
template <int M> __device__ __forceinline__ void drain4(const float* d, uint32_t ya) {
  uint32_t r[4];
#pragma unroll
  for (int q = 0; q < 4; q++) {
    const int mu = M + q;
    float v0 = d[4 * mu], v1 = d[4 * mu + 1];
    if (mu > 0) { v0 += d[4 * mu - 2]; v1 += d[4 * mu - 1]; }
    r[q] = packbf(v0, v1);
  }
  asm volatile("stmatrix.sync.aligned.m8n8.x4.trans.shared.b16 [%0],{%1,%2,%3,%4};" ::"r"(ya + M * 128), "r"(r[0]), "r"(r[1]), "r"(r[2]), "r"(r[3]) : "memory");
}
__device__ __forceinline__ void lda(uint32_t* a, uint32_t ua) { a[0] = lds32(ua); a[1] = lds32(ua + 128); a[2] = lds32(ua - 16); a[3] = lds32(ua + 112); }
template <int P> struct Pass {
  static __device__ __forceinline__ void run(float* d, uint32_t (*a)[4], uint32_t ua, uint64_t db, uint32_t ya, uint32_t ubar, bool first) {
    if constexpr (P > 0) rename<8 * (P - 1), 128>(d);
    wg_fence();
    wgmma_rs<256 - 16 * P>(d + 8 * P, a[P & 1], db, P != 0);
    wg_commit();
    if constexpr (P < 15) {
      if constexpr (P & 1) { if (first) { mbar_wait_cluster(ubar + 8 * ((P + 1) / 2), 0); if (threadIdx.x == 0) TS(48 + (P + 1) / 2); } }
      lda(a[(P + 1) & 1], ua + (P + 1) * 256);
    }
    if constexpr (P >= 2 && (P & 1) == 0) drain4<2 * P - 4>(d, ya);
    wg_wait<0>();
    if constexpr (P < 15) Pass<P + 1>::run(d, a, ua, db, ya, ubar, first);
    else { rename<120, 128>(d); drain4<28>(d, ya); }
  }
};

__device__ __forceinline__ uint32_t off_T(int r) { return r == 0 ? OFF_T0 : r == 1 ? OFF_T1 : r == 2 ? OFF_T2 : OFF_T3; }
__device__ __forceinline__ uint32_t off_Y(int r) { return r == 1 ? OFF_KVA : r == 2 ? OFF_KVB : OFF_X; }

template <int NT>
__device__ __forceinline__ void gemm1_main(float* out, uint32_t sb, int wg) {
  const uint32_t bar = sb + OFF_BAR;
  float acc[NT / 2];
  const bool elect = (threadIdx.x & 127) == 0;
  const uint64_t da0 = mkdesc(sb + wg * 8192, 16, 1024, 1), db0 = mkdesc(sb + 16384, 8192, 1024, 1);
  mbar_wait(bar + 8 * B_FULL1, 0);
  wg_fence();
#pragma unroll
  for (int kk = 0; kk < 4; kk++) wgmma_ss<NT>(acc, da0 + kk * 2, db0 + kk * 128, kk != 0);
  wg_commit();
#pragma unroll 1
  for (int kb = 1; kb < 16; kb++) {
    const int s = kb & 3;
    mbar_wait(bar + 8 * (B_FULL1 + s), (kb >> 2) & 1);
    const uint64_t da = da0 + s * 3072, db = db0 + s * 3072;
    wg_fence();
#pragma unroll
    for (int kk = 0; kk < 4; kk++) wgmma_ss<NT>(acc, da + kk * 2, db + kk * 128, 1);
    wg_commit();
    wg_wait<1>();
    if (elect) mbar_arrive(bar + 8 * (B_EMPTY1 + ((kb - 1) & 3)));
  }
  wg_wait<0>();
#pragma unroll
  for (int i = 0; i < NT / 2; i++) asm volatile("mov.b32 %0, %1;" : "=f"(out[i]) : "f"(acc[i]));
  if (elect) mbar_arrive(bar + 8 * (B_EMPTY1 + 3));
}

__global__ void __cluster_dims__(2, 1, 1) __launch_bounds__(NTHREADS, 1) fused_kernel(const __grid_constant__ Params P) {
  extern __shared__ __align__(1024) unsigned char smem[];
  const uint32_t sb = (uint32_t)__cvta_generic_to_shared(smem);
  const uint32_t bar = sb + OFF_BAR;
  const int tid = threadIdx.x, warp = tid >> 5, lane = tid & 31;
  const int c = blockIdx.x, m = c & 15, j = c >> 4;

  uint4 pre[4];
  uint32_t epoch = 0;
  if (warp == 0 && lane < 8) {
    pre[0] = __ldg((const uint4*)(P.ssm_k + (size_t)(8 * c + lane) * S));
    pre[1].x = __ldg((const unsigned short*)P.ssm_D + 8 * c + lane);
  }
  if (warp >= 8) {
    epoch = ldg_relaxed(g_epoch + c) + 1;
    const uint4* wp = (const uint4*)(P.shift_k + (size_t)32 * ((c & ~1) + (lane & 1)));
#pragma unroll
    for (int p = 0; p < 4; p++) pre[p] = __ldg(wp + p);
  }
  if (warp == 8) {
    if (lane == 0) { TS(0); prefetch_tmap(&P.tm_k); prefetch_tmap(&P.tm_v); }
#pragma unroll
    for (int h = 0; h < 2; h++) {
      const int i = lane + 32 * h;
      const uint32_t cnt = i < 8 ? 1 : i < 16 ? 2 : i < 24 ? 1 : i < 28 ? 8 : i < 32 ? 3 : i < 36 ? 1 : i < 40 ? 2 : i < 46 ? 1 : i < 52 ? 2 : i == 52 ? 3 : i == 53 ? 1 : i < 56 ? 8 : 3;
      if (i < B_COUNT) mbar_init(bar + 8 * i, cnt);
    }
    __syncwarp();
    if (lane < 24) mbar_expect_tx(bar + 8 * lane, lane < 8 ? 2 * KV_STAGE : lane < 16 ? 4080 : 8192);
    asm volatile("fence.mbarrier_init.release.cluster;" ::: "memory");
    fence_async_smem();
    __syncwarp();
    if (lane == 0) {
#pragma unroll 1
      for (int i = 0; i < 2; i++) {
        tma3d(sb + OFF_KVA + i * KV_STAGE, &P.tm_k, bar + 8 * (B_KVFULL + i), 8 * (c & ~1), 32 * i + 16 * (c & 1) - 1, 0);
        tma3d(sb + OFF_KVB + i * KV_STAGE, &P.tm_v, bar + 8 * (B_KVFULL + i), 8 * (c & ~1), 32 * i + 16 * (c & 1) - 1, 0);
        bulk_g2s(sb + OFF_T0 + 2 * UT_SIZE + i * KT_SIZE + 32, P.ssm_k + (size_t)(8 * c + i) * S + 8, 4080, bar + 8 * (B_KFULL + i));
      }
    }
  }
  if (warp == 1 && lane < 16) sts128(sb + off_T(lane >> 2) + (lane & 3) * UT_COPY, 0, 0, 0, 0);
  __syncthreads();
  asm volatile("barrier.cluster.arrive.relaxed.aligned;" ::: "memory");

  if (warp < 8) {
    if (warp == 0 && lane < 8) {
      const float k0 = bflo(pre[0].x) + bflo(pre[1].x);
      const uint32_t kt = sb + off_T(lane >> 1) + 2 * UT_SIZE + (lane & 1) * KT_SIZE;
      sts128(kt, 0, 0, 0, 0);
      sts128(kt + 16, (pre[0].x & 0xffff0000u) | (packbf(k0, 0.f) & 0xffffu), pre[0].y, pre[0].z, pre[0].w);
      fence_async_smem();
      mbar_arrive(bar + 8 * (B_KFULL + lane));
    }
    __syncwarp();
    asm volatile("barrier.cluster.wait.aligned;" ::: "memory");
    const int wg = warp >> 2, w = warp & 3, g = lane >> 2, t = lane & 3;
#pragma unroll 1
    for (int r = 0; r < 4; r++) {
      float d[128];
      uint32_t a[2][4];
      const uint32_t tb = sb + off_T(r);
      const uint32_t ua = tb + wg * UT_SIZE + ((g & 1) ? 0 : UT_COPY) + ((g >> 1) + 8 * w + 8 - t) * 4;
      const uint64_t db = mkdesc(tb + 2 * UT_SIZE + wg * KT_SIZE, 16, 128, 0);
      const uint32_t yb = sb + off_Y(r) + wg * YBUF + w * YW;
      if (r == 3) mbar_wait(bar + 8 * B_ZDONE, 0);
      if (lane < 2 * w) sts128(yb + lane * 16, 0, 0, 0, 0);
      mbar_wait(bar + 8 * (B_KFULL + 2 * r + wg), 0);
      if (r == 0) mbar_wait_cluster(bar + 8 * B_UFULL, 0);
      if (tid == 0) TS(1 + r);
      lda(a[0], ua);
      Pass<0>::run(d, a, ua, db, yb + (2 * w + lane) * 16, bar + 8 * B_UFULL, r == 0);
      __syncwarp();
      if (lane == 0) mbar_arrive(bar + 8 * (B_YFULL + r));
    }
    if (tid == 0) TS(5);
    {
      const int r0 = 128 * m + 64 * wg + 16 * w + g;
      float2 st0, st1;
#pragma unroll 1
      for (int tile = 0; tile < 2; tile++) {
        float acc[128];
        if (tile == 0) {
          gemm1_main<256>(acc, sb, wg);
          asm volatile("ld.global.cg.v2.f32 {%0,%1},[%2];" : "=f"(st0.x), "=f"(st0.y) : "l"(g_hstat + r0) : "memory");
          asm volatile("ld.global.cg.v2.f32 {%0,%1},[%2];" : "=f"(st1.x), "=f"(st1.y) : "l"(g_hstat + r0 + 8) : "memory");
          mbar_wait(bar + 8 * B_CSFULL, 0);
        } else {
          gemm1_main<192>(acc, sb, wg);
#pragma unroll
          for (int i = 96; i < 128; i++) asm volatile("mov.b32 %0, 0;" : "=f"(acc[i]));
        }
        if (tid == 0) TS(44 + tile);
        const uint32_t csb = sb + (tile ? OFF_CSB2 : OFF_X) + t * 16;
        __nv_bfloat16* p0 = g_act + (size_t)r0 * F + 448 * j + 256 * tile + 8 * t;
        __nv_bfloat16* p1 = p0 + 8 * F;
#pragma unroll
        for (int J = 0; J < 8; J++) {
          if (J == 6 && tile) break;
          uint32_t o0[4], o1[4];
#pragma unroll
          for (int jj = 0; jj < 4; jj++) {
            const int mu = 4 * J + jj;
            const float4 cb = lds128f(csb + mu * 64);
            const float a0 = fmaf(acc[4 * mu + 0], st0.y, fmaf(st0.x, cb.x, cb.z));
            const float a1 = fmaf(acc[4 * mu + 1], st0.y, fmaf(st0.x, cb.y, cb.w));
            const float a2 = fmaf(acc[4 * mu + 2], st1.y, fmaf(st1.x, cb.x, cb.z));
            const float a3 = fmaf(acc[4 * mu + 3], st1.y, fmaf(st1.x, cb.y, cb.w));
            const uint32_t u0 = packbf_relu(a0, a1), u1 = packbf_relu(a2, a3);
            o0[jj] = bmul2(u0, u0);
            o1[jj] = bmul2(u1, u1);
          }
          stg128(p0 + 32 * J, o0[0], o0[1], o0[2], o0[3]);
          stg128(p1 + 32 * J, o1[0], o1[1], o1[2], o1[3]);
        }
        fence_async_global();
        __syncwarp();
        if (lane == 0) mbar_arrive(bar + 8 * (B_ADONE + tile));
        if (tid == 0) TS(6 + tile);
      }
    }
    {
      float acc[64], res[64];
      const bool elect = (tid & 127) == 0;
      int s = 0, ph = 0, prev = 0;
#pragma unroll 1
      for (int kb = 0; kb < 56; kb++) {
        mbar_wait(bar + 8 * (B_FULL2 + s), ph);
        const uint32_t sa = sb + s * 32768;
        const uint64_t da = mkdesc(sa + wg * 8192, 16, 1024, 1), db = mkdesc(sa + 16384, 8192, 1024, 1);
        wg_fence();
#pragma unroll
        for (int kk = 0; kk < 4; kk++) wgmma_ss<128>(acc, da + kk * 2, db + kk * 128, (kb | kk) != 0);
        wg_commit();
        if (kb == 8) {
          mbar_wait(bar + 8 * B_HRES, 0);
          const uint32_t* b2p = (const uint32_t*)(P.b2 + 128 * j) + t;
#pragma unroll
          for (int h = 0; h < 2; h++) {
            const int row = 64 * wg + 16 * w + 8 * h + g;
            const uint32_t la = sb + OFF_X + row * 256 + t * 64;
            const int sw = (2 * row + (t >> 1)) & 3;
#pragma unroll
            for (int cc = 0; cc < 4; cc++) {
              const uint4 v = lds128(la + ((cc ^ sw) << 4));
              const uint32_t vv[4] = {v.x, v.y, v.z, v.w};
#pragma unroll
              for (int q = 0; q < 4; q++) {
                const int mu = 4 * cc + q;
                const uint32_t b = __ldg(b2p + 4 * mu);
                res[4 * mu + 2 * h] = bflo(vv[q]) + bflo(b);
                res[4 * mu + 2 * h + 1] = bfhi(vv[q]) + bfhi(b);
              }
            }
          }
        }
        wg_wait<1>();
        if (kb > 0 && elect) mbar_arrive(bar + 8 * (B_EMPTY2 + prev));
        prev = s;
        if (++s == 6) { s = 0; ph ^= 1; }
      }
      wg_wait<0>();
      rename<0, 64>(acc);
      if (tid == 0) TS(8);
      const int id = lane >> 3, row = 16 * w + (lane & 7) + 8 * (id & 1);
      const uint32_t ob = sb + OFF_X + wg * 16384 + row * 128;
#pragma unroll
      for (int mu = 0; mu < 16; mu += 2) {
        const uint32_t r0 = packbf(acc[4 * mu] + res[4 * mu], acc[4 * mu + 1] + res[4 * mu + 1]);
        const uint32_t r1 = packbf(acc[4 * mu + 2] + res[4 * mu + 2], acc[4 * mu + 3] + res[4 * mu + 3]);
        const uint32_t r2 = packbf(acc[4 * mu + 4] + res[4 * mu + 4], acc[4 * mu + 5] + res[4 * mu + 5]);
        const uint32_t r3 = packbf(acc[4 * mu + 6] + res[4 * mu + 6], acc[4 * mu + 7] + res[4 * mu + 7]);
        const int ch = (mu & 7) + (id >> 1);
        asm volatile("stmatrix.sync.aligned.m8n8.x4.shared.b16 [%0],{%1,%2,%3,%4};"
                     ::"r"(ob + (mu >> 3) * 8192 + ((ch ^ (row & 7)) << 4)), "r"(r0), "r"(r1), "r"(r2), "r"(r3) : "memory");
      }
      fence_async_smem();
      bar_sync(3 + wg, 128);
      if (elect) {
        for (int b = 0; b < 2; b++)
          asm volatile("cp.async.bulk.tensor.2d.global.shared::cta.bulk_group [%0, {%2,%3}], [%1];"
                       ::"l"(&P.tm_out), "r"(sb + OFF_X + wg * 16384 + b * 8192), "r"(128 * j + 64 * b), "r"(128 * m + 64 * wg) : "memory");
        asm volatile("cp.async.bulk.commit_group;" ::: "memory");
        asm volatile("cp.async.bulk.wait_group.read 0;" ::: "memory");
        if (tid == 0) TS(9);
      }
    }
  } else {
    if (warp == 8) {
      if (lane == 0) {
#pragma unroll 1
        for (int i = 2; i < 8; i++) {
          tma3d(sb + OFF_KVA + i * KV_STAGE, &P.tm_k, bar + 8 * (B_KVFULL + i), 8 * (c & ~1), 32 * i + 16 * (c & 1) - 1, 0);
          tma3d(sb + OFF_KVB + i * KV_STAGE, &P.tm_v, bar + 8 * (B_KVFULL + i), 8 * (c & ~1), 32 * i + 16 * (c & 1) - 1, 0);
        }
      }
      __syncwarp();
      asm volatile("barrier.cluster.wait.aligned;" ::: "memory");
      if (lane == 0) {
        prefetch_tmap(&P.tm_h); prefetch_tmap(&P.tm_w1); prefetch_tmap(&P.tm_act); prefetch_tmap(&P.tm_w2);
        prefetch_tmap(&P.tm_hres); prefetch_tmap(&P.tm_out);
        mbar_wait(bar + 8 * (B_KVFULL + KV_GATE), 0);
#pragma unroll 1
        for (int ch = 2; ch < 8; ch++) {
          if (ch == 4) prefetch_l2(P.x + (size_t)(128 * m + 16 * j) * D, 16 * D * 2);
          bulk_g2s(sb + off_T(ch >> 1) + 2 * UT_SIZE + (ch & 1) * KT_SIZE + 32, P.ssm_k + (size_t)(8 * c + ch) * S + 8, 4080, bar + 8 * (B_KFULL + ch));
        }
        mbar_wait(bar + 8 * (B_KFULL + 7), 0);
        TS(31);
        prefetch_l2(P.w1 + (size_t)c * 8 * F, 8 * F * 2);
#pragma unroll 1
        for (int it = 0; it < 32; it++) {
          const int s = it & 3, kb = it & 15, tile = it >> 4;
          mbar_wait(bar + 8 * (it < 2 ? B_ZDONE + 1 : it == 2 ? B_ZDONE + 2 : it == 3 ? B_YFULL + 3 : B_EMPTY1 + s), it < 4 ? 0 : ((it >> 2) - 1) & 1);
          if (it < 4) fence_async_smem();
          const uint32_t sa = sb + s * 49152, fb = bar + 8 * (B_FULL1 + s);
          const int nb = tile ? 3 : 4, n0 = 448 * j + 256 * tile;
          mbar_expect_tx(fb, 16384 + nb * 8192);
#pragma unroll 1
          for (int i = 0; i < nb; i++) tma3d(sa + 16384 + i * 8192, &P.tm_w1, fb, n0 + 64 * i, 2 * (kb >> 2), 32 * (kb & 3));
          if (it < 16 && (it & 3) == 0) { wait_count(g_hcnt + ((it >> 2) * 16 + m) * 32, epoch * 24); fence_async_global(); TS(11 + (it >> 2)); }
          tma2d(sa, &P.tm_h, fb, 64 * kb, 128 * m);
          if (it == 8) prefetch_l2(P.w2 + (size_t)c * 28 * D, 28 * D * 2);
          if (it == 21) {
            mbar_expect_tx(bar + 8 * B_HRES, 32768);
            tma3d(sb + OFF_X, &P.tm_hres, bar + 8 * B_HRES, 32 * j, 0, 128 * m);
          }
        }
        int s = 0, ph = 1;
#pragma unroll 1
        for (int kb = 0; kb < 56; kb++) {
          mbar_wait(bar + 8 * (kb < 6 ? B_EMPTY1 + (2 * kb + 1) / 3 : B_EMPTY2 + s), ph);
          const int col = kb < 32 ? 448 * (kb >> 2) + 64 * (kb & 3) : 448 * ((kb - 32) / 3) + 256 + 64 * ((kb - 32) % 3);
          const uint32_t sa = sb + s * 32768, fb = bar + 8 * (B_FULL2 + s);
          mbar_expect_tx(fb, 32768);
          tma5d(sa + 16384, &P.tm_w2, fb, 128 * j, col >> 5);
          tma5d(sa + 24576, &P.tm_w2, fb, 128 * j + 64, col >> 5);
          if ((kb & 31) == 0) { wait_count(g_acnt + ((kb >> 5) * 16 + m) * 32, epoch * 8); fence_async_global(); TS(15 + (kb >> 5)); }
          tma2d(sa, &P.tm_act, fb, col, 128 * m);
          if (++s == 6) { s = 0; ph ^= 1; }
        }
      }
    } else {
      const int zw = warp - 9;
      {
        uint32_t W[4][4];
#pragma unroll
        for (int p = 0; p < 4; p++) {
          W[0][p] = __byte_perm(pre[p].x, pre[p].z, 0x5410); W[1][p] = __byte_perm(pre[p].x, pre[p].z, 0x7632);
          W[2][p] = __byte_perm(pre[p].y, pre[p].w, 0x5410); W[3][p] = __byte_perm(pre[p].y, pre[p].w, 0x7632);
        }
        uint32_t rb;
        asm volatile("mapa.shared::cluster.u32 %0, %1, %2;" : "=r"(rb) : "r"(sb), "r"(lane & 1));
        asm volatile("barrier.cluster.wait.aligned;" ::: "memory");
#pragma unroll 1
        for (int st = zw; st < 8; st += 3) {
          mbar_wait(bar + 8 * (B_KVFULL + st), 0);
          const uint32_t ka = sb + OFF_KVA + st * KV_STAGE + lane * 16, va = sb + OFF_KVB + st * KV_STAGE + lane * 16;
          uint32_t u[9][4];
          uint4 k3 = lds128(ka + 4 * 544), k2 = lds128(ka + 5 * 544), k1 = lds128(ka + 6 * 544);
#pragma unroll
          for (int i = 0; i < 9; i++) {
            const uint32_t o = i == 0 ? 7 * 544 : (i - 1) * 544 + 32;
            const uint4 k0 = lds128(ka + o), v = lds128(va + o);
            u[i][0] = bmul2(bfma2(k0.x, W[0][0], bfma2(k1.x, W[1][0], bfma2(k2.x, W[2][0], bmul2(k3.x, W[3][0])))), v.x);
            u[i][1] = bmul2(bfma2(k0.y, W[0][1], bfma2(k1.y, W[1][1], bfma2(k2.y, W[2][1], bmul2(k3.y, W[3][1])))), v.y);
            u[i][2] = bmul2(bfma2(k0.z, W[0][2], bfma2(k1.z, W[1][2], bfma2(k2.z, W[2][2], bmul2(k3.z, W[3][2])))), v.z);
            u[i][3] = bmul2(bfma2(k0.w, W[0][3], bfma2(k1.w, W[1][3], bfma2(k2.w, W[2][3], bmul2(k3.w, W[3][3])))), v.w);
            k3 = k2; k2 = k1; k1 = k0;
          }
          const uint32_t ub = rb + OFF_BAR + 8 * (B_UFULL + st);
#pragma unroll
          for (int p = 0; p < 4; p++) {
            const uint32_t ta = rb + off_T(p) + 16 + (32 * st + 16 * (c & 1) + (lane >> 1)) * 16;
#pragma unroll
            for (int e = 0; e < 2; e++) {
              const uint32_t sel = e ? 0x7632 : 0x5410;
              st_async128(ta + e * UT_SIZE, ub, __byte_perm(u[2][p], u[1][p], sel), __byte_perm(u[4][p], u[3][p], sel),
                          __byte_perm(u[6][p], u[5][p], sel), __byte_perm(u[8][p], u[7][p], sel));
              st_async128(ta + e * UT_SIZE + UT_COPY, ub, __byte_perm(u[1][p], u[0][p], sel), __byte_perm(u[3][p], u[2][p], sel),
                          __byte_perm(u[5][p], u[4][p], sel), __byte_perm(u[7][p], u[6][p], sel));
            }
          }
        }
      }
      if (tid == 288) TS(43);
      const int q = lane & 3, ip = 8 * (2 - zw) + (lane >> 2);
      const int rowb = 128 * m + 16 * j, row0 = rowb + 4 * q;
      float s1[4] = {0.f, 0.f, 0.f, 0.f}, s2[4] = {0.f, 0.f, 0.f, 0.f};
#pragma unroll 1
      for (int ev = 0; ev < 8; ev++) {
        const int r = (0xed90 >> (2 * ev)) & 3;
        if (((0x5104 >> (2 * ev)) & 3) == 0) {
          mbar_wait(bar + 8 * (B_YFULL + r), 0);
          const uint32_t yb = sb + off_Y(r) + lane * 8;
          uint32_t* zp = g_z + (size_t)(r * NCTA + c) * S + lane * 4;
          uint2 p[8];
#pragma unroll
          for (int i = 0; i < 8; i++) p[i] = lds64(yb + i * YW + zw * 256);
#pragma unroll 1
          for (int task = zw; task < 16; task += 3) {
            float a[2][4];
#pragma unroll
            for (int e = 0; e < 2; e++) {
              a[e][0] = (bflo(p[4 * e].x) + bflo(p[4 * e + 1].x)) + (bflo(p[4 * e + 2].x) + bflo(p[4 * e + 3].x));
              a[e][1] = (bfhi(p[4 * e].x) + bfhi(p[4 * e + 1].x)) + (bfhi(p[4 * e + 2].x) + bfhi(p[4 * e + 3].x));
              a[e][2] = (bflo(p[4 * e].y) + bflo(p[4 * e + 1].y)) + (bflo(p[4 * e + 2].y) + bflo(p[4 * e + 3].y));
              a[e][3] = (bfhi(p[4 * e].y) + bfhi(p[4 * e + 1].y)) + (bfhi(p[4 * e + 2].y) + bfhi(p[4 * e + 3].y));
              const int nt = min(task + 3, 15);
#pragma unroll
              for (int i = 4 * e; i < 4 * e + 4; i++) p[i] = lds64(yb + i * YW + nt * 256);
            }
            stg_relaxed4(zp + task * 128, max(packbf(a[0][0], a[1][0]), 1u), max(packbf(a[0][1], a[1][1]), 1u),
                         max(packbf(a[0][2], a[1][2]), 1u), max(packbf(a[0][3], a[1][3]), 1u));
          }
          __syncwarp();
          if (lane == 0) mbar_arrive(bar + 8 * (B_ZDONE + r));
          if (tid == 288) TS(17 + r);
        } else {
          if (r == 0) {
            const uint4* xp = (const uint4*)(P.x + (size_t)rowb * D) + lane;
            uint4 v[4];
#pragma unroll
            for (int k = 0; k < 4; k++) v[k] = __ldg(xp + zw * 128 + 32 * k);
#pragma unroll 1
            for (int row = zw; row < 16; row += 3) {
              float t1 = 0.f, t2 = 0.f;
              const int nr = min(row + 3, 15);
#pragma unroll
              for (int k = 0; k < 4; k++) {
                const uint32_t vv[4] = {v[k].x, v[k].y, v[k].z, v[k].w};
                v[k] = __ldg(xp + nr * 128 + 32 * k);
#pragma unroll
                for (int i = 0; i < 4; i++) {
                  const float lo = bflo(vv[i]), hi = bfhi(vv[i]);
                  t1 += lo + hi;
                  t2 = fmaf(lo, lo, fmaf(hi, hi, t2));
                }
              }
#pragma unroll
              for (int o = 1; o < 32; o <<= 1) { t1 += __shfl_xor_sync(0xffffffffu, t1, o); t2 += __shfl_xor_sync(0xffffffffu, t2, o); }
              const float mu = t1 * (1.f / D);
              const float rs = rsqrtf(fmaxf(fmaf(-mu, mu, t2 * (1.f / D)), 0.f) + 1e-5f);
              if (lane == 0) ((float2*)(smem + OFF_XS))[row] = make_float2(-mu * rs, rs);
            }
            bar_sync(1, 96);
            if (tid == 288) TS(22);
          }
          uint32_t xv[3][4][2];
          uint4 zv[3][2];
          const bool full = zw > 0;
          const uint32_t* xp = (const uint32_t*)(P.x + (size_t)row0 * D) + 8 * ip + r;
#pragma unroll
          for (int k = 0; k < 3; k++)
#pragma unroll
            for (int a = 0; a < 4; a++)
#pragma unroll
              for (int e = 0; e < 2; e++) xv[k][a][e] = (k < 2 || full) ? __ldg(xp + a * (D / 2) + 192 * k + 4 * e) : 0;
          uint32_t* zp = g_z + (size_t)(r * NCTA + 2 * ip) * S + row0;
          zv[2][0] = zv[2][1] = make_uint4(1, 1, 1, 1);
          {
            int it = 0;
            while (true) {
              uint32_t lo = 1;
#pragma unroll
              for (int k = 0; k < 3; k++)
#pragma unroll
                for (int e = 0; e < 2; e++)
                  if (k < 2 || full) zv[k][e] = ldg_relaxed4(zp + (size_t)(48 * k + e) * S);
#pragma unroll
              for (int k = 0; k < 3; k++)
#pragma unroll
                for (int e = 0; e < 2; e++) lo = min(min(lo, min(zv[k][e].x, zv[k][e].y)), min(zv[k][e].z, zv[k][e].w));
              if (__all_sync(0xffffffffu, lo != 0)) break;
              __nanosleep(64);
              if (++it > (1 << 20)) __trap();
            }
          }
          if (tid == 288) TS(27 + r);
          __nv_bfloat16* hp = g_h + (size_t)row0 * D + 256 * r + 4 * ip;
          float2 xs[4];
#pragma unroll
          for (int a = 0; a < 4; a++) xs[a] = ((const float2*)(smem + OFF_XS))[4 * q + a];
#pragma unroll
          for (int k = 0; k < 3; k++) {
            if (k == 2 && !full) break;
#pragma unroll
            for (int a = 0; a < 4; a++) {
              uint32_t o[2];
#pragma unroll
              for (int e = 0; e < 2; e++) {
                const uint32_t xx = xv[k][a][e];
                const uint32_t zz = a == 0 ? zv[k][e].x : a == 1 ? zv[k][e].y : a == 2 ? zv[k][e].z : zv[k][e].w;
                const float x0 = bflo(xx), x1 = bfhi(xx);
                o[e] = packbf(fmaf(fmaf(x0, xs[a].y, xs[a].x), bflo(zz), x0), fmaf(fmaf(x1, xs[a].y, xs[a].x), bfhi(zz), x1));
                const float f0 = bflo(o[e]), f1 = bfhi(o[e]);
                s1[a] += f0 + f1;
                s2[a] = fmaf(f0, f0, fmaf(f1, f1, s2[a]));
              }
              stg64(hp + a * D + 96 * k, o[0], o[1]);
            }
          }
          if (r == 3) {
            float* red = (float*)(smem + OFF_RED);
#pragma unroll
            for (int a = 0; a < 4; a++) {
#pragma unroll
              for (int o = 4; o < 32; o <<= 1) {
                s1[a] += __shfl_xor_sync(0xffffffffu, s1[a], o);
                s2[a] += __shfl_xor_sync(0xffffffffu, s2[a], o);
              }
              if (lane < 4) ((float2*)red)[zw * 16 + 4 * q + a] = make_float2(s1[a], s2[a]);
            }
            bar_sync(1, 96);
            if (zw == 0 && lane < 16) {
              const float mu = (red[2 * lane] + red[32 + 2 * lane] + red[64 + 2 * lane]) * (1.f / D);
              const float e2 = (red[2 * lane + 1] + red[33 + 2 * lane] + red[65 + 2 * lane]) * (1.f / D);
              const float rs = rsqrtf(fmaxf(fmaf(-mu, mu, e2), 0.f) + 1e-5f);
              g_hstat[rowb + lane] = make_float2(-mu * rs, rs);
            }
          }
          fence_async_global();
          __syncwarp();
          if (tid == 288) TS(23 + r);
          if (lane == 0) signal(g_hcnt + (r * 16 + m) * 32);
          if (tid == 288) TS(32 + r);
#pragma unroll
          for (int k = 0; k < 3; k++)
#pragma unroll
            for (int e = 0; e < 2; e++)
              if (k < 2 || full) stg_relaxed4(zp + (size_t)(48 * k + e) * S, 0, 0, 0, 0);
        }
      }
      if (m < 14) {
        float cs[8];
#pragma unroll
        for (int i = 0; i < 8; i++) cs[i] = 0.f;
        const __nv_bfloat16* wp = P.w1 + (size_t)(lane >> 2) * F + 448 * j + 32 * m + 8 * (lane & 3);
#pragma unroll 1
        for (int b = 0; b < 4; b++) {
          uint4 v[11];
#pragma unroll
          for (int i = 0; i < 11; i++) {
            const int task = zw + 3 * (11 * b + i);
            v[i] = task < 128 ? __ldg((const uint4*)(wp + (size_t)task * 8 * F)) : make_uint4(0, 0, 0, 0);
          }
#pragma unroll
          for (int i = 0; i < 11; i++) {
            cs[0] += bflo(v[i].x); cs[1] += bfhi(v[i].x); cs[2] += bflo(v[i].y); cs[3] += bfhi(v[i].y);
            cs[4] += bflo(v[i].z); cs[5] += bfhi(v[i].z); cs[6] += bflo(v[i].w); cs[7] += bfhi(v[i].w);
          }
        }
#pragma unroll
        for (int i = 0; i < 8; i++) {
          cs[i] += __shfl_xor_sync(0xffffffffu, cs[i], 4);
          cs[i] += __shfl_xor_sync(0xffffffffu, cs[i], 8);
          cs[i] += __shfl_xor_sync(0xffffffffu, cs[i], 16);
        }
        float* red2 = (float*)(smem + OFF_CSB2);
        if (lane < 4) {
#pragma unroll
          for (int i = 0; i < 8; i++) red2[zw * 32 + lane * 8 + i] = cs[i];
        }
        bar_sync(1, 96);
        if (zw == 0) {
          g_cs[448 * j + 32 * m + lane] = red2[lane] + red2[32 + lane] + red2[64 + lane];
          __syncwarp();
          if (lane == 0) signal(g_ccnt + j * 32);
        }
      }
      if (tid == 288) wait_count(g_ccnt + j * 32, epoch * 14);
      bar_sync(1, 96);
#pragma unroll 1
      for (int i = zw * 32 + lane; i < 224; i += 96) {
        float2 cv;
        asm volatile("ld.global.cg.v2.f32 {%0,%1},[%2];" : "=f"(cv.x), "=f"(cv.y) : "l"(g_cs + 448 * j + 2 * i) : "memory");
        const uint32_t b = __ldg((const uint32_t*)(P.b1 + 448 * j) + i);
        const uint32_t dst = i < 128 ? sb + OFF_X + i * 16 : sb + OFF_CSB2 + (i - 128) * 16;
        sts128(dst, __float_as_uint(cv.x), __float_as_uint(cv.y), __float_as_uint(bflo(b)), __float_as_uint(bfhi(b)));
      }
      __syncwarp();
      if (lane == 0) mbar_arrive(bar + 8 * B_CSFULL);
      if (tid == 288) {
        TS(21);
#pragma unroll 1
        for (int tile = 0; tile < 2; tile++) {
          mbar_wait(bar + 8 * (B_ADONE + tile), 0);
          signal(g_acnt + (tile * 16 + m) * 32);
          TS(41 + tile);
        }
        g_epoch[c] = epoch;
      }
    }
  }
}

typedef CUresult (*PFN_encode)(CUtensorMap*, CUtensorMapDataType, cuuint32_t, void*, const cuuint64_t*, const cuuint64_t*, const cuuint32_t*,
                               const cuuint32_t*, CUtensorMapInterleave, CUtensorMapSwizzle, CUtensorMapL2promotion, CUtensorMapFloatOOBfill);

void encode(PFN_encode enc, CUtensorMap* m, const void* ptr, int rank, const cuuint64_t* dims, const cuuint64_t* strides, const cuuint32_t* box,
            CUtensorMapSwizzle swz) {
  const cuuint32_t es[5] = {1, 1, 1, 1, 1};
  enc(m, CU_TENSOR_MAP_DATA_TYPE_BFLOAT16, rank, (void*)ptr, dims, strides, box, es, CU_TENSOR_MAP_INTERLEAVE_NONE, swz,
      CU_TENSOR_MAP_L2_PROMOTION_L2_128B, CU_TENSOR_MAP_FLOAT_OOB_FILL_NONE);
}

}

extern "C" void kernel_launch(void* const* d_in, const int* in_sizes, int n_in, void* d_out, int out_size) {
  static PFN_encode enc = nullptr;
  static void *p_h = nullptr, *p_act = nullptr;
  if (!enc) {
    cudaDriverEntryPointQueryResult qr;
    cudaGetDriverEntryPoint("cuTensorMapEncodeTiled", (void**)&enc, cudaEnableDefault, &qr);
    cudaGetSymbolAddress(&p_h, g_h);
    cudaGetSymbolAddress(&p_act, g_act);
    cudaFuncSetAttribute(fused_kernel, cudaFuncAttributeMaxDynamicSharedMemorySize, SMEM_BYTES);
  }
  Params P;
  P.x = (const __nv_bfloat16*)d_in[0];
  P.shift_k = (const __nv_bfloat16*)d_in[3];
  P.ssm_k = (const __nv_bfloat16*)d_in[4];
  P.ssm_D = (const __nv_bfloat16*)d_in[5];
  P.w1 = (const __nv_bfloat16*)d_in[7];
  P.b1 = (const __nv_bfloat16*)d_in[8];
  P.w2 = (const __nv_bfloat16*)d_in[9];
  P.b2 = (const __nv_bfloat16*)d_in[10];
  {
    const cuuint64_t dims[3] = {D, S / 8, 8}, str[2] = {8 * D * 2, D * 2};
    const cuuint32_t box[3] = {16, 17, 8};
    encode(enc, &P.tm_k, d_in[1], 3, dims, str, box, CU_TENSOR_MAP_SWIZZLE_NONE);
    encode(enc, &P.tm_v, d_in[2], 3, dims, str, box, CU_TENSOR_MAP_SWIZZLE_NONE);
  }
  {
    const cuuint64_t dims[2] = {D, S}, str[1] = {D * 2};
    const cuuint32_t box[2] = {64, 128}, boxo[2] = {64, 64};
    encode(enc, &P.tm_h, p_h, 2, dims, str, box, CU_TENSOR_MAP_SWIZZLE_128B);
    encode(enc, &P.tm_out, d_out, 2, dims, str, boxo, CU_TENSOR_MAP_SWIZZLE_128B);
  }
  {
    const cuuint64_t dims[3] = {F, 8, D / 8}, str[2] = {F * 2, 8 * F * 2};
    const cuuint32_t box[3] = {64, 2, 32};
    encode(enc, &P.tm_w1, P.w1, 3, dims, str, box, CU_TENSOR_MAP_SWIZZLE_128B);
  }
  {
    const cuuint64_t dims[2] = {F, S}, str[1] = {F * 2};
    const cuuint32_t box[2] = {64, 128};
    encode(enc, &P.tm_act, p_act, 2, dims, str, box, CU_TENSOR_MAP_SWIZZLE_128B);
  }
  {
    const cuuint64_t dims[5] = {D, 2, 4, 4, F / 32}, str[4] = {D * 2, 8 * D * 2, 2 * D * 2, 32 * D * 2};
    const cuuint32_t box[5] = {64, 2, 4, 4, 2};
    encode(enc, &P.tm_w2, P.w2, 5, dims, str, box, CU_TENSOR_MAP_SWIZZLE_128B);
  }
  {
    const cuuint64_t dims[3] = {256, 4, S}, str[2] = {512, D * 2};
    const cuuint32_t box[3] = {32, 4, 128};
    encode(enc, &P.tm_hres, p_h, 3, dims, str, box, CU_TENSOR_MAP_SWIZZLE_64B);
  }
  fused_kernel<<<NCTA, NTHREADS, SMEM_BYTES>>>(P);
}
```

```cpp
#include <cuda_runtime.h>
#include <cuda_bf16.h>
#include <cuda.h>
#include <stdint.h>

#define DBG_TS 0
#define KV_GATE 5
#define ST_SLEEP 200

namespace {

constexpr int S = 2048, D = 1024, F = 3584;
constexpr int NCTA = 128, NTHREADS = 384;

constexpr int UT_COPY = 1040 * 4;
constexpr int UT_SIZE = 2 * UT_COPY;
constexpr int KT_SIZE = 16 + 4096;
constexpr int T_SIZE = 2 * (UT_SIZE + KT_SIZE);
constexpr int KV_STAGE = 17 * 8 * 32;
constexpr int KV_SIZE = 8 * KV_STAGE;
constexpr int YW = 4096 + 96;
constexpr int YBUF = 4 * YW;
constexpr int OFF_T3 = 196608 - T_SIZE;
constexpr int OFF_KVB = (OFF_T3 - KV_SIZE) & ~127;
constexpr int OFF_T2 = OFF_KVB - T_SIZE;
constexpr int OFF_KVA = (OFF_T2 - KV_SIZE) & ~127;
constexpr int OFF_T1 = OFF_KVA - T_SIZE;
constexpr int OFF_T0 = OFF_T1 - T_SIZE;
constexpr int OFF_X = 196608;
constexpr int OFF_CSB = OFF_X + 32768;
constexpr int OFF_RED = OFF_X + 34816;
constexpr int OFF_XS = OFF_X + 35072;
constexpr int OFF_BAR = OFF_X + 35200;
constexpr int SMEM_BYTES = 232448;
static_assert(OFF_T0 >= 0 && 2 * YBUF <= KV_SIZE && OFF_X + 2 * YBUF <= OFF_RED && OFF_BAR + 640 <= SMEM_BYTES, "smem map");
static_assert(OFF_T2 >= 98304, "stage 1 must only overlap T0,T1,KVA");
static_assert(OFF_T3 >= 147456, "stage 2 must not overlap T3");

enum {
  B_KVFULL = 0, B_KFULL = 8, B_UFULL = 16, B_YFULL = 24  , B_FULL1 = 40, B_ZDONE = 44, B_FULL2 = 48, B_CSFULL = 54, B_HRES = 55,
  B_EMPTY1 = 56, B_XFREE = 60, B_EMPTY2 = 64, B_ADONE = 72
};

struct Params {
  CUtensorMap tm_k, tm_v, tm_h, tm_w1, tm_act, tm_actst, tm_w2, tm_hres, tm_out;
  const __nv_bfloat16 *x, *shift_k, *ssm_k, *ssm_D, *w1, *b1, *w2, *b2;
};

__device__ __align__(1024) uint32_t g_z[4 * NCTA * S];
__device__ __align__(1024) __nv_bfloat16 g_h[S * D];
__device__ __align__(1024) __nv_bfloat16 g_act[S * F];
__device__ __align__(128) float2 g_hstat[S];
__device__ __align__(128) float g_cs[F];
__device__ __align__(128) uint32_t g_hcnt[4 * 16 * 32];
__device__ __align__(128) uint32_t g_acnt[2 * 16 * 32];
__device__ __align__(128) uint32_t g_ccnt[2 * 8 * 32];
__device__ __align__(128) uint32_t g_epoch[NCTA];
#define TS(slot) do {} while (0)

template<int N> __device__ __forceinline__ void wgmma_rs(float* d, const uint32_t* a, uint64_t db, int sc);
template<int N> __device__ __forceinline__ void wgmma_ss(float* d, uint64_t da, uint64_t db, int sc);
template<> __device__ __forceinline__ void wgmma_rs<16>(float* d, const uint32_t* a, uint64_t db, int sc) {
  asm volatile("{.reg .pred p; setp.ne.b32 p, %13, 0;\n"
  "wgmma.mma_async.sync.aligned.m64n16k16.f32.bf16.bf16 {%0,%1,%2,%3,%4,%5,%6,%7}, {%8,%9,%10,%11}, %12, p, 1, 1, 0;}\n"
  : "+f"(d[0]),"+f"(d[1]),"+f"(d[2]),"+f"(d[3]),"+f"(d[4]),"+f"(d[5]),"+f"(d[6]),"+f"(d[7])
  : "r"(a[0]), "r"(a[1]), "r"(a[2]), "r"(a[3]), "l"(db), "r"(sc));
}
template<> __device__ __forceinline__ void wgmma_rs<32>(float* d, const uint32_t* a, uint64_t db, int sc) {
  asm volatile("{.reg .pred p; setp.ne.b32 p, %21, 0;\n"
  "wgmma.mma_async.sync.aligned.m64n32k16.f32.bf16.bf16 {%0,%1,%2,%3,%4,%5,%6,%7,%8,%9,%10,%11,%12,%13,%14,%15}, {%16,%17,%18,%19}, %20, p, 1, 1, 0;}\n"
  : "+f"(d[0]),"+f"(d[1]),"+f"(d[2]),"+f"(d[3]),"+f"(d[4]),"+f"(d[5]),"+f"(d[6]),"+f"(d[7]),"+f"(d[8]),"+f"(d[9]),"+f"(d[10]),"+f"(d[11]),"+f"(d[12]),"+f"(d[13]),"+f"(d[14]),"+f"(d[15])
  : "r"(a[0]), "r"(a[1]), "r"(a[2]), "r"(a[3]), "l"(db), "r"(sc));
}
template<> __device__ __forceinline__ void wgmma_rs<48>(float* d, const uint32_t* a, uint64_t db, int sc) {
  asm volatile("{.reg .pred p; setp.ne.b32 p, %29, 0;\n"
  "wgmma.mma_async.sync.aligned.m64n48k16.f32.bf16.bf16 {%0,%1,%2,%3,%4,%5,%6,%7,%8,%9,%10,%11,%12,%13,%14,%15,%16,%17,%18,%19,%20,%21,%22,%23}, {%24,%25,%26,%27}, %28, p, 1, 1, 0;}\n"
  : "+f"(d[0]),"+f"(d[1]),"+f"(d[2]),"+f"(d[3]),"+f"(d[4]),"+f"(d[5]),"+f"(d[6]),"+f"(d[7]),"+f"(d[8]),"+f"(d[9]),"+f"(d[10]),"+f"(d[11]),"+f"(d[12]),"+f"(d[13]),"+f"(d[14]),"+f"(d[15]),"+f"(d[16]),"+f"(d[17]),"+f"(d[18]),"+f"(d[19]),"+f"(d[20]),"+f"(d[21]),"+f"(d[22]),"+f"(d[23])
  : "r"(a[0]), "r"(a[1]), "r"(a[2]), "r"(a[3]), "l"(db), "r"(sc));
}
template<> __device__ __forceinline__ void wgmma_rs<64>(float* d, const uint32_t* a, uint64_t db, int sc) {
  asm volatile("{.reg .pred p; setp.ne.b32 p, %37, 0;\n"
  "wgmma.mma_async.sync.aligned.m64n64k16.f32.bf16.bf16 {%0,%1,%2,%3,%4,%5,%6,%7,%8,%9,%10,%11,%12,%13,%14,%15,%16,%17,%18,%19,%20,%21,%22,%23,%24,%25,%26,%27,%28,%29,%30,%31}, {%32,%33,%34,%35}, %36, p, 1, 1, 0;}\n"
  : "+f"(d[0]),"+f"(d[1]),"+f"(d[2]),"+f"(d[3]),"+f"(d[4]),"+f"(d[5]),"+f"(d[6]),"+f"(d[7]),"+f"(d[8]),"+f"(d[9]),"+f"(d[10]),"+f"(d[11]),"+f"(d[12]),"+f"(d[13]),"+f"(d[14]),"+f"(d[15]),"+f"(d[16]),"+f"(d[17]),"+f"(d[18]),"+f"(d[19]),"+f"(d[20]),"+f"(d[21]),"+f"(d[22]),"+f"(d[23]),"+f"(d[24]),"+f"(d[25]),"+f"(d[26]),"+f"(d[27]),"+f"(d[28]),"+f"(d[29]),"+f"(d[30]),"+f"(d[31])
  : "r"(a[0]), "r"(a[1]), "r"(a[2]), "r"(a[3]), "l"(db), "r"(sc));
}
template<> __device__ __forceinline__ void wgmma_rs<80>(float* d, const uint32_t* a, uint64_t db, int sc) {
  asm volatile("{.reg .pred p; setp.ne.b32 p, %45, 0;\n"
  "wgmma.mma_async.sync.aligned.m64n80k16.f32.bf16.bf16 {%0,%1,%2,%3,%4,%5,%6,%7,%8,%9,%10,%11,%12,%13,%14,%15,%16,%17,%18,%19,%20,%21,%22,%23,%24,%25,%26,%27,%28,%29,%30,%31,%32,%33,%34,%35,%36,%37,%38,%39}, {%40,%41,%42,%43}, %44, p, 1, 1, 0;}\n"
  : "+f"(d[0]),"+f"(d[1]),"+f"(d[2]),"+f"(d[3]),"+f"(d[4]),"+f"(d[5]),"+f"(d[6]),"+f"(d[7]),"+f"(d[8]),"+f"(d[9]),"+f"(d[10]),"+f"(d[11]),"+f"(d[12]),"+f"(d[13]),"+f"(d[14]),"+f"(d[15]),"+f"(d[16]),"+f"(d[17]),"+f"(d[18]),"+f"(d[19]),"+f"(d[20]),"+f"(d[21]),"+f"(d[22]),"+f"(d[23]),"+f"(d[24]),"+f"(d[25]),"+f"(d[26]),"+f"(d[27]),"+f"(d[28]),"+f"(d[29]),"+f"(d[30]),"+f"(d[31]),"+f"(d[32]),"+f"(d[33]),"+f"(d[34]),"+f"(d[35]),"+f"(d[36]),"+f"(d[37]),"+f"(d[38]),"+f"(d[39])
  : "r"(a[0]), "r"(a[1]), "r"(a[2]), "r"(a[3]), "l"(db), "r"(sc));
}
template<> __device__ __forceinline__ void wgmma_rs<96>(float* d, const uint32_t* a, uint64_t db, int sc) {
  asm volatile("{.reg .pred p; setp.ne.b32 p, %53, 0;\n"
  "wgmma.mma_async.sync.aligned.m64n96k16.f32.bf16.bf16 {%0,%1,%2,%3,%4,%5,%6,%7,%8,%9,%10,%11,%12,%13,%14,%15,%16,%17,%18,%19,%20,%21,%22,%23,%24,%25,%26,%27,%28,%29,%30,%31,%32,%33,%34,%35,%36,%37,%38,%39,%40,%41,%42,%43,%44,%45,%46,%47}, {%48,%49,%50,%51}, %52, p, 1, 1, 0;}\n"
  : "+f"(d[0]),"+f"(d[1]),"+f"(d[2]),"+f"(d[3]),"+f"(d[4]),"+f"(d[5]),"+f"(d[6]),"+f"(d[7]),"+f"(d[8]),"+f"(d[9]),"+f"(d[10]),"+f"(d[11]),"+f"(d[12]),"+f"(d[13]),"+f"(d[14]),"+f"(d[15]),"+f"(d[16]),"+f"(d[17]),"+f"(d[18]),"+f"(d[19]),"+f"(d[20]),"+f"(d[21]),"+f"(d[22]),"+f"(d[23]),"+f"(d[24]),"+f"(d[25]),"+f"(d[26]),"+f"(d[27]),"+f"(d[28]),"+f"(d[29]),"+f"(d[30]),"+f"(d[31]),"+f"(d[32]),"+f"(d[33]),"+f"(d[34]),"+f"(d[35]),"+f"(d[36]),"+f"(d[37]),"+f"(d[38]),"+f"(d[39]),"+f"(d[40]),"+f"(d[41]),"+f"(d[42]),"+f"(d[43]),"+f"(d[44]),"+f"(d[45]),"+f"(d[46]),"+f"(d[47])
  : "r"(a[0]), "r"(a[1]), "r"(a[2]), "r"(a[3]), "l"(db), "r"(sc));
}
template<> __device__ __forceinline__ void wgmma_rs<112>(float* d, const uint32_t* a, uint64_t db, int sc) {
  asm volatile("{.reg .pred p; setp.ne.b32 p, %61, 0;\n"
  "wgmma.mma_async.sync.aligned.m64n112k16.f32.bf16.bf16 {%0,%1,%2,%3,%4,%5,%6,%7,%8,%9,%10,%11,%12,%13,%14,%15,%16,%17,%18,%19,%20,%21,%22,%23,%24,%25,%26,%27,%28,%29,%30,%31,%32,%33,%34,%35,%36,%37,%38,%39,%40,%41,%42,%43,%44,%45,%46,%47,%48,%49,%50,%51,%52,%53,%54,%55}, {%56,%57,%58,%59}, %60, p, 1, 1, 0;}\n"
  : "+f"(d[0]),"+f"(d[1]),"+f"(d[2]),"+f"(d[3]),"+f"(d[4]),"+f"(d[5]),"+f"(d[6]),"+f"(d[7]),"+f"(d[8]),"+f"(d[9]),"+f"(d[10]),"+f"(d[11]),"+f"(d[12]),"+f"(d[13]),"+f"(d[14]),"+f"(d[15]),"+f"(d[16]),"+f"(d[17]),"+f"(d[18]),"+f"(d[19]),"+f"(d[20]),"+f"(d[21]),"+f"(d[22]),"+f"(d[23]),"+f"(d[24]),"+f"(d[25]),"+f"(d[26]),"+f"(d[27]),"+f"(d[28]),"+f"(d[29]),"+f"(d[30]),"+f"(d[31]),"+f"(d[32]),"+f"(d[33]),"+f"(d[34]),"+f"(d[35]),"+f"(d[36]),"+f"(d[37]),"+f"(d[38]),"+f"(d[39]),"+f"(d[40]),"+f"(d[41]),"+f"(d[42]),"+f"(d[43]),"+f"(d[44]),"+f"(d[45]),"+f"(d[46]),"+f"(d[47]),"+f"(d[48]),"+f"(d[49]),"+f"(d[50]),"+f"(d[51]),"+f"(d[52]),"+f"(d[53]),"+f"(d[54]),"+f"(d[55])
  : "r"(a[0]), "r"(a[1]), "r"(a[2]), "r"(a[3]), "l"(db), "r"(sc));
}
template<> __device__ __forceinline__ void wgmma_rs<128>(float* d, const uint32_t* a, uint64_t db, int sc) {
  asm volatile("{.reg .pred p; setp.ne.b32 p, %69, 0;\n"
  "wgmma.mma_async.sync.aligned.m64n128k16.f32.bf16.bf16 {%0,%1,%2,%3,%4,%5,%6,%7,%8,%9,%10,%11,%12,%13,%14,%15,%16,%17,%18,%19,%20,%21,%22,%23,%24,%25,%26,%27,%28,%29,%30,%31,%32,%33,%34,%35,%36,%37,%38,%39,%40,%41,%42,%43,%44,%45,%46,%47,%48,%49,%50,%51,%52,%53,%54,%55,%56,%57,%58,%59,%60,%61,%62,%63}, {%64,%65,%66,%67}, %68, p, 1, 1, 0;}\n"
  : "+f"(d[0]),"+f"(d[1]),"+f"(d[2]),"+f"(d[3]),"+f"(d[4]),"+f"(d[5]),"+f"(d[6]),"+f"(d[7]),"+f"(d[8]),"+f"(d[9]),"+f"(d[10]),"+f"(d[11]),"+f"(d[12]),"+f"(d[13]),"+f"(d[14]),"+f"(d[15]),"+f"(d[16]),"+f"(d[17]),"+f"(d[18]),"+f"(d[19]),"+f"(d[20]),"+f"(d[21]),"+f"(d[22]),"+f"(d[23]),"+f"(d[24]),"+f"(d[25]),"+f"(d[26]),"+f"(d[27]),"+f"(d[28]),"+f"(d[29]),"+f"(d[30]),"+f"(d[31]),"+f"(d[32]),"+f"(d[33]),"+f"(d[34]),"+f"(d[35]),"+f"(d[36]),"+f"(d[37]),"+f"(d[38]),"+f"(d[39]),"+f"(d[40]),"+f"(d[41]),"+f"(d[42]),"+f"(d[43]),"+f"(d[44]),"+f"(d[45]),"+f"(d[46]),"+f"(d[47]),"+f"(d[48]),"+f"(d[49]),"+f"(d[50]),"+f"(d[51]),"+f"(d[52]),"+f"(d[53]),"+f"(d[54]),"+f"(d[55]),"+f"(d[56]),"+f"(d[57]),"+f"(d[58]),"+f"(d[59]),"+f"(d[60]),"+f"(d[61]),"+f"(d[62]),"+f"(d[63])
  : "r"(a[0]), "r"(a[1]), "r"(a[2]), "r"(a[3]), "l"(db), "r"(sc));
}
template<> __device__ __forceinline__ void wgmma_rs<144>(float* d, const uint32_t* a, uint64_t db, int sc) {
  asm volatile("{.reg .pred p; setp.ne.b32 p, %77, 0;\n"
  "wgmma.mma_async.sync.aligned.m64n144k16.f32.bf16.bf16 {%0,%1,%2,%3,%4,%5,%6,%7,%8,%9,%10,%11,%12,%13,%14,%15,%16,%17,%18,%19,%20,%21,%22,%23,%24,%25,%26,%27,%28,%29,%30,%31,%32,%33,%34,%35,%36,%37,%38,%39,%40,%41,%42,%43,%44,%45,%46,%47,%48,%49,%50,%51,%52,%53,%54,%55,%56,%57,%58,%59,%60,%61,%62,%63,%64,%65,%66,%67,%68,%69,%70,%71}, {%72,%73,%74,%75}, %76, p, 1, 1, 0;}\n"
  : "+f"(d[0]),"+f"(d[1]),"+f"(d[2]),"+f"(d[3]),"+f"(d[4]),"+f"(d[5]),"+f"(d[6]),"+f"(d[7]),"+f"(d[8]),"+f"(d[9]),"+f"(d[10]),"+f"(d[11]),"+f"(d[12]),"+f"(d[13]),"+f"(d[14]),"+f"(d[15]),"+f"(d[16]),"+f"(d[17]),"+f"(d[18]),"+f"(d[19]),"+f"(d[20]),"+f"(d[21]),"+f"(d[22]),"+f"(d[23]),"+f"(d[24]),"+f"(d[25]),"+f"(d[26]),"+f"(d[27]),"+f"(d[28]),"+f"(d[29]),"+f"(d[30]),"+f"(d[31]),"+f"(d[32]),"+f"(d[33]),"+f"(d[34]),"+f"(d[35]),"+f"(d[36]),"+f"(d[37]),"+f"(d[38]),"+f"(d[39]),"+f"(d[40]),"+f"(d[41]),"+f"(d[42]),"+f"(d[43]),"+f"(d[44]),"+f"(d[45]),"+f"(d[46]),"+f"(d[47]),"+f"(d[48]),"+f"(d[49]),"+f"(d[50]),"+f"(d[51]),"+f"(d[52]),"+f"(d[53]),"+f"(d[54]),"+f"(d[55]),"+f"(d[56]),"+f"(d[57]),"+f"(d[58]),"+f"(d[59]),"+f"(d[60]),"+f"(d[61]),"+f"(d[62]),"+f"(d[63]),"+f"(d[64]),"+f"(d[65]),"+f"(d[66]),"+f"(d[67]),"+f"(d[68]),"+f"(d[69]),"+f"(d[70]),"+f"(d[71])
  : "r"(a[0]), "r"(a[1]), "r"(a[2]), "r"(a[3]), "l"(db), "r"(sc));
}
template<> __device__ __forceinline__ void wgmma_rs<160>(float* d, const uint32_t* a, uint64_t db, int sc) {
  asm volatile("{.reg .pred p; setp.ne.b32 p, %85, 0;\n"
  "wgmma.mma_async.sync.aligned.m64n160k16.f32.bf16.bf16 {%0,%1,%2,%3,%4,%5,%6,%7,%8,%9,%10,%11,%12,%13,%14,%15,%16,%17,%18,%19,%20,%21,%22,%23,%24,%25,%26,%27,%28,%29,%30,%31,%32,%33,%34,%35,%36,%37,%38,%39,%40,%41,%42,%43,%44,%45,%46,%47,%48,%49,%50,%51,%52,%53,%54,%55,%56,%57,%58,%59,%60,%61,%62,%63,%64,%65,%66,%67,%68,%69,%70,%71,%72,%73,%74,%75,%76,%77,%78,%79}, {%80,%81,%82,%83}, %84, p, 1, 1, 0;}\n"
  : "+f"(d[0]),"+f"(d[1]),"+f"(d[2]),"+f"(d[3]),"+f"(d[4]),"+f"(d[5]),"+f"(d[6]),"+f"(d[7]),"+f"(d[8]),"+f"(d[9]),"+f"(d[10]),"+f"(d[11]),"+f"(d[12]),"+f"(d[13]),"+f"(d[14]),"+f"(d[15]),"+f"(d[16]),"+f"(d[17]),"+f"(d[18]),"+f"(d[19]),"+f"(d[20]),"+f"(d[21]),"+f"(d[22]),"+f"(d[23]),"+f"(d[24]),"+f"(d[25]),"+f"(d[26]),"+f"(d[27]),"+f"(d[28]),"+f"(d[29]),"+f"(d[30]),"+f"(d[31]),"+f"(d[32]),"+f"(d[33]),"+f"(d[34]),"+f"(d[35]),"+f"(d[36]),"+f"(d[37]),"+f"(d[38]),"+f"(d[39]),"+f"(d[40]),"+f"(d[41]),"+f"(d[42]),"+f"(d[43]),"+f"(d[44]),"+f"(d[45]),"+f"(d[46]),"+f"(d[47]),"+f"(d[48]),"+f"(d[49]),"+f"(d[50]),"+f"(d[51]),"+f"(d[52]),"+f"(d[53]),"+f"(d[54]),"+f"(d[55]),"+f"(d[56]),"+f"(d[57]),"+f"(d[58]),"+f"(d[59]),"+f"(d[60]),"+f"(d[61]),"+f"(d[62]),"+f"(d[63]),"+f"(d[64]),"+f"(d[65]),"+f"(d[66]),"+f"(d[67]),"+f"(d[68]),"+f"(d[69]),"+f"(d[70]),"+f"(d[71]),"+f"(d[72]),"+f"(d[73]),"+f"(d[74]),"+f"(d[75]),"+f"(d[76]),"+f"(d[77]),"+f"(d[78]),"+f"(d[79])
  : "r"(a[0]), "r"(a[1]), "r"(a[2]), "r"(a[3]), "l"(db), "r"(sc));
}
template<> __device__ __forceinline__ void wgmma_rs<176>(float* d, const uint32_t* a, uint64_t db, int sc) {
  asm volatile("{.reg .pred p; setp.ne.b32 p, %93, 0;\n"
  "wgmma.mma_async.sync.aligned.m64n176k16.f32.bf16.bf16 {%0,%1,%2,%3,%4,%5,%6,%7,%8,%9,%10,%11,%12,%13,%14,%15,%16,%17,%18,%19,%20,%21,%22,%23,%24,%25,%26,%27,%28,%29,%30,%31,%32,%33,%34,%35,%36,%37,%38,%39,%40,%41,%42,%43,%44,%45,%46,%47,%48,%49,%50,%51,%52,%53,%54,%55,%56,%57,%58,%59,%60,%61,%62,%63,%64,%65,%66,%67,%68,%69,%70,%71,%72,%73,%74,%75,%76,%77,%78,%79,%80,%81,%82,%83,%84,%85,%86,%87}, {%88,%89,%90,%91}, %92, p, 1, 1, 0;}\n"
  : "+f"(d[0]),"+f"(d[1]),"+f"(d[2]),"+f"(d[3]),"+f"(d[4]),"+f"(d[5]),"+f"(d[6]),"+f"(d[7]),"+f"(d[8]),"+f"(d[9]),"+f"(d[10]),"+f"(d[11]),"+f"(d[12]),"+f"(d[13]),"+f"(d[14]),"+f"(d[15]),"+f"(d[16]),"+f"(d[17]),"+f"(d[18]),"+f"(d[19]),"+f"(d[20]),"+f"(d[21]),"+f"(d[22]),"+f"(d[23]),"+f"(d[24]),"+f"(d[25]),"+f"(d[26]),"+f"(d[27]),"+f"(d[28]),"+f"(d[29]),"+f"(d[30]),"+f"(d[31]),"+f"(d[32]),"+f"(d[33]),"+f"(d[34]),"+f"(d[35]),"+f"(d[36]),"+f"(d[37]),"+f"(d[38]),"+f"(d[39]),"+f"(d[40]),"+f"(d[41]),"+f"(d[42]),"+f"(d[43]),"+f"(d[44]),"+f"(d[45]),"+f"(d[46]),"+f"(d[47]),"+f"(d[48]),"+f"(d[49]),"+f"(d[50]),"+f"(d[51]),"+f"(d[52]),"+f"(d[53]),"+f"(d[54]),"+f"(d[55]),"+f"(d[56]),"+f"(d[57]),"+f"(d[58]),"+f"(d[59]),"+f"(d[60]),"+f"(d[61]),"+f"(d[62]),"+f"(d[63]),"+f"(d[64]),"+f"(d[65]),"+f"(d[66]),"+f"(d[67]),"+f"(d[68]),"+f"(d[69]),"+f"(d[70]),"+f"(d[71]),"+f"(d[72]),"+f"(d[73]),"+f"(d[74]),"+f"(d[75]),"+f"(d[76]),"+f"(d[77]),"+f"(d[78]),"+f"(d[79]),"+f"(d[80]),"+f"(d[81]),"+f"(d[82]),"+f"(d[83]),"+f"(d[84]),"+f"(d[85]),"+f"(d[86]),"+f"(d[87])
  : "r"(a[0]), "r"(a[1]), "r"(a[2]), "r"(a[3]), "l"(db), "r"(sc));
}
template<> __device__ __forceinline__ void wgmma_rs<192>(float* d, const uint32_t* a, uint64_t db, int sc) {
  asm volatile("{.reg .pred p; setp.ne.b32 p, %101, 0;\n"
  "wgmma.mma_async.sync.aligned.m64n192k16.f32.bf16.bf16 {%0,%1,%2,%3,%4,%5,%6,%7,%8,%9,%10,%11,%12,%13,%14,%15,%16,%17,%18,%19,%20,%21,%22,%23,%24,%25,%26,%27,%28,%29,%30,%31,%32,%33,%34,%35,%36,%37,%38,%39,%40,%41,%42,%43,%44,%45,%46,%47,%48,%49,%50,%51,%52,%53,%54,%55,%56,%57,%58,%59,%60,%61,%62,%63,%64,%65,%66,%67,%68,%69,%70,%71,%72,%73,%74,%75,%76,%77,%78,%79,%80,%81,%82,%83,%84,%85,%86,%87,%88,%89,%90,%91,%92,%93,%94,%95}, {%96,%97,%98,%99}, %100, p, 1, 1, 0;}\n"
  : "+f"(d[0]),"+f"(d[1]),"+f"(d[2]),"+f"(d[3]),"+f"(d[4]),"+f"(d[5]),"+f"(d[6]),"+f"(d[7]),"+f"(d[8]),"+f"(d[9]),"+f"(d[10]),"+f"(d[11]),"+f"(d[12]),"+f"(d[13]),"+f"(d[14]),"+f"(d[15]),"+f"(d[16]),"+f"(d[17]),"+f"(d[18]),"+f"(d[19]),"+f"(d[20]),"+f"(d[21]),"+f"(d[22]),"+f"(d[23]),"+f"(d[24]),"+f"(d[25]),"+f"(d[26]),"+f"(d[27]),"+f"(d[28]),"+f"(d[29]),"+f"(d[30]),"+f"(d[31]),"+f"(d[32]),"+f"(d[33]),"+f"(d[34]),"+f"(d[35]),"+f"(d[36]),"+f"(d[37]),"+f"(d[38]),"+f"(d[39]),"+f"(d[40]),"+f"(d[41]),"+f"(d[42]),"+f"(d[43]),"+f"(d[44]),"+f"(d[45]),"+f"(d[46]),"+f"(d[47]),"+f"(d[48]),"+f"(d[49]),"+f"(d[50]),"+f"(d[51]),"+f"(d[52]),"+f"(d[53]),"+f"(d[54]),"+f"(d[55]),"+f"(d[56]),"+f"(d[57]),"+f"(d[58]),"+f"(d[59]),"+f"(d[60]),"+f"(d[61]),"+f"(d[62]),"+f"(d[63]),"+f"(d[64]),"+f"(d[65]),"+f"(d[66]),"+f"(d[67]),"+f"(d[68]),"+f"(d[69]),"+f"(d[70]),"+f"(d[71]),"+f"(d[72]),"+f"(d[73]),"+f"(d[74]),"+f"(d[75]),"+f"(d[76]),"+f"(d[77]),"+f"(d[78]),"+f"(d[79]),"+f"(d[80]),"+f"(d[81]),"+f"(d[82]),"+f"(d[83]),"+f"(d[84]),"+f"(d[85]),"+f"(d[86]),"+f"(d[87]),"+f"(d[88]),"+f"(d[89]),"+f"(d[90]),"+f"(d[91]),"+f"(d[92]),"+f"(d[93]),"+f"(d[94]),"+f"(d[95])
  : "r"(a[0]), "r"(a[1]), "r"(a[2]), "r"(a[3]), "l"(db), "r"(sc));
}
template<> __device__ __forceinline__ void wgmma_rs<208>(float* d, const uint32_t* a, uint64_t db, int sc) {
  asm volatile("{.reg .pred p; setp.ne.b32 p, %109, 0;\n"
  "wgmma.mma_async.sync.aligned.m64n208k16.f32.bf16.bf16 {%0,%1,%2,%3,%4,%5,%6,%7,%8,%9,%10,%11,%12,%13,%14,%15,%16,%17,%18,%19,%20,%21,%22,%23,%24,%25,%26,%27,%28,%29,%30,%31,%32,%33,%34,%35,%36,%37,%38,%39,%40,%41,%42,%43,%44,%45,%46,%47,%48,%49,%50,%51,%52,%53,%54,%55,%56,%57,%58,%59,%60,%61,%62,%63,%64,%65,%66,%67,%68,%69,%70,%71,%72,%73,%74,%75,%76,%77,%78,%79,%80,%81,%82,%83,%84,%85,%86,%87,%88,%89,%90,%91,%92,%93,%94,%95,%96,%97,%98,%99,%100,%101,%102,%103}, {%104,%105,%106,%107}, %108, p, 1, 1, 0;}\n"
  : "+f"(d[0]),"+f"(d[1]),"+f"(d[2]),"+f"(d[3]),"+f"(d[4]),"+f"(d[5]),"+f"(d[6]),"+f"(d[7]),"+f"(d[8]),"+f"(d[9]),"+f"(d[10]),"+f"(d[11]),"+f"(d[12]),"+f"(d[13]),"+f"(d[14]),"+f"(d[15]),"+f"(d[16]),"+f"(d[17]),"+f"(d[18]),"+f"(d[19]),"+f"(d[20]),"+f"(d[21]),"+f"(d[22]),"+f"(d[23]),"+f"(d[24]),"+f"(d[25]),"+f"(d[26]),"+f"(d[27]),"+f"(d[28]),"+f"(d[29]),"+f"(d[30]),"+f"(d[31]),"+f"(d[32]),"+f"(d[33]),"+f"(d[34]),"+f"(d[35]),"+f"(d[36]),"+f"(d[37]),"+f"(d[38]),"+f"(d[39]),"+f"(d[40]),"+f"(d[41]),"+f"(d[42]),"+f"(d[43]),"+f"(d[44]),"+f"(d[45]),"+f"(d[46]),"+f"(d[47]),"+f"(d[48]),"+f"(d[49]),"+f"(d[50]),"+f"(d[51]),"+f"(d[52]),"+f"(d[53]),"+f"(d[54]),"+f"(d[55]),"+f"(d[56]),"+f"(d[57]),"+f"(d[58]),"+f"(d[59]),"+f"(d[60]),"+f"(d[61]),"+f"(d[62]),"+f"(d[63]),"+f"(d[64]),"+f"(d[65]),"+f"(d[66]),"+f"(d[67]),"+f"(d[68]),"+f"(d[69]),"+f"(d[70]),"+f"(d[71]),"+f"(d[72]),"+f"(d[73]),"+f"(d[74]),"+f"(d[75]),"+f"(d[76]),"+f"(d[77]),"+f"(d[78]),"+f"(d[79]),"+f"(d[80]),"+f"(d[81]),"+f"(d[82]),"+f"(d[83]),"+f"(d[84]),"+f"(d[85]),"+f"(d[86]),"+f"(d[87]),"+f"(d[88]),"+f"(d[89]),"+f"(d[90]),"+f"(d[91]),"+f"(d[92]),"+f"(d[93]),"+f"(d[94]),"+f"(d[95]),"+f"(d[96]),"+f"(d[97]),"+f"(d[98]),"+f"(d[99]),"+f"(d[100]),"+f"(d[101]),"+f"(d[102]),"+f"(d[103])
  : "r"(a[0]), "r"(a[1]), "r"(a[2]), "r"(a[3]), "l"(db), "r"(sc));
}
template<> __device__ __forceinline__ void wgmma_rs<224>(float* d, const uint32_t* a, uint64_t db, int sc) {
  asm volatile("{.reg .pred p; setp.ne.b32 p, %117, 0;\n"
  "wgmma.mma_async.sync.aligned.m64n224k16.f32.bf16.bf16 {%0,%1,%2,%3,%4,%5,%6,%7,%8,%9,%10,%11,%12,%13,%14,%15,%16,%17,%18,%19,%20,%21,%22,%23,%24,%25,%26,%27,%28,%29,%30,%31,%32,%33,%34,%35,%36,%37,%38,%39,%40,%41,%42,%43,%44,%45,%46,%47,%48,%49,%50,%51,%52,%53,%54,%55,%56,%57,%58,%59,%60,%61,%62,%63,%64,%65,%66,%67,%68,%69,%70,%71,%72,%73,%74,%75,%76,%77,%78,%79,%80,%81,%82,%83,%84,%85,%86,%87,%88,%89,%90,%91,%92,%93,%94,%95,%96,%97,%98,%99,%100,%101,%102,%103,%104,%105,%106,%107,%108,%109,%110,%111}, {%112,%113,%114,%115}, %116, p, 1, 1, 0;}\n"
  : "+f"(d[0]),"+f"(d[1]),"+f"(d[2]),"+f"(d[3]),"+f"(d[4]),"+f"(d[5]),"+f"(d[6]),"+f"(d[7]),"+f"(d[8]),"+f"(d[9]),"+f"(d[10]),"+f"(d[11]),"+f"(d[12]),"+f"(d[13]),"+f"(d[14]),"+f"(d[15]),"+f"(d[16]),"+f"(d[17]),"+f"(d[18]),"+f"(d[19]),"+f"(d[20]),"+f"(d[21]),"+f"(d[22]),"+f"(d[23]),"+f"(d[24]),"+f"(d[25]),"+f"(d[26]),"+f"(d[27]),"+f"(d[28]),"+f"(d[29]),"+f"(d[30]),"+f"(d[31]),"+f"(d[32]),"+f"(d[33]),"+f"(d[34]),"+f"(d[35]),"+f"(d[36]),"+f"(d[37]),"+f"(d[38]),"+f"(d[39]),"+f"(d[40]),"+f"(d[41]),"+f"(d[42]),"+f"(d[43]),"+f"(d[44]),"+f"(d[45]),"+f"(d[46]),"+f"(d[47]),"+f"(d[48]),"+f"(d[49]),"+f"(d[50]),"+f"(d[51]),"+f"(d[52]),"+f"(d[53]),"+f"(d[54]),"+f"(d[55]),"+f"(d[56]),"+f"(d[57]),"+f"(d[58]),"+f"(d[59]),"+f"(d[60]),"+f"(d[61]),"+f"(d[62]),"+f"(d[63]),"+f"(d[64]),"+f"(d[65]),"+f"(d[66]),"+f"(d[67]),"+f"(d[68]),"+f"(d[69]),"+f"(d[70]),"+f"(d[71]),"+f"(d[72]),"+f"(d[73]),"+f"(d[74]),"+f"(d[75]),"+f"(d[76]),"+f"(d[77]),"+f"(d[78]),"+f"(d[79]),"+f"(d[80]),"+f"(d[81]),"+f"(d[82]),"+f"(d[83]),"+f"(d[84]),"+f"(d[85]),"+f"(d[86]),"+f"(d[87]),"+f"(d[88]),"+f"(d[89]),"+f"(d[90]),"+f"(d[91]),"+f"(d[92]),"+f"(d[93]),"+f"(d[94]),"+f"(d[95]),"+f"(d[96]),"+f"(d[97]),"+f"(d[98]),"+f"(d[99]),"+f"(d[100]),"+f"(d[101]),"+f"(d[102]),"+f"(d[103]),"+f"(d[104]),"+f"(d[105]),"+f"(d[106]),"+f"(d[107]),"+f"(d[108]),"+f"(d[109]),"+f"(d[110]),"+f"(d[111])
  : "r"(a[0]), "r"(a[1]), "r"(a[2]), "r"(a[3]), "l"(db), "r"(sc));
}
template<> __device__ __forceinline__ void wgmma_rs<240>(float* d, const uint32_t* a, uint64_t db, int sc) {
  asm volatile("{.reg .pred p; setp.ne.b32 p, %125, 0;\n"
  "wgmma.mma_async.sync.aligned.m64n240k16.f32.bf16.bf16 {%0,%1,%2,%3,%4,%5,%6,%7,%8,%9,%10,%11,%12,%13,%14,%15,%16,%17,%18,%19,%20,%21,%22,%23,%24,%25,%26,%27,%28,%29,%30,%31,%32,%33,%34,%35,%36,%37,%38,%39,%40,%41,%42,%43,%44,%45,%46,%47,%48,%49,%50,%51,%52,%53,%54,%55,%56,%57,%58,%59,%60,%61,%62,%63,%64,%65,%66,%67,%68,%69,%70,%71,%72,%73,%74,%75,%76,%77,%78,%79,%80,%81,%82,%83,%84,%85,%86,%87,%88,%89,%90,%91,%92,%93,%94,%95,%96,%97,%98,%99,%100,%101,%102,%103,%104,%105,%106,%107,%108,%109,%110,%111,%112,%113,%114,%115,%116,%117,%118,%119}, {%120,%121,%122,%123}, %124, p, 1, 1, 0;}\n"
  : "+f"(d[0]),"+f"(d[1]),"+f"(d[2]),"+f"(d[3]),"+f"(d[4]),"+f"(d[5]),"+f"(d[6]),"+f"(d[7]),"+f"(d[8]),"+f"(d[9]),"+f"(d[10]),"+f"(d[11]),"+f"(d[12]),"+f"(d[13]),"+f"(d[14]),"+f"(d[15]),"+f"(d[16]),"+f"(d[17]),"+f"(d[18]),"+f"(d[19]),"+f"(d[20]),"+f"(d[21]),"+f"(d[22]),"+f"(d[23]),"+f"(d[24]),"+f"(d[25]),"+f"(d[26]),"+f"(d[27]),"+f"(d[28]),"+f"(d[29]),"+f"(d[30]),"+f"(d[31]),"+f"(d[32]),"+f"(d[33]),"+f"(d[34]),"+f"(d[35]),"+f"(d[36]),"+f"(d[37]),"+f"(d[38]),"+f"(d[39]),"+f"(d[40]),"+f"(d[41]),"+f"(d[42]),"+f"(d[43]),"+f"(d[44]),"+f"(d[45]),"+f"(d[46]),"+f"(d[47]),"+f"(d[48]),"+f"(d[49]),"+f"(d[50]),"+f"(d[51]),"+f"(d[52]),"+f"(d[53]),"+f"(d[54]),"+f"(d[55]),"+f"(d[56]),"+f"(d[57]),"+f"(d[58]),"+f"(d[59]),"+f"(d[60]),"+f"(d[61]),"+f"(d[62]),"+f"(d[63]),"+f"(d[64]),"+f"(d[65]),"+f"(d[66]),"+f"(d[67]),"+f"(d[68]),"+f"(d[69]),"+f"(d[70]),"+f"(d[71]),"+f"(d[72]),"+f"(d[73]),"+f"(d[74]),"+f"(d[75]),"+f"(d[76]),"+f"(d[77]),"+f"(d[78]),"+f"(d[79]),"+f"(d[80]),"+f"(d[81]),"+f"(d[82]),"+f"(d[83]),"+f"(d[84]),"+f"(d[85]),"+f"(d[86]),"+f"(d[87]),"+f"(d[88]),"+f"(d[89]),"+f"(d[90]),"+f"(d[91]),"+f"(d[92]),"+f"(d[93]),"+f"(d[94]),"+f"(d[95]),"+f"(d[96]),"+f"(d[97]),"+f"(d[98]),"+f"(d[99]),"+f"(d[100]),"+f"(d[101]),"+f"(d[102]),"+f"(d[103]),"+f"(d[104]),"+f"(d[105]),"+f"(d[106]),"+f"(d[107]),"+f"(d[108]),"+f"(d[109]),"+f"(d[110]),"+f"(d[111]),"+f"(d[112]),"+f"(d[113]),"+f"(d[114]),"+f"(d[115]),"+f"(d[116]),"+f"(d[117]),"+f"(d[118]),"+f"(d[119])
  : "r"(a[0]), "r"(a[1]), "r"(a[2]), "r"(a[3]), "l"(db), "r"(sc));
}
template<> __device__ __forceinline__ void wgmma_rs<256>(float* d, const uint32_t* a, uint64_t db, int sc) {
  asm volatile("{.reg .pred p; setp.ne.b32 p, %133, 0;\n"
  "wgmma.mma_async.sync.aligned.m64n256k16.f32.bf16.bf16 {%0,%1,%2,%3,%4,%5,%6,%7,%8,%9,%10,%11,%12,%13,%14,%15,%16,%17,%18,%19,%20,%21,%22,%23,%24,%25,%26,%27,%28,%29,%30,%31,%32,%33,%34,%35,%36,%37,%38,%39,%40,%41,%42,%43,%44,%45,%46,%47,%48,%49,%50,%51,%52,%53,%54,%55,%56,%57,%58,%59,%60,%61,%62,%63,%64,%65,%66,%67,%68,%69,%70,%71,%72,%73,%74,%75,%76,%77,%78,%79,%80,%81,%82,%83,%84,%85,%86,%87,%88,%89,%90,%91,%92,%93,%94,%95,%96,%97,%98,%99,%100,%101,%102,%103,%104,%105,%106,%107,%108,%109,%110,%111,%112,%113,%114,%115,%116,%117,%118,%119,%120,%121,%122,%123,%124,%125,%126,%127}, {%128,%129,%130,%131}, %132, p, 1, 1, 0;}\n"
  : "+f"(d[0]),"+f"(d[1]),"+f"(d[2]),"+f"(d[3]),"+f"(d[4]),"+f"(d[5]),"+f"(d[6]),"+f"(d[7]),"+f"(d[8]),"+f"(d[9]),"+f"(d[10]),"+f"(d[11]),"+f"(d[12]),"+f"(d[13]),"+f"(d[14]),"+f"(d[15]),"+f"(d[16]),"+f"(d[17]),"+f"(d[18]),"+f"(d[19]),"+f"(d[20]),"+f"(d[21]),"+f"(d[22]),"+f"(d[23]),"+f"(d[24]),"+f"(d[25]),"+f"(d[26]),"+f"(d[27]),"+f"(d[28]),"+f"(d[29]),"+f"(d[30]),"+f"(d[31]),"+f"(d[32]),"+f"(d[33]),"+f"(d[34]),"+f"(d[35]),"+f"(d[36]),"+f"(d[37]),"+f"(d[38]),"+f"(d[39]),"+f"(d[40]),"+f"(d[41]),"+f"(d[42]),"+f"(d[43]),"+f"(d[44]),"+f"(d[45]),"+f"(d[46]),"+f"(d[47]),"+f"(d[48]),"+f"(d[49]),"+f"(d[50]),"+f"(d[51]),"+f"(d[52]),"+f"(d[53]),"+f"(d[54]),"+f"(d[55]),"+f"(d[56]),"+f"(d[57]),"+f"(d[58]),"+f"(d[59]),"+f"(d[60]),"+f"(d[61]),"+f"(d[62]),"+f"(d[63]),"+f"(d[64]),"+f"(d[65]),"+f"(d[66]),"+f"(d[67]),"+f"(d[68]),"+f"(d[69]),"+f"(d[70]),"+f"(d[71]),"+f"(d[72]),"+f"(d[73]),"+f"(d[74]),"+f"(d[75]),"+f"(d[76]),"+f"(d[77]),"+f"(d[78]),"+f"(d[79]),"+f"(d[80]),"+f"(d[81]),"+f"(d[82]),"+f"(d[83]),"+f"(d[84]),"+f"(d[85]),"+f"(d[86]),"+f"(d[87]),"+f"(d[88]),"+f"(d[89]),"+f"(d[90]),"+f"(d[91]),"+f"(d[92]),"+f"(d[93]),"+f"(d[94]),"+f"(d[95]),"+f"(d[96]),"+f"(d[97]),"+f"(d[98]),"+f"(d[99]),"+f"(d[100]),"+f"(d[101]),"+f"(d[102]),"+f"(d[103]),"+f"(d[104]),"+f"(d[105]),"+f"(d[106]),"+f"(d[107]),"+f"(d[108]),"+f"(d[109]),"+f"(d[110]),"+f"(d[111]),"+f"(d[112]),"+f"(d[113]),"+f"(d[114]),"+f"(d[115]),"+f"(d[116]),"+f"(d[117]),"+f"(d[118]),"+f"(d[119]),"+f"(d[120]),"+f"(d[121]),"+f"(d[122]),"+f"(d[123]),"+f"(d[124]),"+f"(d[125]),"+f"(d[126]),"+f"(d[127])
  : "r"(a[0]), "r"(a[1]), "r"(a[2]), "r"(a[3]), "l"(db), "r"(sc));
}
template<> __device__ __forceinline__ void wgmma_ss<128>(float* d, uint64_t da, uint64_t db, int sc) {
  asm volatile("{.reg .pred p; setp.ne.b32 p, %66, 0;\n"
  "wgmma.mma_async.sync.aligned.m64n128k16.f32.bf16.bf16 {%0,%1,%2,%3,%4,%5,%6,%7,%8,%9,%10,%11,%12,%13,%14,%15,%16,%17,%18,%19,%20,%21,%22,%23,%24,%25,%26,%27,%28,%29,%30,%31,%32,%33,%34,%35,%36,%37,%38,%39,%40,%41,%42,%43,%44,%45,%46,%47,%48,%49,%50,%51,%52,%53,%54,%55,%56,%57,%58,%59,%60,%61,%62,%63}, %64, %65, p, 1, 1, 0, 1;}\n"
  : "+f"(d[0]),"+f"(d[1]),"+f"(d[2]),"+f"(d[3]),"+f"(d[4]),"+f"(d[5]),"+f"(d[6]),"+f"(d[7]),"+f"(d[8]),"+f"(d[9]),"+f"(d[10]),"+f"(d[11]),"+f"(d[12]),"+f"(d[13]),"+f"(d[14]),"+f"(d[15]),"+f"(d[16]),"+f"(d[17]),"+f"(d[18]),"+f"(d[19]),"+f"(d[20]),"+f"(d[21]),"+f"(d[22]),"+f"(d[23]),"+f"(d[24]),"+f"(d[25]),"+f"(d[26]),"+f"(d[27]),"+f"(d[28]),"+f"(d[29]),"+f"(d[30]),"+f"(d[31]),"+f"(d[32]),"+f"(d[33]),"+f"(d[34]),"+f"(d[35]),"+f"(d[36]),"+f"(d[37]),"+f"(d[38]),"+f"(d[39]),"+f"(d[40]),"+f"(d[41]),"+f"(d[42]),"+f"(d[43]),"+f"(d[44]),"+f"(d[45]),"+f"(d[46]),"+f"(d[47]),"+f"(d[48]),"+f"(d[49]),"+f"(d[50]),"+f"(d[51]),"+f"(d[52]),"+f"(d[53]),"+f"(d[54]),"+f"(d[55]),"+f"(d[56]),"+f"(d[57]),"+f"(d[58]),"+f"(d[59]),"+f"(d[60]),"+f"(d[61]),"+f"(d[62]),"+f"(d[63])
  : "l"(da), "l"(db), "r"(sc));
}
template<> __device__ __forceinline__ void wgmma_ss<192>(float* d, uint64_t da, uint64_t db, int sc) {
  asm volatile("{.reg .pred p; setp.ne.b32 p, %98, 0;\n"
  "wgmma.mma_async.sync.aligned.m64n192k16.f32.bf16.bf16 {%0,%1,%2,%3,%4,%5,%6,%7,%8,%9,%10,%11,%12,%13,%14,%15,%16,%17,%18,%19,%20,%21,%22,%23,%24,%25,%26,%27,%28,%29,%30,%31,%32,%33,%34,%35,%36,%37,%38,%39,%40,%41,%42,%43,%44,%45,%46,%47,%48,%49,%50,%51,%52,%53,%54,%55,%56,%57,%58,%59,%60,%61,%62,%63,%64,%65,%66,%67,%68,%69,%70,%71,%72,%73,%74,%75,%76,%77,%78,%79,%80,%81,%82,%83,%84,%85,%86,%87,%88,%89,%90,%91,%92,%93,%94,%95}, %96, %97, p, 1, 1, 0, 1;}\n"
  : "+f"(d[0]),"+f"(d[1]),"+f"(d[2]),"+f"(d[3]),"+f"(d[4]),"+f"(d[5]),"+f"(d[6]),"+f"(d[7]),"+f"(d[8]),"+f"(d[9]),"+f"(d[10]),"+f"(d[11]),"+f"(d[12]),"+f"(d[13]),"+f"(d[14]),"+f"(d[15]),"+f"(d[16]),"+f"(d[17]),"+f"(d[18]),"+f"(d[19]),"+f"(d[20]),"+f"(d[21]),"+f"(d[22]),"+f"(d[23]),"+f"(d[24]),"+f"(d[25]),"+f"(d[26]),"+f"(d[27]),"+f"(d[28]),"+f"(d[29]),"+f"(d[30]),"+f"(d[31]),"+f"(d[32]),"+f"(d[33]),"+f"(d[34]),"+f"(d[35]),"+f"(d[36]),"+f"(d[37]),"+f"(d[38]),"+f"(d[39]),"+f"(d[40]),"+f"(d[41]),"+f"(d[42]),"+f"(d[43]),"+f"(d[44]),"+f"(d[45]),"+f"(d[46]),"+f"(d[47]),"+f"(d[48]),"+f"(d[49]),"+f"(d[50]),"+f"(d[51]),"+f"(d[52]),"+f"(d[53]),"+f"(d[54]),"+f"(d[55]),"+f"(d[56]),"+f"(d[57]),"+f"(d[58]),"+f"(d[59]),"+f"(d[60]),"+f"(d[61]),"+f"(d[62]),"+f"(d[63]),"+f"(d[64]),"+f"(d[65]),"+f"(d[66]),"+f"(d[67]),"+f"(d[68]),"+f"(d[69]),"+f"(d[70]),"+f"(d[71]),"+f"(d[72]),"+f"(d[73]),"+f"(d[74]),"+f"(d[75]),"+f"(d[76]),"+f"(d[77]),"+f"(d[78]),"+f"(d[79]),"+f"(d[80]),"+f"(d[81]),"+f"(d[82]),"+f"(d[83]),"+f"(d[84]),"+f"(d[85]),"+f"(d[86]),"+f"(d[87]),"+f"(d[88]),"+f"(d[89]),"+f"(d[90]),"+f"(d[91]),"+f"(d[92]),"+f"(d[93]),"+f"(d[94]),"+f"(d[95])
  : "l"(da), "l"(db), "r"(sc));
}
template<> __device__ __forceinline__ void wgmma_ss<256>(float* d, uint64_t da, uint64_t db, int sc) {
  asm volatile("{.reg .pred p; setp.ne.b32 p, %130, 0;\n"
  "wgmma.mma_async.sync.aligned.m64n256k16.f32.bf16.bf16 {%0,%1,%2,%3,%4,%5,%6,%7,%8,%9,%10,%11,%12,%13,%14,%15,%16,%17,%18,%19,%20,%21,%22,%23,%24,%25,%26,%27,%28,%29,%30,%31,%32,%33,%34,%35,%36,%37,%38,%39,%40,%41,%42,%43,%44,%45,%46,%47,%48,%49,%50,%51,%52,%53,%54,%55,%56,%57,%58,%59,%60,%61,%62,%63,%64,%65,%66,%67,%68,%69,%70,%71,%72,%73,%74,%75,%76,%77,%78,%79,%80,%81,%82,%83,%84,%85,%86,%87,%88,%89,%90,%91,%92,%93,%94,%95,%96,%97,%98,%99,%100,%101,%102,%103,%104,%105,%106,%107,%108,%109,%110,%111,%112,%113,%114,%115,%116,%117,%118,%119,%120,%121,%122,%123,%124,%125,%126,%127}, %128, %129, p, 1, 1, 0, 1;}\n"
  : "+f"(d[0]),"+f"(d[1]),"+f"(d[2]),"+f"(d[3]),"+f"(d[4]),"+f"(d[5]),"+f"(d[6]),"+f"(d[7]),"+f"(d[8]),"+f"(d[9]),"+f"(d[10]),"+f"(d[11]),"+f"(d[12]),"+f"(d[13]),"+f"(d[14]),"+f"(d[15]),"+f"(d[16]),"+f"(d[17]),"+f"(d[18]),"+f"(d[19]),"+f"(d[20]),"+f"(d[21]),"+f"(d[22]),"+f"(d[23]),"+f"(d[24]),"+f"(d[25]),"+f"(d[26]),"+f"(d[27]),"+f"(d[28]),"+f"(d[29]),"+f"(d[30]),"+f"(d[31]),"+f"(d[32]),"+f"(d[33]),"+f"(d[34]),"+f"(d[35]),"+f"(d[36]),"+f"(d[37]),"+f"(d[38]),"+f"(d[39]),"+f"(d[40]),"+f"(d[41]),"+f"(d[42]),"+f"(d[43]),"+f"(d[44]),"+f"(d[45]),"+f"(d[46]),"+f"(d[47]),"+f"(d[48]),"+f"(d[49]),"+f"(d[50]),"+f"(d[51]),"+f"(d[52]),"+f"(d[53]),"+f"(d[54]),"+f"(d[55]),"+f"(d[56]),"+f"(d[57]),"+f"(d[58]),"+f"(d[59]),"+f"(d[60]),"+f"(d[61]),"+f"(d[62]),"+f"(d[63]),"+f"(d[64]),"+f"(d[65]),"+f"(d[66]),"+f"(d[67]),"+f"(d[68]),"+f"(d[69]),"+f"(d[70]),"+f"(d[71]),"+f"(d[72]),"+f"(d[73]),"+f"(d[74]),"+f"(d[75]),"+f"(d[76]),"+f"(d[77]),"+f"(d[78]),"+f"(d[79]),"+f"(d[80]),"+f"(d[81]),"+f"(d[82]),"+f"(d[83]),"+f"(d[84]),"+f"(d[85]),"+f"(d[86]),"+f"(d[87]),"+f"(d[88]),"+f"(d[89]),"+f"(d[90]),"+f"(d[91]),"+f"(d[92]),"+f"(d[93]),"+f"(d[94]),"+f"(d[95]),"+f"(d[96]),"+f"(d[97]),"+f"(d[98]),"+f"(d[99]),"+f"(d[100]),"+f"(d[101]),"+f"(d[102]),"+f"(d[103]),"+f"(d[104]),"+f"(d[105]),"+f"(d[106]),"+f"(d[107]),"+f"(d[108]),"+f"(d[109]),"+f"(d[110]),"+f"(d[111]),"+f"(d[112]),"+f"(d[113]),"+f"(d[114]),"+f"(d[115]),"+f"(d[116]),"+f"(d[117]),"+f"(d[118]),"+f"(d[119]),"+f"(d[120]),"+f"(d[121]),"+f"(d[122]),"+f"(d[123]),"+f"(d[124]),"+f"(d[125]),"+f"(d[126]),"+f"(d[127])
  : "l"(da), "l"(db), "r"(sc));
}

__device__ __forceinline__ void wg_fence() { asm volatile("wgmma.fence.sync.aligned;" ::: "memory"); }
__device__ __forceinline__ void wg_commit() { asm volatile("wgmma.commit_group.sync.aligned;" ::: "memory"); }
template <int N> __device__ __forceinline__ void wg_wait() { asm volatile("wgmma.wait_group.sync.aligned %0;" ::"n"(N) : "memory"); }
__device__ __forceinline__ uint64_t mkdesc(uint32_t addr, uint32_t lbo, uint32_t sbo, uint32_t swz) {
  return (uint64_t)((addr & 0x3FFFF) >> 4) | ((uint64_t)(lbo >> 4) << 16) | ((uint64_t)(sbo >> 4) << 32) | ((uint64_t)swz << 62);
}
__device__ __forceinline__ void mbar_init(uint32_t a, uint32_t c) { asm volatile("mbarrier.init.shared.b64 [%0], %1;" ::"r"(a), "r"(c) : "memory"); }
__device__ __forceinline__ void mbar_expect_tx(uint32_t a, uint32_t b) { asm volatile("mbarrier.arrive.expect_tx.shared.b64 _, [%0], %1;" ::"r"(a), "r"(b) : "memory"); }
__device__ __forceinline__ void mbar_arrive(uint32_t a) { asm volatile("mbarrier.arrive.shared.b64 _, [%0];" ::"r"(a) : "memory"); }
__device__ __forceinline__ void mbar_arrive_c(uint32_t a, uint32_t n) { asm volatile("mbarrier.arrive.shared::cluster.b64 _, [%0], %1;" ::"r"(a), "r"(n) : "memory"); }
__device__ __forceinline__ void mbar_wait(uint32_t a, uint32_t parity) {
  asm volatile("{.reg .pred p, q; .reg .u32 n; mov.u32 n, 0;\n"
               "W: mbarrier.try_wait.parity.shared.b64 p, [%0], %1;\n"
               "add.u32 n, n, 1; setp.eq.u32 q, n, 0x100000; @q trap; @!p bra.uni W;}" ::"r"(a), "r"(parity) : "memory");
}
__device__ __forceinline__ uint32_t mapa(uint32_t a, uint32_t rank) { uint32_t r; asm("mapa.shared::cluster.u32 %0, %1, %2;" : "=r"(r) : "r"(a), "r"(rank)); return r; }
__device__ __forceinline__ void tma2d(uint32_t dst, const CUtensorMap* m, uint32_t bar, int c0, int c1) {
  asm volatile("cp.async.bulk.tensor.2d.shared::cluster.global.mbarrier::complete_tx::bytes [%0], [%1, {%3,%4}], [%2];"
               ::"r"(dst), "l"(m), "r"(bar), "r"(c0), "r"(c1) : "memory");
}
__device__ __forceinline__ void tma2d_mc(uint32_t dst, const CUtensorMap* m, uint32_t bar, int c0, int c1) {
  asm volatile("cp.async.bulk.tensor.2d.shared::cluster.global.mbarrier::complete_tx::bytes.multicast::cluster [%0], [%1, {%3,%4}], [%2], %5;"
               ::"r"(dst), "l"(m), "r"(bar), "r"(c0), "r"(c1), "h"((uint16_t)3) : "memory");
}
__device__ __forceinline__ void tma3d(uint32_t dst, const CUtensorMap* m, uint32_t bar, int c0, int c1, int c2) {
  asm volatile("cp.async.bulk.tensor.3d.shared::cluster.global.mbarrier::complete_tx::bytes [%0], [%1, {%3,%4,%5}], [%2];"
               ::"r"(dst), "l"(m), "r"(bar), "r"(c0), "r"(c1), "r"(c2) : "memory");
}
__device__ __forceinline__ void tma3d_mc(uint32_t dst, const CUtensorMap* m, uint32_t bar, int c0, int c1, int c2) {
  asm volatile("cp.async.bulk.tensor.3d.shared::cluster.global.mbarrier::complete_tx::bytes.multicast::cluster [%0], [%1, {%3,%4,%5}], [%2], %6;"
               ::"r"(dst), "l"(m), "r"(bar), "r"(c0), "r"(c1), "r"(c2), "h"((uint16_t)3) : "memory");
}
__device__ __forceinline__ void tma_store(const CUtensorMap* m, uint32_t src, int c0, int c1) {
  asm volatile("cp.async.bulk.tensor.2d.global.shared::cta.bulk_group [%0, {%2,%3}], [%1];" ::"l"(m), "r"(src), "r"(c0), "r"(c1) : "memory");
}
__device__ __forceinline__ void bulk_commit() { asm volatile("cp.async.bulk.commit_group;" ::: "memory"); }
__device__ __forceinline__ void bulk_wait_read() { asm volatile("cp.async.bulk.wait_group.read 0;" ::: "memory"); }
__device__ __forceinline__ void bulk_wait() { asm volatile("cp.async.bulk.wait_group 0;" ::: "memory"); }
__device__ __forceinline__ void bulk_g2s(uint32_t dst, const void* src, uint32_t bytes, uint32_t bar) {
  asm volatile("cp.async.bulk.shared::cluster.global.mbarrier::complete_tx::bytes [%0], [%1], %2, [%3];"
               ::"r"(dst), "l"(src), "r"(bytes), "r"(bar) : "memory");
}
__device__ __forceinline__ void prefetch_l2(const void* src, uint32_t bytes) {
  asm volatile("cp.async.bulk.prefetch.L2.global [%0], %1;" ::"l"(src), "r"(bytes) : "memory");
}
__device__ __forceinline__ void prefetch_tmap(const CUtensorMap* m) { asm volatile("prefetch.tensormap [%0];" ::"l"(m) : "memory"); }
__device__ __forceinline__ void fence_async_smem() { asm volatile("fence.proxy.async.shared::cta;" ::: "memory"); }
__device__ __forceinline__ void fence_async_global() { asm volatile("fence.proxy.async.global;" ::: "memory"); }
__device__ __forceinline__ void bar_sync(int id, int n) { asm volatile("bar.sync %0, %1;" ::"r"(id), "r"(n) : "memory"); }
__device__ __forceinline__ void cluster_wait() { asm volatile("barrier.cluster.wait.aligned;" ::: "memory"); }
__device__ __forceinline__ uint32_t lds32(uint32_t a) { uint32_t v; asm volatile("ld.volatile.shared.b32 %0,[%1];" : "=r"(v) : "r"(a)); return v; }
__device__ __forceinline__ uint2 lds64(uint32_t a) { uint2 v; asm volatile("ld.shared.v2.b32 {%0,%1},[%2];" : "=r"(v.x), "=r"(v.y) : "r"(a) : "memory"); return v; }
__device__ __forceinline__ uint4 lds128(uint32_t a) { uint4 v; asm volatile("ld.shared.v4.b32 {%0,%1,%2,%3},[%4];" : "=r"(v.x), "=r"(v.y), "=r"(v.z), "=r"(v.w) : "r"(a) : "memory"); return v; }
__device__ __forceinline__ float4 lds128f(uint32_t a) { float4 v; asm volatile("ld.shared.v4.f32 {%0,%1,%2,%3},[%4];" : "=f"(v.x), "=f"(v.y), "=f"(v.z), "=f"(v.w) : "r"(a) : "memory"); return v; }
__device__ __forceinline__ void sts128(uint32_t a, uint32_t x, uint32_t y, uint32_t z, uint32_t w) { asm volatile("st.shared.v4.b32 [%0],{%1,%2,%3,%4};" ::"r"(a), "r"(x), "r"(y), "r"(z), "r"(w) : "memory"); }
__device__ __forceinline__ void stsm4(uint32_t a, uint32_t x, uint32_t y, uint32_t z, uint32_t w) { asm volatile("stmatrix.sync.aligned.m8n8.x4.shared.b16 [%0],{%1,%2,%3,%4};" ::"r"(a), "r"(x), "r"(y), "r"(z), "r"(w) : "memory"); }
__device__ __forceinline__ void st_async128(uint32_t a, uint32_t bar, uint32_t x, uint32_t y, uint32_t z, uint32_t w) {
  asm volatile("st.async.weak.shared::cluster.mbarrier::complete_tx::bytes.v4.b32 [%0],{%2,%3,%4,%5},[%1];" ::"r"(a), "r"(bar), "r"(x), "r"(y), "r"(z), "r"(w) : "memory");
}
__device__ __forceinline__ uint32_t packbf(float lo, float hi) { uint32_t r; asm("cvt.rn.bf16x2.f32 %0, %1, %2;" : "=r"(r) : "f"(hi), "f"(lo)); return r; }
__device__ __forceinline__ uint32_t packbf_relu(float lo, float hi) { uint32_t r; asm("cvt.rn.relu.bf16x2.f32 %0, %1, %2;" : "=r"(r) : "f"(hi), "f"(lo)); return r; }
__device__ __forceinline__ uint32_t bmul2(uint32_t a, uint32_t b) { uint32_t r; asm("mul.rn.bf16x2 %0, %1, %2;" : "=r"(r) : "r"(a), "r"(b)); return r; }
__device__ __forceinline__ uint32_t bfma2(uint32_t a, uint32_t b, uint32_t c) { uint32_t r; asm("fma.rn.bf16x2 %0, %1, %2, %3;" : "=r"(r) : "r"(a), "r"(b), "r"(c)); return r; }
__device__ __forceinline__ float bflo(uint32_t v) { return __uint_as_float(v << 16); }
__device__ __forceinline__ float bfhi(uint32_t v) { return __uint_as_float(v & 0xffff0000u); }
__device__ __forceinline__ uint32_t ldg_relaxed(const uint32_t* p) { uint32_t v; asm volatile("ld.relaxed.gpu.global.b32 %0,[%1];" : "=r"(v) : "l"(p) : "memory"); return v; }
__device__ __forceinline__ uint4 ldg_relaxed4(const uint32_t* p) { uint4 v; asm volatile("ld.relaxed.gpu.global.v4.b32 {%0,%1,%2,%3},[%4];" : "=r"(v.x), "=r"(v.y), "=r"(v.z), "=r"(v.w) : "l"(p) : "memory"); return v; }
__device__ __forceinline__ float2 ldg_cg2f(const void* p) { float2 v; asm volatile("ld.global.cg.v2.f32 {%0,%1},[%2];" : "=f"(v.x), "=f"(v.y) : "l"(p) : "memory"); return v; }
__device__ __forceinline__ void stg_relaxed4(uint32_t* p, uint32_t x, uint32_t y, uint32_t z, uint32_t w) { asm volatile("st.relaxed.gpu.global.v4.b32 [%0],{%1,%2,%3,%4};" ::"l"(p), "r"(x), "r"(y), "r"(z), "r"(w) : "memory"); }
__device__ __forceinline__ void signal(uint32_t* cnt) { asm volatile("red.release.gpu.global.add.u32 [%0], 1;" ::"l"(cnt) : "memory"); }
__device__ __forceinline__ void wait_count(const uint32_t* cnt, uint32_t target) {
  int it = 0;
  while (true) {
    uint32_t v;
    asm volatile("ld.acquire.gpu.global.b32 %0,[%1];" : "=r"(v) : "l"(cnt) : "memory");
    if ((int)(v - target) >= 0) break;
    __nanosleep(32);
    if (++it > (1 << 21)) __trap();
  }
}

template <int LO, int HI> __device__ __forceinline__ void rename(float* d) {
#pragma unroll
  for (int i = LO; i < HI; i++) { float e; asm volatile("mov.b32 %0, %1;" : "=f"(e) : "f"(d[i])); d[i] = e; }
}
template <int M> __device__ __forceinline__ void drain4(const float* d, uint32_t ya, uint32_t ybar, bool lane0) {
  uint32_t r[4];
#pragma unroll
  for (int q = 0; q < 4; q++) {
    const int mu = M + q;
    float v0 = d[4 * mu], v1 = d[4 * mu + 1];
    if (mu > 0) { v0 += d[4 * mu - 2]; v1 += d[4 * mu - 1]; }
    r[q] = packbf(v0, v1);
  }
  asm volatile("stmatrix.sync.aligned.m8n8.x4.trans.shared.b16 [%0],{%1,%2,%3,%4};" ::"r"(ya + M * 128), "r"(r[0]), "r"(r[1]), "r"(r[2]), "r"(r[3]) : "memory");
  if constexpr ((M & 7) == 4) {
    __syncwarp();
    if (lane0) mbar_arrive(ybar + (M >> 3) * 8);
  }
}
__device__ __forceinline__ void lda(uint32_t* a, uint32_t ua) { a[0] = lds32(ua); a[1] = lds32(ua + 128); a[2] = lds32(ua - 16); a[3] = lds32(ua + 112); }
template <int P> struct Pass {
  static __device__ __forceinline__ void run(float* d, uint32_t (*a)[4], uint32_t ua, uint64_t db, uint32_t ya, uint32_t ubar, uint32_t ybar, bool lane0) {
    if constexpr (P > 0) rename<8 * (P - 1), 128>(d);
    wg_fence();
    wgmma_rs<256 - 16 * P>(d + 8 * P, a[P & 1], db, P != 0);
    wg_commit();
    if constexpr (P < 15) {
      if constexpr (P & 1) mbar_wait(ubar + 8 * ((P + 1) / 2), 0);
      lda(a[(P + 1) & 1], ua + (P + 1) * 256);
    }
    if constexpr (P >= 3 && (P & 1)) drain4<2 * P - 6>(d, ya, ybar, lane0);
    wg_wait<0>();
    if constexpr (P < 15) Pass<P + 1>::run(d, a, ua, db, ya, ubar, ybar, lane0);
    else { rename<120, 128>(d); drain4<28>(d, ya, ybar, lane0); }
  }
};

__device__ __forceinline__ uint32_t off_T(int r) { return r == 0 ? OFF_T0 : r == 1 ? OFF_T1 : r == 2 ? OFF_T2 : OFF_T3; }
__device__ __forceinline__ uint32_t off_Y(int r) { return r == 1 ? OFF_KVA : r == 2 ? OFF_KVB : OFF_X; }
__device__ __forceinline__ uint32_t off_act(int tile, int wg, int b) {
  return b < 2 ? OFF_X + wg * 16384 + b * 8192 : tile == 0 ? (2 * wg + b - 2) * 49152 + 40960 : 180224 + wg * 8192;
}

template <int NT>
__device__ __forceinline__ void gemm1_main(float* out, uint32_t sb, int wg, uint32_t ebar, bool rel) {
  const uint32_t bar = sb + OFF_BAR;
  float acc[NT / 2];
  const uint64_t da0 = mkdesc(sb + wg * 8192, 16, 1024, 1), db0 = mkdesc(sb + 16384, 8192, 1024, 1);
  mbar_wait(bar + 8 * B_FULL1, 0);
  wg_fence();
#pragma unroll
  for (int kk = 0; kk < 4; kk++) wgmma_ss<NT>(acc, da0 + kk * 2, db0 + kk * 128, kk != 0);
  wg_commit();
#pragma unroll 1
  for (int kb = 1; kb < 16; kb++) {
    const int s = kb & 3;
    mbar_wait(bar + 8 * (B_FULL1 + s), (kb >> 2) & 1);
    const uint64_t da = da0 + s * 3072, db = db0 + s * 3072;
    wg_fence();
#pragma unroll
    for (int kk = 0; kk < 4; kk++) wgmma_ss<NT>(acc, da + kk * 2, db + kk * 128, 1);
    wg_commit();
    wg_wait<1>();
    if (rel) mbar_arrive_c(ebar + 8 * (B_EMPTY1 + ((kb - 1) & 3)), 1);
  }
  wg_wait<0>();
#pragma unroll
  for (int i = 0; i < NT / 2; i++) asm volatile("mov.b32 %0, %1;" : "=f"(out[i]) : "f"(acc[i]));
  if (rel) mbar_arrive_c(ebar + 8 * (B_EMPTY1 + 3), 1);
}

__global__ void __cluster_dims__(2, 1, 1) __launch_bounds__(NTHREADS, 1) fused_kernel(const __grid_constant__ Params P) {
  extern __shared__ __align__(1024) unsigned char smem[];
  const uint32_t sb = (uint32_t)__cvta_generic_to_shared(smem);
  const uint32_t bar = sb + OFF_BAR;
  const int tid = threadIdx.x, warp = __shfl_sync(0xffffffffu, tid >> 5, 0), lane = tid & 31;
  const int c = blockIdx.x, m = c & 15, j = c >> 4, rank = c & 1;

  if (lane == 0) {
    if (warp == 8) {
      TS(0);
#pragma unroll
      for (int i = 0; i < 2; i++) { mbar_init(bar + 8 * (B_KVFULL + i), 1); mbar_init(bar + 8 * (B_KFULL + i), 2); }
#pragma unroll 1
      for (int i = 0; i < 2; i++) {
        mbar_expect_tx(bar + 8 * (B_KVFULL + i), 2 * KV_STAGE);
        tma3d(sb + OFF_KVA + i * KV_STAGE, &P.tm_k, bar + 8 * (B_KVFULL + i), 8 * (c & ~1), 32 * i + 16 * rank - 1, 0);
        tma3d(sb + OFF_KVB + i * KV_STAGE, &P.tm_v, bar + 8 * (B_KVFULL + i), 8 * (c & ~1), 32 * i + 16 * rank - 1, 0);
        mbar_expect_tx(bar + 8 * (B_KFULL + i), 4080);
        bulk_g2s(sb + OFF_T0 + 2 * UT_SIZE + i * KT_SIZE + 32, P.ssm_k + (size_t)(8 * c + i) * S + 8, 4080, bar + 8 * (B_KFULL + i));
      }
    } else if (warp < 8) {
      const uint32_t cnt = (0x84411881u >> (4 * warp)) & 15;
#pragma unroll
      for (int i = 0; i < 8; i++) mbar_init(bar + 8 * (16 + 8 * warp + i), cnt);
      if (warp == 0) {
#pragma unroll
        for (int i = 0; i < 8; i++) mbar_expect_tx(bar + 8 * (B_UFULL + i), 8192);
      }
    } else if (warp < 11) {
#pragma unroll
      for (int i = 2; i < 8; i++) mbar_init(bar + 8 * (8 * (warp - 9) + i), warp - 8);
    }
    asm volatile("fence.mbarrier_init.release.cluster;" ::: "memory");
  }
  if (warp == 11 && lane < 16) sts128(sb + off_T(lane >> 2) + (lane & 3) * UT_COPY, 0, 0, 0, 0);
  __syncthreads();
  asm volatile("barrier.cluster.arrive.relaxed.aligned;" ::: "memory");

  if (warp < 8) {
    if (tid == 32) TS(46);
    if (warp == 0 && lane < 8) {
      const uint4 v = __ldg((const uint4*)(P.ssm_k + (size_t)(8 * c + lane) * S));
      const float k0 = bflo(v.x) + __bfloat162float(P.ssm_D[8 * c + lane]);
      const uint32_t kt = sb + off_T(lane >> 1) + 2 * UT_SIZE + (lane & 1) * KT_SIZE;
      sts128(kt, 0, 0, 0, 0);
      sts128(kt + 16, (v.x & 0xffff0000u) | (packbf(k0, 0.f) & 0xffffu), v.y, v.z, v.w);
      fence_async_smem();
      mbar_arrive(bar + 8 * (B_KFULL + lane));
    }
    __syncwarp();
    cluster_wait();
    const int wg = warp >> 2, w = warp & 3, g = lane >> 2, t = lane & 3;
#pragma unroll 1
    for (int r = 0; r < 4; r++) {
      float d[128];
      uint32_t a[2][4];
      const uint32_t tb = sb + off_T(r);
      const uint32_t ua = tb + wg * UT_SIZE + ((g & 1) ? 0 : UT_COPY) + ((g >> 1) + 8 * w + 8 - t) * 4;
      const uint64_t db = mkdesc(tb + 2 * UT_SIZE + wg * KT_SIZE, 16, 128, 0);
      const uint32_t yb = sb + off_Y(r) + wg * YBUF + w * YW;
      mbar_wait(bar + 8 * (r == 3 ? B_ZDONE : B_UFULL), 0);
      lda(a[0], ua);
      if (lane < 2 * w) sts128(yb + lane * 16, 0, 0, 0, 0);
      mbar_wait(bar + 8 * (B_KFULL + 2 * r + wg), 0);
      if (tid == 0) TS(1 + r);
      Pass<0>::run(d, a, ua, db, yb + (2 * w + lane) * 16, bar + 8 * B_UFULL, bar + 8 * (B_YFULL + 4 * r), lane == 0);
    }
    if (tid == 0) TS(5);
    const bool rel = lane == 0 && w < 2;
    const uint32_t ebar = mapa(bar, w & 1);
    const int id = lane >> 3, srow = 16 * w + (lane & 7) + 8 * (id & 1);
    const uint32_t soff = srow * 128, sx = ((id >> 1) ^ (srow & 7)) << 4;
    {
      float2 st0, st1;
#pragma unroll 1
      for (int tile = 0; tile < 2; tile++) {
        float acc[128];
        if (tile == 0) {
          gemm1_main<256>(acc, sb, wg, ebar, rel);
          const int r0 = 128 * m + 64 * wg + 16 * w + g;
          st0 = ldg_cg2f(g_hstat + r0);
          st1 = ldg_cg2f(g_hstat + r0 + 8);
        } else {
          gemm1_main<192>(acc, sb, wg, ebar, rel);
#pragma unroll
          for (int i = 96; i < 128; i++) asm volatile("mov.b32 %0, 0;" : "=f"(acc[i]));
          mbar_wait(bar + 8 * B_XFREE, 0);
        }
        mbar_wait(bar + 8 * B_CSFULL, tile);
        if (tid == 0) TS(44 + tile);
        const uint32_t csb = sb + OFF_CSB + t * 16;
#pragma unroll
        for (int b = 0; b < 4; b++) {
          if (b == 3 && tile) break;
          if (b == 2) mbar_wait(bar + 8 * (B_EMPTY1 + 3), 0);
          const uint32_t dst = sb + off_act(tile, wg, b) + soff;
#pragma unroll
          for (int p = 0; p < 4; p++) {
            uint32_t o[4];
#pragma unroll
            for (int e = 0; e < 2; e++) {
              const int mu = 8 * b + 2 * p + e;
              const float4 cb = lds128f(csb + mu * 64);
              const float a0 = fmaf(acc[4 * mu + 0], st0.y, fmaf(st0.x, cb.x, cb.z));
              const float a1 = fmaf(acc[4 * mu + 1], st0.y, fmaf(st0.x, cb.y, cb.w));
              const float a2 = fmaf(acc[4 * mu + 2], st1.y, fmaf(st1.x, cb.x, cb.z));
              const float a3 = fmaf(acc[4 * mu + 3], st1.y, fmaf(st1.x, cb.y, cb.w));
              const uint32_t u0 = packbf_relu(a0, a1), u1 = packbf_relu(a2, a3);
              o[2 * e] = bmul2(u0, u0);
              o[2 * e + 1] = bmul2(u1, u1);
            }
            stsm4(dst + (sx ^ (p << 5)), o[0], o[1], o[2], o[3]);
          }
        }
        fence_async_smem();
        __syncwarp();
        if (lane == 0) mbar_arrive(bar + 8 * (B_ADONE + tile));
        if (tid == 0) TS(6 + tile);
      }
    }
    {
      float acc[64], res[64];
      const uint64_t da0 = mkdesc(sb + wg * 8192, 16, 1024, 1), db0 = mkdesc(sb + 16384, 8192, 1024, 1);
      int s = 0, ph = 0, prev = 0;
#pragma unroll 1
      for (int kb = 0; kb < 56; kb++) {
        mbar_wait(bar + 8 * (B_FULL2 + s), ph);
        const uint64_t da = da0 + s * 2048, db = db0 + s * 2048;
        wg_fence();
#pragma unroll
        for (int kk = 0; kk < 4; kk++) wgmma_ss<128>(acc, da + kk * 2, db + kk * 128, (kb | kk) != 0);
        wg_commit();
        if (kb == 40) {
          const uint32_t* b2p = (const uint32_t*)(P.b2 + 128 * j) + t;
          uint32_t bv[16];
#pragma unroll
          for (int mu = 0; mu < 16; mu++) bv[mu] = __ldg(b2p + 4 * mu);
          mbar_wait(bar + 8 * B_HRES, 0);
#pragma unroll
          for (int h = 0; h < 2; h++) {
            const int row = 64 * wg + 16 * w + 8 * h + g;
            const uint32_t la = sb + OFF_X + row * 256 + t * 64;
            const int sw = (2 * row + (t >> 1)) & 3;
#pragma unroll
            for (int cc = 0; cc < 4; cc++) {
              const uint4 v = lds128(la + ((cc ^ sw) << 4));
              const uint32_t vv[4] = {v.x, v.y, v.z, v.w};
#pragma unroll
              for (int q = 0; q < 4; q++) {
                const int mu = 4 * cc + q;
                res[4 * mu + 2 * h] = bflo(vv[q]) + bflo(bv[mu]);
                res[4 * mu + 2 * h + 1] = bfhi(vv[q]) + bfhi(bv[mu]);
              }
            }
          }
        }
        wg_wait<1>();
        if (rel && kb > 0 && kb <= 50) mbar_arrive_c(ebar + 8 * (B_EMPTY2 + prev), 1);
        prev = s;
        if (++s == 6) { s = 0; ph ^= 1; }
      }
      wg_wait<0>();
      rename<0, 64>(acc);
      if (tid == 0) TS(8);
      const uint32_t ob = sb + OFF_X + wg * 16384;
#pragma unroll
      for (int mu = 0; mu < 16; mu += 2) {
        stsm4(ob + (mu >> 3) * 8192 + soff + (sx ^ ((mu & 6) << 4)),
              packbf(acc[4 * mu] + res[4 * mu], acc[4 * mu + 1] + res[4 * mu + 1]), packbf(acc[4 * mu + 2] + res[4 * mu + 2], acc[4 * mu + 3] + res[4 * mu + 3]),
              packbf(acc[4 * mu + 4] + res[4 * mu + 4], acc[4 * mu + 5] + res[4 * mu + 5]), packbf(acc[4 * mu + 6] + res[4 * mu + 6], acc[4 * mu + 7] + res[4 * mu + 7]));
      }
      fence_async_smem();
      bar_sync(3 + wg, 128);
      if (w == 0 && lane == 0) {
        tma_store(&P.tm_out, ob, 128 * j, 128 * m + 64 * wg);
        tma_store(&P.tm_out, ob + 8192, 128 * j + 64, 128 * m + 64 * wg);
        bulk_commit();
        bulk_wait_read();
        if (tid == 0) TS(9);
      }
    }
  } else if (warp == 8) {
    if (lane == 0) {
#pragma unroll 1
      for (int i = 2; i < 8; i++) {
        mbar_expect_tx(bar + 8 * (B_KVFULL + i), 2 * KV_STAGE);
        tma3d(sb + OFF_KVA + i * KV_STAGE, &P.tm_k, bar + 8 * (B_KVFULL + i), 8 * (c & ~1), 32 * i + 16 * rank - 1, 0);
        tma3d(sb + OFF_KVB + i * KV_STAGE, &P.tm_v, bar + 8 * (B_KVFULL + i), 8 * (c & ~1), 32 * i + 16 * rank - 1, 0);
      }
    }
    __syncwarp();
    cluster_wait();
    if (lane == 0) {
      const uint32_t epoch = ldg_relaxed(g_epoch + c) + 1;
      const uint32_t bar0 = mapa(bar, 0), bar1 = mapa(bar, 1);
      prefetch_tmap(&P.tm_h); prefetch_tmap(&P.tm_w1); prefetch_tmap(&P.tm_act); prefetch_tmap(&P.tm_w2);
      prefetch_tmap(&P.tm_actst); prefetch_tmap(&P.tm_hres); prefetch_tmap(&P.tm_out);
      mbar_wait(bar + 8 * (B_KVFULL + KV_GATE), 0);
#pragma unroll 1
      for (int ch = 2; ch < 8; ch++) {
        if (ch == 4) prefetch_l2(P.x + (size_t)(128 * m + 16 * j) * D, 16 * D * 2);
        mbar_expect_tx(bar + 8 * (B_KFULL + ch), 4080);
        bulk_g2s(sb + off_T(ch >> 1) + 2 * UT_SIZE + (ch & 1) * KT_SIZE + 32, P.ssm_k + (size_t)(8 * c + ch) * S + 8, 4080, bar + 8 * (B_KFULL + ch));
      }
      mbar_wait(bar + 8 * (B_KFULL + 7), 0);
      TS(31);
      prefetch_l2(P.w1 + (size_t)c * 8 * F, 8 * F * 2);
#pragma unroll 1
      for (int it = 0; it < 32; it++) {
        const int s = it & 3, kb = it & 15, tile = it >> 4;
        if (it < 4) {
          mbar_wait(bar + 8 * (it < 2 ? B_ZDONE + 1 : it == 2 ? B_ZDONE + 2 : B_YFULL + 15), 0);
          fence_async_smem();
          mbar_arrive_c(bar0 + 8 * (B_EMPTY1 + s), 2);
          mbar_arrive_c(bar1 + 8 * (B_EMPTY1 + s), 2);
        }
        mbar_wait(bar + 8 * (B_EMPTY1 + s), (it >> 2) & 1);
        const uint32_t sa = sb + s * 49152, fb = bar + 8 * (B_FULL1 + s);
        const int nb = tile ? 3 : 4, n0 = 448 * j + 256 * tile;
        mbar_expect_tx(fb, 16384 + nb * 8192);
#pragma unroll 1
        for (int i = 0; i < nb; i++) tma3d_mc(sa + 16384 + i * 8192 + rank * 4096, &P.tm_w1, fb, n0 + 64 * i, 2 * (kb >> 2), 32 * (kb & 3) + 16 * rank);
        if (it < 16 && (it & 3) == 0) { wait_count(g_hcnt + ((it >> 2) * 16 + m) * 32, epoch * 16); fence_async_global(); TS(11 + (it >> 2)); }
        tma2d(sa, &P.tm_h, fb, 64 * kb, 128 * m);
        if (it == 8) prefetch_l2(P.w2 + (size_t)c * 28 * D, 28 * D * 2);
      }
      int s = 0, ph = 0;
#pragma unroll 1
      for (int kb = 0; kb < 56; kb++) {
        if (kb < 6) mbar_wait(bar + 8 * (B_EMPTY1 + (2 * kb + 1) / 3), 0);
        mbar_wait(bar + 8 * (B_EMPTY2 + s), ph);
        const int col = kb < 32 ? 448 * (kb >> 2) + 64 * (kb & 3) : 448 * ((kb - 32) / 3) + 256 + 64 * ((kb - 32) % 3);
        const uint32_t sa = sb + s * 32768, fb = bar + 8 * (B_FULL2 + s);
        mbar_expect_tx(fb, 32768);
        tma2d_mc(sa + 16384 + rank * 8192, &P.tm_w2, fb, 128 * j + 64 * rank, col);
        if ((kb & 31) == 0) { wait_count(g_acnt + ((kb >> 5) * 16 + m) * 32, epoch * 8); fence_async_global(); TS(15 + (kb >> 5)); }
        tma2d(sa, &P.tm_act, fb, col, 128 * m);
        if (++s == 6) { s = 0; ph ^= 1; }
      }
    }
  } else {
    const int zw = warp - 9;
    {
      uint32_t W[4][4];
      const uint4* wp = (const uint4*)(P.shift_k + (size_t)32 * ((c & ~1) + (lane & 1)));
#pragma unroll
      for (int p = 0; p < 4; p++) {
        const uint4 v = __ldg(wp + p);
        W[0][p] = __byte_perm(v.x, v.z, 0x5410); W[1][p] = __byte_perm(v.x, v.z, 0x7632);
        W[2][p] = __byte_perm(v.y, v.w, 0x5410); W[3][p] = __byte_perm(v.y, v.w, 0x7632);
      }
      const uint32_t rb = mapa(sb, lane & 1);
      cluster_wait();
#pragma unroll 1
      for (int st = zw; st < 8; st += 3) {
        mbar_wait(bar + 8 * (B_KVFULL + st), 0);
        if (lane == 0) TS(48 + st);
        const uint32_t ka = sb + OFF_KVA + st * KV_STAGE + lane * 16, va = sb + OFF_KVB + st * KV_STAGE + lane * 16;
        uint32_t u[9][4];
        uint4 k3 = lds128(ka + 4 * 544), k2 = lds128(ka + 5 * 544), k1 = lds128(ka + 6 * 544);
#pragma unroll
        for (int i = 0; i < 9; i++) {
          const uint32_t o = i == 0 ? 7 * 544 : (i - 1) * 544 + 32;
          const uint4 k0 = lds128(ka + o), v = lds128(va + o);
          u[i][0] = bmul2(bfma2(k0.x, W[0][0], bfma2(k1.x, W[1][0], bfma2(k2.x, W[2][0], bmul2(k3.x, W[3][0])))), v.x);
          u[i][1] = bmul2(bfma2(k0.y, W[0][1], bfma2(k1.y, W[1][1], bfma2(k2.y, W[2][1], bmul2(k3.y, W[3][1])))), v.y);
          u[i][2] = bmul2(bfma2(k0.z, W[0][2], bfma2(k1.z, W[1][2], bfma2(k2.z, W[2][2], bmul2(k3.z, W[3][2])))), v.z);
          u[i][3] = bmul2(bfma2(k0.w, W[0][3], bfma2(k1.w, W[1][3], bfma2(k2.w, W[2][3], bmul2(k3.w, W[3][3])))), v.w);
          k3 = k2; k2 = k1; k1 = k0;
        }
        const uint32_t ub = rb + OFF_BAR + 8 * (B_UFULL + st);
#pragma unroll
        for (int p = 0; p < 4; p++) {
          const uint32_t ta = rb + off_T(p) + 16 + (32 * st + 16 * rank + (lane >> 1)) * 16;
#pragma unroll
          for (int e = 0; e < 2; e++) {
            const uint32_t sel = e ? 0x7632 : 0x5410;
            st_async128(ta + e * UT_SIZE, ub, __byte_perm(u[2][p], u[1][p], sel), __byte_perm(u[4][p], u[3][p], sel),
                        __byte_perm(u[6][p], u[5][p], sel), __byte_perm(u[8][p], u[7][p], sel));
            st_async128(ta + e * UT_SIZE + UT_COPY, ub, __byte_perm(u[1][p], u[0][p], sel), __byte_perm(u[3][p], u[2][p], sel),
                        __byte_perm(u[5][p], u[4][p], sel), __byte_perm(u[7][p], u[6][p], sel));
          }
        }
        if (lane == 0) TS(56 + st);
      }
    }
    const uint32_t epoch = ldg_relaxed(g_epoch + c) + 1;
    if (zw == 0) {
#pragma unroll 1
      for (int qt = 0; qt < 16; qt++) {
        mbar_wait(bar + 8 * (B_YFULL + qt), 0);
        const uint32_t yb = sb + off_Y(qt >> 2) + (qt & 3) * 1024 + lane * 8;
        uint32_t* zp = g_z + (size_t)((qt >> 2) * NCTA + c) * S + (qt & 3) * 512 + lane * 4;
#pragma unroll
        for (int hf = 0; hf < 2; hf++) {
          uint2 p[2][8];
#pragma unroll
          for (int k = 0; k < 2; k++)
#pragma unroll
            for (int i = 0; i < 8; i++) p[k][i] = lds64(yb + i * YW + (2 * hf + k) * 256);
#pragma unroll
          for (int k = 0; k < 2; k++) {
            float a[2][4];
#pragma unroll
            for (int e = 0; e < 2; e++) {
              const uint2* pp = p[k] + 4 * e;
              a[e][0] = (bflo(pp[0].x) + bflo(pp[1].x)) + (bflo(pp[2].x) + bflo(pp[3].x));
              a[e][1] = (bfhi(pp[0].x) + bfhi(pp[1].x)) + (bfhi(pp[2].x) + bfhi(pp[3].x));
              a[e][2] = (bflo(pp[0].y) + bflo(pp[1].y)) + (bflo(pp[2].y) + bflo(pp[3].y));
              a[e][3] = (bfhi(pp[0].y) + bfhi(pp[1].y)) + (bfhi(pp[2].y) + bfhi(pp[3].y));
            }
            stg_relaxed4(zp + (2 * hf + k) * 128, max(packbf(a[0][0], a[1][0]), 1u), max(packbf(a[0][1], a[1][1]), 1u),
                         max(packbf(a[0][2], a[1][2]), 1u), max(packbf(a[0][3], a[1][3]), 1u));
          }
        }
        if ((qt & 3) == 3) {
          __syncwarp();
          if (lane == 0) { mbar_arrive(bar + 8 * (B_ZDONE + (qt >> 2))); TS(17 + (qt >> 2)); }
        }
      }
#pragma unroll 1
      for (int tile = 0; tile < 2; tile++) {
        const int n0 = 448 * j + 256 * tile;
        if (tile == 0 || m < 12) {
          float cs[8];
#pragma unroll
          for (int i = 0; i < 8; i++) cs[i] = 0.f;
          const __nv_bfloat16* wp = P.w1 + (size_t)(lane >> 1) * F + n0 + 16 * m + 8 * (lane & 1);
#pragma unroll 1
          for (int b = 0; b < 4; b++) {
            uint4 v[16];
#pragma unroll
            for (int i = 0; i < 16; i++) v[i] = __ldg((const uint4*)(wp + (size_t)(16 * b + i) * 16 * F));
#pragma unroll
            for (int i = 0; i < 16; i++) {
              cs[0] += bflo(v[i].x); cs[1] += bfhi(v[i].x); cs[2] += bflo(v[i].y); cs[3] += bfhi(v[i].y);
              cs[4] += bflo(v[i].z); cs[5] += bfhi(v[i].z); cs[6] += bflo(v[i].w); cs[7] += bfhi(v[i].w);
            }
          }
#pragma unroll 1
          for (int o = 2; o < 32; o <<= 1) {
#pragma unroll
            for (int i = 0; i < 8; i++) cs[i] += __shfl_xor_sync(0xffffffffu, cs[i], o);
          }
          if (lane < 2) {
            float4* cp = (float4*)(g_cs + n0 + 16 * m + 8 * lane);
            cp[0] = make_float4(cs[0], cs[1], cs[2], cs[3]);
            cp[1] = make_float4(cs[4], cs[5], cs[6], cs[7]);
          }
          __syncwarp();
          if (lane == 0) signal(g_ccnt + (tile * 8 + j) * 32);
        }
        if (lane == 0) wait_count(g_ccnt + (tile * 8 + j) * 32, epoch * (tile ? 12 : 16));
        __syncwarp();
        float2 cv[4];
        uint32_t bv[4];
#pragma unroll
        for (int i = 0; i < 4; i++)
          if (i < 3 || tile == 0) { cv[i] = ldg_cg2f(g_cs + n0 + 2 * (lane + 32 * i)); bv[i] = __ldg((const uint32_t*)(P.b1 + n0) + lane + 32 * i); }
        if (tile) mbar_wait(bar + 8 * B_ADONE, 0);
#pragma unroll
        for (int i = 0; i < 4; i++)
          if (i < 3 || tile == 0)
            sts128(sb + OFF_CSB + (lane + 32 * i) * 16, __float_as_uint(cv[i].x), __float_as_uint(cv[i].y), bv[i] << 16, bv[i] & 0xffff0000u);
        __syncwarp();
        if (lane == 0) { mbar_arrive(bar + 8 * B_CSFULL); TS(21 + 19 * tile); }
      }
    } else {
      const int hw = zw - 1, rowb = 128 * m + 16 * j;
      {
        const uint4* xp = (const uint4*)(P.x + (size_t)(rowb + 8 * hw) * D) + lane;
        uint4 v[4][4];
#pragma unroll
        for (int a = 0; a < 4; a++)
#pragma unroll
          for (int k = 0; k < 4; k++) v[a][k] = __ldg(xp + a * 128 + 32 * k);
#pragma unroll 1
        for (int b = 0; b < 2; b++) {
          float t1[4], t2[4];
#pragma unroll
          for (int a = 0; a < 4; a++) {
            t1[a] = 0.f; t2[a] = 0.f;
#pragma unroll
            for (int k = 0; k < 4; k++) {
              const uint32_t vv[4] = {v[a][k].x, v[a][k].y, v[a][k].z, v[a][k].w};
              v[a][k] = __ldg(xp + (4 + a) * 128 + 32 * k);
#pragma unroll
              for (int i = 0; i < 4; i++) {
                const float lo = bflo(vv[i]), hi = bfhi(vv[i]);
                t1[a] += lo + hi;
                t2[a] = fmaf(lo, lo, fmaf(hi, hi, t2[a]));
              }
            }
          }
#pragma unroll 1
          for (int o = 1; o < 32; o <<= 1) {
#pragma unroll
            for (int a = 0; a < 4; a++) { t1[a] += __shfl_xor_sync(0xffffffffu, t1[a], o); t2[a] += __shfl_xor_sync(0xffffffffu, t2[a], o); }
          }
          const float s1 = lane == 0 ? t1[0] : lane == 1 ? t1[1] : lane == 2 ? t1[2] : t1[3];
          const float s2 = lane == 0 ? t2[0] : lane == 1 ? t2[1] : lane == 2 ? t2[2] : t2[3];
          const float mu = s1 * (1.f / D);
          const float rs = rsqrtf(fmaxf(fmaf(-mu, mu, s2 * (1.f / D)), 0.f) + 1e-5f);
          if (lane < 4) ((float2*)(smem + OFF_XS))[8 * hw + 4 * b + lane] = make_float2(-mu * rs, rs);
        }
      }
      const int q = lane & 3, i0 = 64 * hw + (lane >> 2), row0 = rowb + 4 * q;
      const uint32_t* xp = (const uint32_t*)(P.x + (size_t)row0 * D) + 4 * i0;
      uint32_t xv[8][4];
#pragma unroll
      for (int k = 0; k < 8; k++)
#pragma unroll
        for (int a = 0; a < 4; a++) xv[k][a] = __ldg(xp + a * (D / 2) + 32 * k);
      bar_sync(1, 64);
      if (tid == 320) TS(22);
      float2 xs[4];
#pragma unroll
      for (int a = 0; a < 4; a++) xs[a] = ((const float2*)(smem + OFF_XS))[4 * q + a];
      float s1[4] = {0.f, 0.f, 0.f, 0.f}, s2[4] = {0.f, 0.f, 0.f, 0.f};
#pragma unroll 1
      for (int r = 0; r < 4; r++) {
        uint4 zv[8];
        uint32_t* zp = g_z + (size_t)(r * NCTA + i0) * S + row0;
        int it = 0;
        while (true) {
          uint32_t lo = 1;
#pragma unroll
          for (int k = 0; k < 8; k++) zv[k] = ldg_relaxed4(zp + (size_t)8 * k * S);
#pragma unroll
          for (int k = 0; k < 8; k++) lo = min(min(lo, min(zv[k].x, zv[k].y)), min(zv[k].z, zv[k].w));
          if (__all_sync(0xffffffffu, lo != 0)) break;
          __nanosleep(64);
          if (++it > (1 << 20)) __trap();
        }
        if (tid == 320) TS(27 + r);
        uint32_t* hp = (uint32_t*)(g_h + (size_t)row0 * D) + 128 * r + i0;
        const uint32_t* xn = xp + min(r + 1, 3);
#pragma unroll
        for (int k = 0; k < 8; k++) {
#pragma unroll
          for (int a = 0; a < 4; a++) {
            const uint32_t xx = xv[k][a];
            const uint32_t zz = a == 0 ? zv[k].x : a == 1 ? zv[k].y : a == 2 ? zv[k].z : zv[k].w;
            const float x0 = bflo(xx), x1 = bfhi(xx);
            const uint32_t o = packbf(fmaf(fmaf(x0, xs[a].y, xs[a].x), bflo(zz), x0), fmaf(fmaf(x1, xs[a].y, xs[a].x), bfhi(zz), x1));
            hp[a * (D / 2) + 8 * k] = o;
            const float f0 = bflo(o), f1 = bfhi(o);
            s1[a] += f0 + f1;
            s2[a] = fmaf(f0, f0, fmaf(f1, f1, s2[a]));
          }
        }
        if (r == 3) {
          float* red = (float*)(smem + OFF_RED);
#pragma unroll 1
          for (int o = 4; o < 32; o <<= 1) {
#pragma unroll
            for (int a = 0; a < 4; a++) { s1[a] += __shfl_xor_sync(0xffffffffu, s1[a], o); s2[a] += __shfl_xor_sync(0xffffffffu, s2[a], o); }
          }
          if (lane < 4) {
#pragma unroll
            for (int a = 0; a < 4; a++) ((float2*)red)[hw * 16 + 4 * q + a] = make_float2(s1[a], s2[a]);
          }
          bar_sync(1, 64);
          if (hw == 0 && lane < 16) {
            const float mu = (red[2 * lane] + red[32 + 2 * lane]) * (1.f / D);
            const float e2 = (red[2 * lane + 1] + red[33 + 2 * lane]) * (1.f / D);
            const float rs = rsqrtf(fmaxf(fmaf(-mu, mu, e2), 0.f) + 1e-5f);
            g_hstat[rowb + lane] = make_float2(-mu * rs, rs);
          }
        }
        fence_async_global();
        __syncwarp();
        if (tid == 320) TS(23 + r);
        if (lane == 0) signal(g_hcnt + (r * 16 + m) * 32);
        if (tid == 320) TS(32 + r);
#pragma unroll
        for (int k = 0; k < 8; k++) {
          stg_relaxed4(zp + (size_t)8 * k * S, 0, 0, 0, 0);
#pragma unroll
          for (int a = 0; a < 4; a++) xv[k][a] = __ldg(xn + a * (D / 2) + 32 * k);
        }
      }
      if (hw == 0 && lane == 0) {
        const uint32_t bar0 = mapa(bar, 0), bar1 = mapa(bar, 1);
#pragma unroll 1
        for (int tile = 0; tile < 2; tile++) {
          mbar_wait(bar + 8 * (B_ADONE + tile), 0);
          const int nb = tile ? 6 : 8;
#pragma unroll 1
          for (int i = nb - 1; i >= 0; i--) {
            tma_store(&P.tm_actst, sb + off_act(tile, i & 1, i >> 1), 448 * j + 256 * tile + 64 * (i >> 1), 128 * m + 64 * (i & 1));
            bulk_commit();
            bulk_wait_read();
            if (tile == 1 && i == 4) { mbar_arrive_c(bar0 + 8 * (B_EMPTY2 + 5), 2); mbar_arrive_c(bar1 + 8 * (B_EMPTY2 + 5), 2); }
            if (tile == 0 || i <= 4) __nanosleep(ST_SLEEP);
          }
          if (tile == 0) {
            mbar_arrive_c(bar + 8 * B_XFREE, 4);
#pragma unroll 1
            for (int s = 0; s < 5; s++) { mbar_arrive_c(bar0 + 8 * (B_EMPTY2 + s), 2); mbar_arrive_c(bar1 + 8 * (B_EMPTY2 + s), 2); }
          } else {
            mbar_expect_tx(bar + 8 * B_HRES, 32768);
            tma3d(sb + OFF_X, &P.tm_hres, bar + 8 * B_HRES, 32 * j, 0, 128 * m);
          }
          bulk_wait();
          fence_async_global();
          signal(g_acnt + (tile * 16 + m) * 32);
          TS(41 + tile);
        }
        g_epoch[c] = epoch;
      }
    }
  }
}

typedef CUresult (*PFN_encode)(CUtensorMap*, CUtensorMapDataType, cuuint32_t, void*, const cuuint64_t*, const cuuint64_t*, const cuuint32_t*,
                               const cuuint32_t*, CUtensorMapInterleave, CUtensorMapSwizzle, CUtensorMapL2promotion, CUtensorMapFloatOOBfill);

void encode(PFN_encode enc, CUtensorMap* m, const void* ptr, int rank, const cuuint64_t* dims, const cuuint64_t* strides, const cuuint32_t* box,
            CUtensorMapSwizzle swz) {
  const cuuint32_t es[5] = {1, 1, 1, 1, 1};
  enc(m, CU_TENSOR_MAP_DATA_TYPE_BFLOAT16, rank, (void*)ptr, dims, strides, box, es, CU_TENSOR_MAP_INTERLEAVE_NONE, swz,
      CU_TENSOR_MAP_L2_PROMOTION_L2_128B, CU_TENSOR_MAP_FLOAT_OOB_FILL_NONE);
}

}

extern "C" void kernel_launch(void* const* d_in, const int* in_sizes, int n_in, void* d_out, int out_size) {
  static PFN_encode enc = nullptr;
  static void *p_h = nullptr, *p_act = nullptr;
  if (!enc) {
    cudaDriverEntryPointQueryResult qr;
    cudaGetDriverEntryPoint("cuTensorMapEncodeTiled", (void**)&enc, cudaEnableDefault, &qr);
    cudaGetSymbolAddress(&p_h, g_h);
    cudaGetSymbolAddress(&p_act, g_act);
    cudaFuncSetAttribute(fused_kernel, cudaFuncAttributeMaxDynamicSharedMemorySize, SMEM_BYTES);
  }
  Params P;
  P.x = (const __nv_bfloat16*)d_in[0];
  P.shift_k = (const __nv_bfloat16*)d_in[3];
  P.ssm_k = (const __nv_bfloat16*)d_in[4];
  P.ssm_D = (const __nv_bfloat16*)d_in[5];
  P.w1 = (const __nv_bfloat16*)d_in[7];
  P.b1 = (const __nv_bfloat16*)d_in[8];
  P.w2 = (const __nv_bfloat16*)d_in[9];
  P.b2 = (const __nv_bfloat16*)d_in[10];
  {
    const cuuint64_t dims[3] = {D, S / 8, 8}, str[2] = {8 * D * 2, D * 2};
    const cuuint32_t box[3] = {16, 17, 8};
    encode(enc, &P.tm_k, d_in[1], 3, dims, str, box, CU_TENSOR_MAP_SWIZZLE_NONE);
    encode(enc, &P.tm_v, d_in[2], 3, dims, str, box, CU_TENSOR_MAP_SWIZZLE_NONE);
  }
  {
    const cuuint64_t dims[2] = {D, S}, str[1] = {D * 2};
    const cuuint32_t box[2] = {64, 128}, boxo[2] = {64, 64};
    encode(enc, &P.tm_h, p_h, 2, dims, str, box, CU_TENSOR_MAP_SWIZZLE_128B);
    encode(enc, &P.tm_out, d_out, 2, dims, str, boxo, CU_TENSOR_MAP_SWIZZLE_128B);
  }
  {
    const cuuint64_t dims[3] = {F, 8, D / 8}, str[2] = {F * 2, 8 * F * 2};
    const cuuint32_t box[3] = {64, 2, 16};
    encode(enc, &P.tm_w1, P.w1, 3, dims, str, box, CU_TENSOR_MAP_SWIZZLE_128B);
  }
  {
    const cuuint64_t dims[2] = {F, S}, str[1] = {F * 2};
    const cuuint32_t box[2] = {64, 128}, boxs[2] = {64, 64};
    encode(enc, &P.tm_act, p_act, 2, dims, str, box, CU_TENSOR_MAP_SWIZZLE_128B);
    encode(enc, &P.tm_actst, p_act, 2, dims, str, boxs, CU_TENSOR_MAP_SWIZZLE_128B);
  }
  {
    const cuuint64_t dims[2] = {D, F}, str[1] = {D * 2};
    const cuuint32_t box[2] = {64, 64};
    encode(enc, &P.tm_w2, P.w2, 2, dims, str, box, CU_TENSOR_MAP_SWIZZLE_128B);
  }
  {
    const cuuint64_t dims[3] = {256, 4, S}, str[2] = {512, D * 2};
    const cuuint32_t box[3] = {32, 4, 128};
    encode(enc, &P.tm_hres, p_h, 3, dims, str, box, CU_TENSOR_MAP_SWIZZLE_64B);
  }
  fused_kernel<<<NCTA, NTHREADS, SMEM_BYTES>>>(P);
}
```

```cpp
#include <cuda_runtime.h>
#include <cuda_bf16.h>
#include <cuda.h>
#include <stdint.h>

#define DBG_TS 0
#define ST_SLEEP 200

namespace {

constexpr int S = 2048, D = 1024, F = 3584;
constexpr int NCTA = 128, NTHREADS = 384;

constexpr int UT_COPY = 1040 * 4;
constexpr int UT_SIZE = 2 * UT_COPY;
constexpr int KT_SIZE = 16 + 4096;
constexpr int T_SIZE = 2 * (UT_SIZE + KT_SIZE);
constexpr int KV_BOX = 17 * 8 * 32;
constexpr int KV_SLOT = 4 * KV_BOX;
constexpr int KV_SIZE = 2 * KV_SLOT;
constexpr int YW = 4096 + 96;
constexpr int YBUF = 4 * YW;
constexpr int OFF_T3 = 196608 - T_SIZE;
constexpr int OFF_KVB = (OFF_T3 - KV_SIZE) & ~127;
constexpr int OFF_T2 = OFF_KVB - T_SIZE;
constexpr int OFF_KVA = (OFF_T2 - KV_SIZE) & ~127;
constexpr int OFF_T1 = OFF_KVA - T_SIZE;
constexpr int OFF_T0 = OFF_T1 - T_SIZE;
constexpr int OFF_X = 196608;
constexpr int OFF_HS = OFF_X + 32768;
constexpr int OFF_RED = OFF_X + 34816;
constexpr int OFF_BAR = OFF_X + 35200;
constexpr int SMEM_BYTES = 232448;
static_assert(OFF_T0 >= KV_SLOT && 2 * YBUF <= KV_SIZE && OFF_X + 2 * YBUF <= OFF_RED && OFF_BAR + 640 <= SMEM_BYTES, "smem map");
static_assert(OFF_T2 >= 98304, "stage 1 must only overlap T0,T1,KVA");
static_assert(OFF_T3 >= 147456, "stage 2 must not overlap T3");

enum {
  B_KVFULL = 0, B_KFULL = 8, B_UFULL = 16, B_YFULL = 24  , B_FULL1 = 40, B_ZDONE = 44, B_FULL2 = 48, B_CSFULL = 54, B_HRES = 55,
  B_EMPTY1 = 56, B_XFREE = 60, B_KVFREE = 61  , B_EMPTY2 = 64, B_ADONE = 72, B_UREST = 74
};

struct Params {
  CUtensorMap tm_k, tm_v, tm_h, tm_w1, tm_act, tm_actst, tm_w2, tm_hres, tm_out;
  const __nv_bfloat16 *x, *shift_k, *ssm_k, *ssm_D, *w1, *b1, *w2, *b2;
};

__device__ __align__(1024) uint32_t g_z[4 * NCTA * S];
__device__ __align__(1024) __nv_bfloat16 g_h[S * D];
__device__ __align__(1024) __nv_bfloat16 g_act[S * F];
__device__ __align__(128) uint4 g_hstat[S];
__device__ __align__(128) float g_cs[F];
__device__ __align__(128) uint32_t g_hcnt[4 * 16 * 32];
__device__ __align__(128) uint32_t g_acnt[3 * 16 * 32];
__device__ __align__(128) uint32_t g_ccnt[2 * 8 * 32];
__device__ __align__(128) uint32_t g_epoch[NCTA];
#define TS(slot) do {} while (0)

template<int N> __device__ __forceinline__ void wgmma_rs(float* d, const uint32_t* a, uint64_t db, int sc);
template<int N> __device__ __forceinline__ void wgmma_ss(float* d, uint64_t da, uint64_t db, int sc);
template<> __device__ __forceinline__ void wgmma_rs<16>(float* d, const uint32_t* a, uint64_t db, int sc) {
  asm volatile("{.reg .pred p; setp.ne.b32 p, %13, 0;\n"
  "wgmma.mma_async.sync.aligned.m64n16k16.f32.bf16.bf16 {%0,%1,%2,%3,%4,%5,%6,%7}, {%8,%9,%10,%11}, %12, p, 1, 1, 0;}\n"
  : "+f"(d[0]),"+f"(d[1]),"+f"(d[2]),"+f"(d[3]),"+f"(d[4]),"+f"(d[5]),"+f"(d[6]),"+f"(d[7])
  : "r"(a[0]), "r"(a[1]), "r"(a[2]), "r"(a[3]), "l"(db), "r"(sc));
}
template<> __device__ __forceinline__ void wgmma_rs<32>(float* d, const uint32_t* a, uint64_t db, int sc) {
  asm volatile("{.reg .pred p; setp.ne.b32 p, %21, 0;\n"
  "wgmma.mma_async.sync.aligned.m64n32k16.f32.bf16.bf16 {%0,%1,%2,%3,%4,%5,%6,%7,%8,%9,%10,%11,%12,%13,%14,%15}, {%16,%17,%18,%19}, %20, p, 1, 1, 0;}\n"
  : "+f"(d[0]),"+f"(d[1]),"+f"(d[2]),"+f"(d[3]),"+f"(d[4]),"+f"(d[5]),"+f"(d[6]),"+f"(d[7]),"+f"(d[8]),"+f"(d[9]),"+f"(d[10]),"+f"(d[11]),"+f"(d[12]),"+f"(d[13]),"+f"(d[14]),"+f"(d[15])
  : "r"(a[0]), "r"(a[1]), "r"(a[2]), "r"(a[3]), "l"(db), "r"(sc));
}
template<> __device__ __forceinline__ void wgmma_rs<48>(float* d, const uint32_t* a, uint64_t db, int sc) {
  asm volatile("{.reg .pred p; setp.ne.b32 p, %29, 0;\n"
  "wgmma.mma_async.sync.aligned.m64n48k16.f32.bf16.bf16 {%0,%1,%2,%3,%4,%5,%6,%7,%8,%9,%10,%11,%12,%13,%14,%15,%16,%17,%18,%19,%20,%21,%22,%23}, {%24,%25,%26,%27}, %28, p, 1, 1, 0;}\n"
  : "+f"(d[0]),"+f"(d[1]),"+f"(d[2]),"+f"(d[3]),"+f"(d[4]),"+f"(d[5]),"+f"(d[6]),"+f"(d[7]),"+f"(d[8]),"+f"(d[9]),"+f"(d[10]),"+f"(d[11]),"+f"(d[12]),"+f"(d[13]),"+f"(d[14]),"+f"(d[15]),"+f"(d[16]),"+f"(d[17]),"+f"(d[18]),"+f"(d[19]),"+f"(d[20]),"+f"(d[21]),"+f"(d[22]),"+f"(d[23])
  : "r"(a[0]), "r"(a[1]), "r"(a[2]), "r"(a[3]), "l"(db), "r"(sc));
}
template<> __device__ __forceinline__ void wgmma_rs<64>(float* d, const uint32_t* a, uint64_t db, int sc) {
  asm volatile("{.reg .pred p; setp.ne.b32 p, %37, 0;\n"
  "wgmma.mma_async.sync.aligned.m64n64k16.f32.bf16.bf16 {%0,%1,%2,%3,%4,%5,%6,%7,%8,%9,%10,%11,%12,%13,%14,%15,%16,%17,%18,%19,%20,%21,%22,%23,%24,%25,%26,%27,%28,%29,%30,%31}, {%32,%33,%34,%35}, %36, p, 1, 1, 0;}\n"
  : "+f"(d[0]),"+f"(d[1]),"+f"(d[2]),"+f"(d[3]),"+f"(d[4]),"+f"(d[5]),"+f"(d[6]),"+f"(d[7]),"+f"(d[8]),"+f"(d[9]),"+f"(d[10]),"+f"(d[11]),"+f"(d[12]),"+f"(d[13]),"+f"(d[14]),"+f"(d[15]),"+f"(d[16]),"+f"(d[17]),"+f"(d[18]),"+f"(d[19]),"+f"(d[20]),"+f"(d[21]),"+f"(d[22]),"+f"(d[23]),"+f"(d[24]),"+f"(d[25]),"+f"(d[26]),"+f"(d[27]),"+f"(d[28]),"+f"(d[29]),"+f"(d[30]),"+f"(d[31])
  : "r"(a[0]), "r"(a[1]), "r"(a[2]), "r"(a[3]), "l"(db), "r"(sc));
}
template<> __device__ __forceinline__ void wgmma_rs<80>(float* d, const uint32_t* a, uint64_t db, int sc) {
  asm volatile("{.reg .pred p; setp.ne.b32 p, %45, 0;\n"
  "wgmma.mma_async.sync.aligned.m64n80k16.f32.bf16.bf16 {%0,%1,%2,%3,%4,%5,%6,%7,%8,%9,%10,%11,%12,%13,%14,%15,%16,%17,%18,%19,%20,%21,%22,%23,%24,%25,%26,%27,%28,%29,%30,%31,%32,%33,%34,%35,%36,%37,%38,%39}, {%40,%41,%42,%43}, %44, p, 1, 1, 0;}\n"
  : "+f"(d[0]),"+f"(d[1]),"+f"(d[2]),"+f"(d[3]),"+f"(d[4]),"+f"(d[5]),"+f"(d[6]),"+f"(d[7]),"+f"(d[8]),"+f"(d[9]),"+f"(d[10]),"+f"(d[11]),"+f"(d[12]),"+f"(d[13]),"+f"(d[14]),"+f"(d[15]),"+f"(d[16]),"+f"(d[17]),"+f"(d[18]),"+f"(d[19]),"+f"(d[20]),"+f"(d[21]),"+f"(d[22]),"+f"(d[23]),"+f"(d[24]),"+f"(d[25]),"+f"(d[26]),"+f"(d[27]),"+f"(d[28]),"+f"(d[29]),"+f"(d[30]),"+f"(d[31]),"+f"(d[32]),"+f"(d[33]),"+f"(d[34]),"+f"(d[35]),"+f"(d[36]),"+f"(d[37]),"+f"(d[38]),"+f"(d[39])
  : "r"(a[0]), "r"(a[1]), "r"(a[2]), "r"(a[3]), "l"(db), "r"(sc));
}
template<> __device__ __forceinline__ void wgmma_rs<96>(float* d, const uint32_t* a, uint64_t db, int sc) {
  asm volatile("{.reg .pred p; setp.ne.b32 p, %53, 0;\n"
  "wgmma.mma_async.sync.aligned.m64n96k16.f32.bf16.bf16 {%0,%1,%2,%3,%4,%5,%6,%7,%8,%9,%10,%11,%12,%13,%14,%15,%16,%17,%18,%19,%20,%21,%22,%23,%24,%25,%26,%27,%28,%29,%30,%31,%32,%33,%34,%35,%36,%37,%38,%39,%40,%41,%42,%43,%44,%45,%46,%47}, {%48,%49,%50,%51}, %52, p, 1, 1, 0;}\n"
  : "+f"(d[0]),"+f"(d[1]),"+f"(d[2]),"+f"(d[3]),"+f"(d[4]),"+f"(d[5]),"+f"(d[6]),"+f"(d[7]),"+f"(d[8]),"+f"(d[9]),"+f"(d[10]),"+f"(d[11]),"+f"(d[12]),"+f"(d[13]),"+f"(d[14]),"+f"(d[15]),"+f"(d[16]),"+f"(d[17]),"+f"(d[18]),"+f"(d[19]),"+f"(d[20]),"+f"(d[21]),"+f"(d[22]),"+f"(d[23]),"+f"(d[24]),"+f"(d[25]),"+f"(d[26]),"+f"(d[27]),"+f"(d[28]),"+f"(d[29]),"+f"(d[30]),"+f"(d[31]),"+f"(d[32]),"+f"(d[33]),"+f"(d[34]),"+f"(d[35]),"+f"(d[36]),"+f"(d[37]),"+f"(d[38]),"+f"(d[39]),"+f"(d[40]),"+f"(d[41]),"+f"(d[42]),"+f"(d[43]),"+f"(d[44]),"+f"(d[45]),"+f"(d[46]),"+f"(d[47])
  : "r"(a[0]), "r"(a[1]), "r"(a[2]), "r"(a[3]), "l"(db), "r"(sc));
}
template<> __device__ __forceinline__ void wgmma_rs<112>(float* d, const uint32_t* a, uint64_t db, int sc) {
  asm volatile("{.reg .pred p; setp.ne.b32 p, %61, 0;\n"
  "wgmma.mma_async.sync.aligned.m64n112k16.f32.bf16.bf16 {%0,%1,%2,%3,%4,%5,%6,%7,%8,%9,%10,%11,%12,%13,%14,%15,%16,%17,%18,%19,%20,%21,%22,%23,%24,%25,%26,%27,%28,%29,%30,%31,%32,%33,%34,%35,%36,%37,%38,%39,%40,%41,%42,%43,%44,%45,%46,%47,%48,%49,%50,%51,%52,%53,%54,%55}, {%56,%57,%58,%59}, %60, p, 1, 1, 0;}\n"
  : "+f"(d[0]),"+f"(d[1]),"+f"(d[2]),"+f"(d[3]),"+f"(d[4]),"+f"(d[5]),"+f"(d[6]),"+f"(d[7]),"+f"(d[8]),"+f"(d[9]),"+f"(d[10]),"+f"(d[11]),"+f"(d[12]),"+f"(d[13]),"+f"(d[14]),"+f"(d[15]),"+f"(d[16]),"+f"(d[17]),"+f"(d[18]),"+f"(d[19]),"+f"(d[20]),"+f"(d[21]),"+f"(d[22]),"+f"(d[23]),"+f"(d[24]),"+f"(d[25]),"+f"(d[26]),"+f"(d[27]),"+f"(d[28]),"+f"(d[29]),"+f"(d[30]),"+f"(d[31]),"+f"(d[32]),"+f"(d[33]),"+f"(d[34]),"+f"(d[35]),"+f"(d[36]),"+f"(d[37]),"+f"(d[38]),"+f"(d[39]),"+f"(d[40]),"+f"(d[41]),"+f"(d[42]),"+f"(d[43]),"+f"(d[44]),"+f"(d[45]),"+f"(d[46]),"+f"(d[47]),"+f"(d[48]),"+f"(d[49]),"+f"(d[50]),"+f"(d[51]),"+f"(d[52]),"+f"(d[53]),"+f"(d[54]),"+f"(d[55])
  : "r"(a[0]), "r"(a[1]), "r"(a[2]), "r"(a[3]), "l"(db), "r"(sc));
}
template<> __device__ __forceinline__ void wgmma_rs<128>(float* d, const uint32_t* a, uint64_t db, int sc) {
  asm volatile("{.reg .pred p; setp.ne.b32 p, %69, 0;\n"
  "wgmma.mma_async.sync.aligned.m64n128k16.f32.bf16.bf16 {%0,%1,%2,%3,%4,%5,%6,%7,%8,%9,%10,%11,%12,%13,%14,%15,%16,%17,%18,%19,%20,%21,%22,%23,%24,%25,%26,%27,%28,%29,%30,%31,%32,%33,%34,%35,%36,%37,%38,%39,%40,%41,%42,%43,%44,%45,%46,%47,%48,%49,%50,%51,%52,%53,%54,%55,%56,%57,%58,%59,%60,%61,%62,%63}, {%64,%65,%66,%67}, %68, p, 1, 1, 0;}\n"
  : "+f"(d[0]),"+f"(d[1]),"+f"(d[2]),"+f"(d[3]),"+f"(d[4]),"+f"(d[5]),"+f"(d[6]),"+f"(d[7]),"+f"(d[8]),"+f"(d[9]),"+f"(d[10]),"+f"(d[11]),"+f"(d[12]),"+f"(d[13]),"+f"(d[14]),"+f"(d[15]),"+f"(d[16]),"+f"(d[17]),"+f"(d[18]),"+f"(d[19]),"+f"(d[20]),"+f"(d[21]),"+f"(d[22]),"+f"(d[23]),"+f"(d[24]),"+f"(d[25]),"+f"(d[26]),"+f"(d[27]),"+f"(d[28]),"+f"(d[29]),"+f"(d[30]),"+f"(d[31]),"+f"(d[32]),"+f"(d[33]),"+f"(d[34]),"+f"(d[35]),"+f"(d[36]),"+f"(d[37]),"+f"(d[38]),"+f"(d[39]),"+f"(d[40]),"+f"(d[41]),"+f"(d[42]),"+f"(d[43]),"+f"(d[44]),"+f"(d[45]),"+f"(d[46]),"+f"(d[47]),"+f"(d[48]),"+f"(d[49]),"+f"(d[50]),"+f"(d[51]),"+f"(d[52]),"+f"(d[53]),"+f"(d[54]),"+f"(d[55]),"+f"(d[56]),"+f"(d[57]),"+f"(d[58]),"+f"(d[59]),"+f"(d[60]),"+f"(d[61]),"+f"(d[62]),"+f"(d[63])
  : "r"(a[0]), "r"(a[1]), "r"(a[2]), "r"(a[3]), "l"(db), "r"(sc));
}
template<> __device__ __forceinline__ void wgmma_rs<144>(float* d, const uint32_t* a, uint64_t db, int sc) {
  asm volatile("{.reg .pred p; setp.ne.b32 p, %77, 0;\n"
  "wgmma.mma_async.sync.aligned.m64n144k16.f32.bf16.bf16 {%0,%1,%2,%3,%4,%5,%6,%7,%8,%9,%10,%11,%12,%13,%14,%15,%16,%17,%18,%19,%20,%21,%22,%23,%24,%25,%26,%27,%28,%29,%30,%31,%32,%33,%34,%35,%36,%37,%38,%39,%40,%41,%42,%43,%44,%45,%46,%47,%48,%49,%50,%51,%52,%53,%54,%55,%56,%57,%58,%59,%60,%61,%62,%63,%64,%65,%66,%67,%68,%69,%70,%71}, {%72,%73,%74,%75}, %76, p, 1, 1, 0;}\n"
  : "+f"(d[0]),"+f"(d[1]),"+f"(d[2]),"+f"(d[3]),"+f"(d[4]),"+f"(d[5]),"+f"(d[6]),"+f"(d[7]),"+f"(d[8]),"+f"(d[9]),"+f"(d[10]),"+f"(d[11]),"+f"(d[12]),"+f"(d[13]),"+f"(d[14]),"+f"(d[15]),"+f"(d[16]),"+f"(d[17]),"+f"(d[18]),"+f"(d[19]),"+f"(d[20]),"+f"(d[21]),"+f"(d[22]),"+f"(d[23]),"+f"(d[24]),"+f"(d[25]),"+f"(d[26]),"+f"(d[27]),"+f"(d[28]),"+f"(d[29]),"+f"(d[30]),"+f"(d[31]),"+f"(d[32]),"+f"(d[33]),"+f"(d[34]),"+f"(d[35]),"+f"(d[36]),"+f"(d[37]),"+f"(d[38]),"+f"(d[39]),"+f"(d[40]),"+f"(d[41]),"+f"(d[42]),"+f"(d[43]),"+f"(d[44]),"+f"(d[45]),"+f"(d[46]),"+f"(d[47]),"+f"(d[48]),"+f"(d[49]),"+f"(d[50]),"+f"(d[51]),"+f"(d[52]),"+f"(d[53]),"+f"(d[54]),"+f"(d[55]),"+f"(d[56]),"+f"(d[57]),"+f"(d[58]),"+f"(d[59]),"+f"(d[60]),"+f"(d[61]),"+f"(d[62]),"+f"(d[63]),"+f"(d[64]),"+f"(d[65]),"+f"(d[66]),"+f"(d[67]),"+f"(d[68]),"+f"(d[69]),"+f"(d[70]),"+f"(d[71])
  : "r"(a[0]), "r"(a[1]), "r"(a[2]), "r"(a[3]), "l"(db), "r"(sc));
}
template<> __device__ __forceinline__ void wgmma_rs<160>(float* d, const uint32_t* a, uint64_t db, int sc) {
  asm volatile("{.reg .pred p; setp.ne.b32 p, %85, 0;\n"
  "wgmma.mma_async.sync.aligned.m64n160k16.f32.bf16.bf16 {%0,%1,%2,%3,%4,%5,%6,%7,%8,%9,%10,%11,%12,%13,%14,%15,%16,%17,%18,%19,%20,%21,%22,%23,%24,%25,%26,%27,%28,%29,%30,%31,%32,%33,%34,%35,%36,%37,%38,%39,%40,%41,%42,%43,%44,%45,%46,%47,%48,%49,%50,%51,%52,%53,%54,%55,%56,%57,%58,%59,%60,%61,%62,%63,%64,%65,%66,%67,%68,%69,%70,%71,%72,%73,%74,%75,%76,%77,%78,%79}, {%80,%81,%82,%83}, %84, p, 1, 1, 0;}\n"
  : "+f"(d[0]),"+f"(d[1]),"+f"(d[2]),"+f"(d[3]),"+f"(d[4]),"+f"(d[5]),"+f"(d[6]),"+f"(d[7]),"+f"(d[8]),"+f"(d[9]),"+f"(d[10]),"+f"(d[11]),"+f"(d[12]),"+f"(d[13]),"+f"(d[14]),"+f"(d[15]),"+f"(d[16]),"+f"(d[17]),"+f"(d[18]),"+f"(d[19]),"+f"(d[20]),"+f"(d[21]),"+f"(d[22]),"+f"(d[23]),"+f"(d[24]),"+f"(d[25]),"+f"(d[26]),"+f"(d[27]),"+f"(d[28]),"+f"(d[29]),"+f"(d[30]),"+f"(d[31]),"+f"(d[32]),"+f"(d[33]),"+f"(d[34]),"+f"(d[35]),"+f"(d[36]),"+f"(d[37]),"+f"(d[38]),"+f"(d[39]),"+f"(d[40]),"+f"(d[41]),"+f"(d[42]),"+f"(d[43]),"+f"(d[44]),"+f"(d[45]),"+f"(d[46]),"+f"(d[47]),"+f"(d[48]),"+f"(d[49]),"+f"(d[50]),"+f"(d[51]),"+f"(d[52]),"+f"(d[53]),"+f"(d[54]),"+f"(d[55]),"+f"(d[56]),"+f"(d[57]),"+f"(d[58]),"+f"(d[59]),"+f"(d[60]),"+f"(d[61]),"+f"(d[62]),"+f"(d[63]),"+f"(d[64]),"+f"(d[65]),"+f"(d[66]),"+f"(d[67]),"+f"(d[68]),"+f"(d[69]),"+f"(d[70]),"+f"(d[71]),"+f"(d[72]),"+f"(d[73]),"+f"(d[74]),"+f"(d[75]),"+f"(d[76]),"+f"(d[77]),"+f"(d[78]),"+f"(d[79])
  : "r"(a[0]), "r"(a[1]), "r"(a[2]), "r"(a[3]), "l"(db), "r"(sc));
}
template<> __device__ __forceinline__ void wgmma_rs<176>(float* d, const uint32_t* a, uint64_t db, int sc) {
  asm volatile("{.reg .pred p; setp.ne.b32 p, %93, 0;\n"
  "wgmma.mma_async.sync.aligned.m64n176k16.f32.bf16.bf16 {%0,%1,%2,%3,%4,%5,%6,%7,%8,%9,%10,%11,%12,%13,%14,%15,%16,%17,%18,%19,%20,%21,%22,%23,%24,%25,%26,%27,%28,%29,%30,%31,%32,%33,%34,%35,%36,%37,%38,%39,%40,%41,%42,%43,%44,%45,%46,%47,%48,%49,%50,%51,%52,%53,%54,%55,%56,%57,%58,%59,%60,%61,%62,%63,%64,%65,%66,%67,%68,%69,%70,%71,%72,%73,%74,%75,%76,%77,%78,%79,%80,%81,%82,%83,%84,%85,%86,%87}, {%88,%89,%90,%91}, %92, p, 1, 1, 0;}\n"
  : "+f"(d[0]),"+f"(d[1]),"+f"(d[2]),"+f"(d[3]),"+f"(d[4]),"+f"(d[5]),"+f"(d[6]),"+f"(d[7]),"+f"(d[8]),"+f"(d[9]),"+f"(d[10]),"+f"(d[11]),"+f"(d[12]),"+f"(d[13]),"+f"(d[14]),"+f"(d[15]),"+f"(d[16]),"+f"(d[17]),"+f"(d[18]),"+f"(d[19]),"+f"(d[20]),"+f"(d[21]),"+f"(d[22]),"+f"(d[23]),"+f"(d[24]),"+f"(d[25]),"+f"(d[26]),"+f"(d[27]),"+f"(d[28]),"+f"(d[29]),"+f"(d[30]),"+f"(d[31]),"+f"(d[32]),"+f"(d[33]),"+f"(d[34]),"+f"(d[35]),"+f"(d[36]),"+f"(d[37]),"+f"(d[38]),"+f"(d[39]),"+f"(d[40]),"+f"(d[41]),"+f"(d[42]),"+f"(d[43]),"+f"(d[44]),"+f"(d[45]),"+f"(d[46]),"+f"(d[47]),"+f"(d[48]),"+f"(d[49]),"+f"(d[50]),"+f"(d[51]),"+f"(d[52]),"+f"(d[53]),"+f"(d[54]),"+f"(d[55]),"+f"(d[56]),"+f"(d[57]),"+f"(d[58]),"+f"(d[59]),"+f"(d[60]),"+f"(d[61]),"+f"(d[62]),"+f"(d[63]),"+f"(d[64]),"+f"(d[65]),"+f"(d[66]),"+f"(d[67]),"+f"(d[68]),"+f"(d[69]),"+f"(d[70]),"+f"(d[71]),"+f"(d[72]),"+f"(d[73]),"+f"(d[74]),"+f"(d[75]),"+f"(d[76]),"+f"(d[77]),"+f"(d[78]),"+f"(d[79]),"+f"(d[80]),"+f"(d[81]),"+f"(d[82]),"+f"(d[83]),"+f"(d[84]),"+f"(d[85]),"+f"(d[86]),"+f"(d[87])
  : "r"(a[0]), "r"(a[1]), "r"(a[2]), "r"(a[3]), "l"(db), "r"(sc));
}
template<> __device__ __forceinline__ void wgmma_rs<192>(float* d, const uint32_t* a, uint64_t db, int sc) {
  asm volatile("{.reg .pred p; setp.ne.b32 p, %101, 0;\n"
  "wgmma.mma_async.sync.aligned.m64n192k16.f32.bf16.bf16 {%0,%1,%2,%3,%4,%5,%6,%7,%8,%9,%10,%11,%12,%13,%14,%15,%16,%17,%18,%19,%20,%21,%22,%23,%24,%25,%26,%27,%28,%29,%30,%31,%32,%33,%34,%35,%36,%37,%38,%39,%40,%41,%42,%43,%44,%45,%46,%47,%48,%49,%50,%51,%52,%53,%54,%55,%56,%57,%58,%59,%60,%61,%62,%63,%64,%65,%66,%67,%68,%69,%70,%71,%72,%73,%74,%75,%76,%77,%78,%79,%80,%81,%82,%83,%84,%85,%86,%87,%88,%89,%90,%91,%92,%93,%94,%95}, {%96,%97,%98,%99}, %100, p, 1, 1, 0;}\n"
  : "+f"(d[0]),"+f"(d[1]),"+f"(d[2]),"+f"(d[3]),"+f"(d[4]),"+f"(d[5]),"+f"(d[6]),"+f"(d[7]),"+f"(d[8]),"+f"(d[9]),"+f"(d[10]),"+f"(d[11]),"+f"(d[12]),"+f"(d[13]),"+f"(d[14]),"+f"(d[15]),"+f"(d[16]),"+f"(d[17]),"+f"(d[18]),"+f"(d[19]),"+f"(d[20]),"+f"(d[21]),"+f"(d[22]),"+f"(d[23]),"+f"(d[24]),"+f"(d[25]),"+f"(d[26]),"+f"(d[27]),"+f"(d[28]),"+f"(d[29]),"+f"(d[30]),"+f"(d[31]),"+f"(d[32]),"+f"(d[33]),"+f"(d[34]),"+f"(d[35]),"+f"(d[36]),"+f"(d[37]),"+f"(d[38]),"+f"(d[39]),"+f"(d[40]),"+f"(d[41]),"+f"(d[42]),"+f"(d[43]),"+f"(d[44]),"+f"(d[45]),"+f"(d[46]),"+f"(d[47]),"+f"(d[48]),"+f"(d[49]),"+f"(d[50]),"+f"(d[51]),"+f"(d[52]),"+f"(d[53]),"+f"(d[54]),"+f"(d[55]),"+f"(d[56]),"+f"(d[57]),"+f"(d[58]),"+f"(d[59]),"+f"(d[60]),"+f"(d[61]),"+f"(d[62]),"+f"(d[63]),"+f"(d[64]),"+f"(d[65]),"+f"(d[66]),"+f"(d[67]),"+f"(d[68]),"+f"(d[69]),"+f"(d[70]),"+f"(d[71]),"+f"(d[72]),"+f"(d[73]),"+f"(d[74]),"+f"(d[75]),"+f"(d[76]),"+f"(d[77]),"+f"(d[78]),"+f"(d[79]),"+f"(d[80]),"+f"(d[81]),"+f"(d[82]),"+f"(d[83]),"+f"(d[84]),"+f"(d[85]),"+f"(d[86]),"+f"(d[87]),"+f"(d[88]),"+f"(d[89]),"+f"(d[90]),"+f"(d[91]),"+f"(d[92]),"+f"(d[93]),"+f"(d[94]),"+f"(d[95])
  : "r"(a[0]), "r"(a[1]), "r"(a[2]), "r"(a[3]), "l"(db), "r"(sc));
}
template<> __device__ __forceinline__ void wgmma_rs<208>(float* d, const uint32_t* a, uint64_t db, int sc) {
  asm volatile("{.reg .pred p; setp.ne.b32 p, %109, 0;\n"
  "wgmma.mma_async.sync.aligned.m64n208k16.f32.bf16.bf16 {%0,%1,%2,%3,%4,%5,%6,%7,%8,%9,%10,%11,%12,%13,%14,%15,%16,%17,%18,%19,%20,%21,%22,%23,%24,%25,%26,%27,%28,%29,%30,%31,%32,%33,%34,%35,%36,%37,%38,%39,%40,%41,%42,%43,%44,%45,%46,%47,%48,%49,%50,%51,%52,%53,%54,%55,%56,%57,%58,%59,%60,%61,%62,%63,%64,%65,%66,%67,%68,%69,%70,%71,%72,%73,%74,%75,%76,%77,%78,%79,%80,%81,%82,%83,%84,%85,%86,%87,%88,%89,%90,%91,%92,%93,%94,%95,%96,%97,%98,%99,%100,%101,%102,%103}, {%104,%105,%106,%107}, %108, p, 1, 1, 0;}\n"
  : "+f"(d[0]),"+f"(d[1]),"+f"(d[2]),"+f"(d[3]),"+f"(d[4]),"+f"(d[5]),"+f"(d[6]),"+f"(d[7]),"+f"(d[8]),"+f"(d[9]),"+f"(d[10]),"+f"(d[11]),"+f"(d[12]),"+f"(d[13]),"+f"(d[14]),"+f"(d[15]),"+f"(d[16]),"+f"(d[17]),"+f"(d[18]),"+f"(d[19]),"+f"(d[20]),"+f"(d[21]),"+f"(d[22]),"+f"(d[23]),"+f"(d[24]),"+f"(d[25]),"+f"(d[26]),"+f"(d[27]),"+f"(d[28]),"+f"(d[29]),"+f"(d[30]),"+f"(d[31]),"+f"(d[32]),"+f"(d[33]),"+f"(d[34]),"+f"(d[35]),"+f"(d[36]),"+f"(d[37]),"+f"(d[38]),"+f"(d[39]),"+f"(d[40]),"+f"(d[41]),"+f"(d[42]),"+f"(d[43]),"+f"(d[44]),"+f"(d[45]),"+f"(d[46]),"+f"(d[47]),"+f"(d[48]),"+f"(d[49]),"+f"(d[50]),"+f"(d[51]),"+f"(d[52]),"+f"(d[53]),"+f"(d[54]),"+f"(d[55]),"+f"(d[56]),"+f"(d[57]),"+f"(d[58]),"+f"(d[59]),"+f"(d[60]),"+f"(d[61]),"+f"(d[62]),"+f"(d[63]),"+f"(d[64]),"+f"(d[65]),"+f"(d[66]),"+f"(d[67]),"+f"(d[68]),"+f"(d[69]),"+f"(d[70]),"+f"(d[71]),"+f"(d[72]),"+f"(d[73]),"+f"(d[74]),"+f"(d[75]),"+f"(d[76]),"+f"(d[77]),"+f"(d[78]),"+f"(d[79]),"+f"(d[80]),"+f"(d[81]),"+f"(d[82]),"+f"(d[83]),"+f"(d[84]),"+f"(d[85]),"+f"(d[86]),"+f"(d[87]),"+f"(d[88]),"+f"(d[89]),"+f"(d[90]),"+f"(d[91]),"+f"(d[92]),"+f"(d[93]),"+f"(d[94]),"+f"(d[95]),"+f"(d[96]),"+f"(d[97]),"+f"(d[98]),"+f"(d[99]),"+f"(d[100]),"+f"(d[101]),"+f"(d[102]),"+f"(d[103])
  : "r"(a[0]), "r"(a[1]), "r"(a[2]), "r"(a[3]), "l"(db), "r"(sc));
}
template<> __device__ __forceinline__ void wgmma_rs<224>(float* d, const uint32_t* a, uint64_t db, int sc) {
  asm volatile("{.reg .pred p; setp.ne.b32 p, %117, 0;\n"
  "wgmma.mma_async.sync.aligned.m64n224k16.f32.bf16.bf16 {%0,%1,%2,%3,%4,%5,%6,%7,%8,%9,%10,%11,%12,%13,%14,%15,%16,%17,%18,%19,%20,%21,%22,%23,%24,%25,%26,%27,%28,%29,%30,%31,%32,%33,%34,%35,%36,%37,%38,%39,%40,%41,%42,%43,%44,%45,%46,%47,%48,%49,%50,%51,%52,%53,%54,%55,%56,%57,%58,%59,%60,%61,%62,%63,%64,%65,%66,%67,%68,%69,%70,%71,%72,%73,%74,%75,%76,%77,%78,%79,%80,%81,%82,%83,%84,%85,%86,%87,%88,%89,%90,%91,%92,%93,%94,%95,%96,%97,%98,%99,%100,%101,%102,%103,%104,%105,%106,%107,%108,%109,%110,%111}, {%112,%113,%114,%115}, %116, p, 1, 1, 0;}\n"
  : "+f"(d[0]),"+f"(d[1]),"+f"(d[2]),"+f"(d[3]),"+f"(d[4]),"+f"(d[5]),"+f"(d[6]),"+f"(d[7]),"+f"(d[8]),"+f"(d[9]),"+f"(d[10]),"+f"(d[11]),"+f"(d[12]),"+f"(d[13]),"+f"(d[14]),"+f"(d[15]),"+f"(d[16]),"+f"(d[17]),"+f"(d[18]),"+f"(d[19]),"+f"(d[20]),"+f"(d[21]),"+f"(d[22]),"+f"(d[23]),"+f"(d[24]),"+f"(d[25]),"+f"(d[26]),"+f"(d[27]),"+f"(d[28]),"+f"(d[29]),"+f"(d[30]),"+f"(d[31]),"+f"(d[32]),"+f"(d[33]),"+f"(d[34]),"+f"(d[35]),"+f"(d[36]),"+f"(d[37]),"+f"(d[38]),"+f"(d[39]),"+f"(d[40]),"+f"(d[41]),"+f"(d[42]),"+f"(d[43]),"+f"(d[44]),"+f"(d[45]),"+f"(d[46]),"+f"(d[47]),"+f"(d[48]),"+f"(d[49]),"+f"(d[50]),"+f"(d[51]),"+f"(d[52]),"+f"(d[53]),"+f"(d[54]),"+f"(d[55]),"+f"(d[56]),"+f"(d[57]),"+f"(d[58]),"+f"(d[59]),"+f"(d[60]),"+f"(d[61]),"+f"(d[62]),"+f"(d[63]),"+f"(d[64]),"+f"(d[65]),"+f"(d[66]),"+f"(d[67]),"+f"(d[68]),"+f"(d[69]),"+f"(d[70]),"+f"(d[71]),"+f"(d[72]),"+f"(d[73]),"+f"(d[74]),"+f"(d[75]),"+f"(d[76]),"+f"(d[77]),"+f"(d[78]),"+f"(d[79]),"+f"(d[80]),"+f"(d[81]),"+f"(d[82]),"+f"(d[83]),"+f"(d[84]),"+f"(d[85]),"+f"(d[86]),"+f"(d[87]),"+f"(d[88]),"+f"(d[89]),"+f"(d[90]),"+f"(d[91]),"+f"(d[92]),"+f"(d[93]),"+f"(d[94]),"+f"(d[95]),"+f"(d[96]),"+f"(d[97]),"+f"(d[98]),"+f"(d[99]),"+f"(d[100]),"+f"(d[101]),"+f"(d[102]),"+f"(d[103]),"+f"(d[104]),"+f"(d[105]),"+f"(d[106]),"+f"(d[107]),"+f"(d[108]),"+f"(d[109]),"+f"(d[110]),"+f"(d[111])
  : "r"(a[0]), "r"(a[1]), "r"(a[2]), "r"(a[3]), "l"(db), "r"(sc));
}
template<> __device__ __forceinline__ void wgmma_rs<240>(float* d, const uint32_t* a, uint64_t db, int sc) {
  asm volatile("{.reg .pred p; setp.ne.b32 p, %125, 0;\n"
  "wgmma.mma_async.sync.aligned.m64n240k16.f32.bf16.bf16 {%0,%1,%2,%3,%4,%5,%6,%7,%8,%9,%10,%11,%12,%13,%14,%15,%16,%17,%18,%19,%20,%21,%22,%23,%24,%25,%26,%27,%28,%29,%30,%31,%32,%33,%34,%35,%36,%37,%38,%39,%40,%41,%42,%43,%44,%45,%46,%47,%48,%49,%50,%51,%52,%53,%54,%55,%56,%57,%58,%59,%60,%61,%62,%63,%64,%65,%66,%67,%68,%69,%70,%71,%72,%73,%74,%75,%76,%77,%78,%79,%80,%81,%82,%83,%84,%85,%86,%87,%88,%89,%90,%91,%92,%93,%94,%95,%96,%97,%98,%99,%100,%101,%102,%103,%104,%105,%106,%107,%108,%109,%110,%111,%112,%113,%114,%115,%116,%117,%118,%119}, {%120,%121,%122,%123}, %124, p, 1, 1, 0;}\n"
  : "+f"(d[0]),"+f"(d[1]),"+f"(d[2]),"+f"(d[3]),"+f"(d[4]),"+f"(d[5]),"+f"(d[6]),"+f"(d[7]),"+f"(d[8]),"+f"(d[9]),"+f"(d[10]),"+f"(d[11]),"+f"(d[12]),"+f"(d[13]),"+f"(d[14]),"+f"(d[15]),"+f"(d[16]),"+f"(d[17]),"+f"(d[18]),"+f"(d[19]),"+f"(d[20]),"+f"(d[21]),"+f"(d[22]),"+f"(d[23]),"+f"(d[24]),"+f"(d[25]),"+f"(d[26]),"+f"(d[27]),"+f"(d[28]),"+f"(d[29]),"+f"(d[30]),"+f"(d[31]),"+f"(d[32]),"+f"(d[33]),"+f"(d[34]),"+f"(d[35]),"+f"(d[36]),"+f"(d[37]),"+f"(d[38]),"+f"(d[39]),"+f"(d[40]),"+f"(d[41]),"+f"(d[42]),"+f"(d[43]),"+f"(d[44]),"+f"(d[45]),"+f"(d[46]),"+f"(d[47]),"+f"(d[48]),"+f"(d[49]),"+f"(d[50]),"+f"(d[51]),"+f"(d[52]),"+f"(d[53]),"+f"(d[54]),"+f"(d[55]),"+f"(d[56]),"+f"(d[57]),"+f"(d[58]),"+f"(d[59]),"+f"(d[60]),"+f"(d[61]),"+f"(d[62]),"+f"(d[63]),"+f"(d[64]),"+f"(d[65]),"+f"(d[66]),"+f"(d[67]),"+f"(d[68]),"+f"(d[69]),"+f"(d[70]),"+f"(d[71]),"+f"(d[72]),"+f"(d[73]),"+f"(d[74]),"+f"(d[75]),"+f"(d[76]),"+f"(d[77]),"+f"(d[78]),"+f"(d[79]),"+f"(d[80]),"+f"(d[81]),"+f"(d[82]),"+f"(d[83]),"+f"(d[84]),"+f"(d[85]),"+f"(d[86]),"+f"(d[87]),"+f"(d[88]),"+f"(d[89]),"+f"(d[90]),"+f"(d[91]),"+f"(d[92]),"+f"(d[93]),"+f"(d[94]),"+f"(d[95]),"+f"(d[96]),"+f"(d[97]),"+f"(d[98]),"+f"(d[99]),"+f"(d[100]),"+f"(d[101]),"+f"(d[102]),"+f"(d[103]),"+f"(d[104]),"+f"(d[105]),"+f"(d[106]),"+f"(d[107]),"+f"(d[108]),"+f"(d[109]),"+f"(d[110]),"+f"(d[111]),"+f"(d[112]),"+f"(d[113]),"+f"(d[114]),"+f"(d[115]),"+f"(d[116]),"+f"(d[117]),"+f"(d[118]),"+f"(d[119])
  : "r"(a[0]), "r"(a[1]), "r"(a[2]), "r"(a[3]), "l"(db), "r"(sc));
}
template<> __device__ __forceinline__ void wgmma_rs<256>(float* d, const uint32_t* a, uint64_t db, int sc) {
  asm volatile("{.reg .pred p; setp.ne.b32 p, %133, 0;\n"
  "wgmma.mma_async.sync.aligned.m64n256k16.f32.bf16.bf16 {%0,%1,%2,%3,%4,%5,%6,%7,%8,%9,%10,%11,%12,%13,%14,%15,%16,%17,%18,%19,%20,%21,%22,%23,%24,%25,%26,%27,%28,%29,%30,%31,%32,%33,%34,%35,%36,%37,%38,%39,%40,%41,%42,%43,%44,%45,%46,%47,%48,%49,%50,%51,%52,%53,%54,%55,%56,%57,%58,%59,%60,%61,%62,%63,%64,%65,%66,%67,%68,%69,%70,%71,%72,%73,%74,%75,%76,%77,%78,%79,%80,%81,%82,%83,%84,%85,%86,%87,%88,%89,%90,%91,%92,%93,%94,%95,%96,%97,%98,%99,%100,%101,%102,%103,%104,%105,%106,%107,%108,%109,%110,%111,%112,%113,%114,%115,%116,%117,%118,%119,%120,%121,%122,%123,%124,%125,%126,%127}, {%128,%129,%130,%131}, %132, p, 1, 1, 0;}\n"
  : "+f"(d[0]),"+f"(d[1]),"+f"(d[2]),"+f"(d[3]),"+f"(d[4]),"+f"(d[5]),"+f"(d[6]),"+f"(d[7]),"+f"(d[8]),"+f"(d[9]),"+f"(d[10]),"+f"(d[11]),"+f"(d[12]),"+f"(d[13]),"+f"(d[14]),"+f"(d[15]),"+f"(d[16]),"+f"(d[17]),"+f"(d[18]),"+f"(d[19]),"+f"(d[20]),"+f"(d[21]),"+f"(d[22]),"+f"(d[23]),"+f"(d[24]),"+f"(d[25]),"+f"(d[26]),"+f"(d[27]),"+f"(d[28]),"+f"(d[29]),"+f"(d[30]),"+f"(d[31]),"+f"(d[32]),"+f"(d[33]),"+f"(d[34]),"+f"(d[35]),"+f"(d[36]),"+f"(d[37]),"+f"(d[38]),"+f"(d[39]),"+f"(d[40]),"+f"(d[41]),"+f"(d[42]),"+f"(d[43]),"+f"(d[44]),"+f"(d[45]),"+f"(d[46]),"+f"(d[47]),"+f"(d[48]),"+f"(d[49]),"+f"(d[50]),"+f"(d[51]),"+f"(d[52]),"+f"(d[53]),"+f"(d[54]),"+f"(d[55]),"+f"(d[56]),"+f"(d[57]),"+f"(d[58]),"+f"(d[59]),"+f"(d[60]),"+f"(d[61]),"+f"(d[62]),"+f"(d[63]),"+f"(d[64]),"+f"(d[65]),"+f"(d[66]),"+f"(d[67]),"+f"(d[68]),"+f"(d[69]),"+f"(d[70]),"+f"(d[71]),"+f"(d[72]),"+f"(d[73]),"+f"(d[74]),"+f"(d[75]),"+f"(d[76]),"+f"(d[77]),"+f"(d[78]),"+f"(d[79]),"+f"(d[80]),"+f"(d[81]),"+f"(d[82]),"+f"(d[83]),"+f"(d[84]),"+f"(d[85]),"+f"(d[86]),"+f"(d[87]),"+f"(d[88]),"+f"(d[89]),"+f"(d[90]),"+f"(d[91]),"+f"(d[92]),"+f"(d[93]),"+f"(d[94]),"+f"(d[95]),"+f"(d[96]),"+f"(d[97]),"+f"(d[98]),"+f"(d[99]),"+f"(d[100]),"+f"(d[101]),"+f"(d[102]),"+f"(d[103]),"+f"(d[104]),"+f"(d[105]),"+f"(d[106]),"+f"(d[107]),"+f"(d[108]),"+f"(d[109]),"+f"(d[110]),"+f"(d[111]),"+f"(d[112]),"+f"(d[113]),"+f"(d[114]),"+f"(d[115]),"+f"(d[116]),"+f"(d[117]),"+f"(d[118]),"+f"(d[119]),"+f"(d[120]),"+f"(d[121]),"+f"(d[122]),"+f"(d[123]),"+f"(d[124]),"+f"(d[125]),"+f"(d[126]),"+f"(d[127])
  : "r"(a[0]), "r"(a[1]), "r"(a[2]), "r"(a[3]), "l"(db), "r"(sc));
}
template<> __device__ __forceinline__ void wgmma_ss<128>(float* d, uint64_t da, uint64_t db, int sc) {
  asm volatile("{.reg .pred p; setp.ne.b32 p, %66, 0;\n"
  "wgmma.mma_async.sync.aligned.m64n128k16.f32.bf16.bf16 {%0,%1,%2,%3,%4,%5,%6,%7,%8,%9,%10,%11,%12,%13,%14,%15,%16,%17,%18,%19,%20,%21,%22,%23,%24,%25,%26,%27,%28,%29,%30,%31,%32,%33,%34,%35,%36,%37,%38,%39,%40,%41,%42,%43,%44,%45,%46,%47,%48,%49,%50,%51,%52,%53,%54,%55,%56,%57,%58,%59,%60,%61,%62,%63}, %64, %65, p, 1, 1, 0, 1;}\n"
  : "+f"(d[0]),"+f"(d[1]),"+f"(d[2]),"+f"(d[3]),"+f"(d[4]),"+f"(d[5]),"+f"(d[6]),"+f"(d[7]),"+f"(d[8]),"+f"(d[9]),"+f"(d[10]),"+f"(d[11]),"+f"(d[12]),"+f"(d[13]),"+f"(d[14]),"+f"(d[15]),"+f"(d[16]),"+f"(d[17]),"+f"(d[18]),"+f"(d[19]),"+f"(d[20]),"+f"(d[21]),"+f"(d[22]),"+f"(d[23]),"+f"(d[24]),"+f"(d[25]),"+f"(d[26]),"+f"(d[27]),"+f"(d[28]),"+f"(d[29]),"+f"(d[30]),"+f"(d[31]),"+f"(d[32]),"+f"(d[33]),"+f"(d[34]),"+f"(d[35]),"+f"(d[36]),"+f"(d[37]),"+f"(d[38]),"+f"(d[39]),"+f"(d[40]),"+f"(d[41]),"+f"(d[42]),"+f"(d[43]),"+f"(d[44]),"+f"(d[45]),"+f"(d[46]),"+f"(d[47]),"+f"(d[48]),"+f"(d[49]),"+f"(d[50]),"+f"(d[51]),"+f"(d[52]),"+f"(d[53]),"+f"(d[54]),"+f"(d[55]),"+f"(d[56]),"+f"(d[57]),"+f"(d[58]),"+f"(d[59]),"+f"(d[60]),"+f"(d[61]),"+f"(d[62]),"+f"(d[63])
  : "l"(da), "l"(db), "r"(sc));
}
template<> __device__ __forceinline__ void wgmma_ss<192>(float* d, uint64_t da, uint64_t db, int sc) {
  asm volatile("{.reg .pred p; setp.ne.b32 p, %98, 0;\n"
  "wgmma.mma_async.sync.aligned.m64n192k16.f32.bf16.bf16 {%0,%1,%2,%3,%4,%5,%6,%7,%8,%9,%10,%11,%12,%13,%14,%15,%16,%17,%18,%19,%20,%21,%22,%23,%24,%25,%26,%27,%28,%29,%30,%31,%32,%33,%34,%35,%36,%37,%38,%39,%40,%41,%42,%43,%44,%45,%46,%47,%48,%49,%50,%51,%52,%53,%54,%55,%56,%57,%58,%59,%60,%61,%62,%63,%64,%65,%66,%67,%68,%69,%70,%71,%72,%73,%74,%75,%76,%77,%78,%79,%80,%81,%82,%83,%84,%85,%86,%87,%88,%89,%90,%91,%92,%93,%94,%95}, %96, %97, p, 1, 1, 0, 1;}\n"
  : "+f"(d[0]),"+f"(d[1]),"+f"(d[2]),"+f"(d[3]),"+f"(d[4]),"+f"(d[5]),"+f"(d[6]),"+f"(d[7]),"+f"(d[8]),"+f"(d[9]),"+f"(d[10]),"+f"(d[11]),"+f"(d[12]),"+f"(d[13]),"+f"(d[14]),"+f"(d[15]),"+f"(d[16]),"+f"(d[17]),"+f"(d[18]),"+f"(d[19]),"+f"(d[20]),"+f"(d[21]),"+f"(d[22]),"+f"(d[23]),"+f"(d[24]),"+f"(d[25]),"+f"(d[26]),"+f"(d[27]),"+f"(d[28]),"+f"(d[29]),"+f"(d[30]),"+f"(d[31]),"+f"(d[32]),"+f"(d[33]),"+f"(d[34]),"+f"(d[35]),"+f"(d[36]),"+f"(d[37]),"+f"(d[38]),"+f"(d[39]),"+f"(d[40]),"+f"(d[41]),"+f"(d[42]),"+f"(d[43]),"+f"(d[44]),"+f"(d[45]),"+f"(d[46]),"+f"(d[47]),"+f"(d[48]),"+f"(d[49]),"+f"(d[50]),"+f"(d[51]),"+f"(d[52]),"+f"(d[53]),"+f"(d[54]),"+f"(d[55]),"+f"(d[56]),"+f"(d[57]),"+f"(d[58]),"+f"(d[59]),"+f"(d[60]),"+f"(d[61]),"+f"(d[62]),"+f"(d[63]),"+f"(d[64]),"+f"(d[65]),"+f"(d[66]),"+f"(d[67]),"+f"(d[68]),"+f"(d[69]),"+f"(d[70]),"+f"(d[71]),"+f"(d[72]),"+f"(d[73]),"+f"(d[74]),"+f"(d[75]),"+f"(d[76]),"+f"(d[77]),"+f"(d[78]),"+f"(d[79]),"+f"(d[80]),"+f"(d[81]),"+f"(d[82]),"+f"(d[83]),"+f"(d[84]),"+f"(d[85]),"+f"(d[86]),"+f"(d[87]),"+f"(d[88]),"+f"(d[89]),"+f"(d[90]),"+f"(d[91]),"+f"(d[92]),"+f"(d[93]),"+f"(d[94]),"+f"(d[95])
  : "l"(da), "l"(db), "r"(sc));
}
template<> __device__ __forceinline__ void wgmma_ss<256>(float* d, uint64_t da, uint64_t db, int sc) {
  asm volatile("{.reg .pred p; setp.ne.b32 p, %130, 0;\n"
  "wgmma.mma_async.sync.aligned.m64n256k16.f32.bf16.bf16 {%0,%1,%2,%3,%4,%5,%6,%7,%8,%9,%10,%11,%12,%13,%14,%15,%16,%17,%18,%19,%20,%21,%22,%23,%24,%25,%26,%27,%28,%29,%30,%31,%32,%33,%34,%35,%36,%37,%38,%39,%40,%41,%42,%43,%44,%45,%46,%47,%48,%49,%50,%51,%52,%53,%54,%55,%56,%57,%58,%59,%60,%61,%62,%63,%64,%65,%66,%67,%68,%69,%70,%71,%72,%73,%74,%75,%76,%77,%78,%79,%80,%81,%82,%83,%84,%85,%86,%87,%88,%89,%90,%91,%92,%93,%94,%95,%96,%97,%98,%99,%100,%101,%102,%103,%104,%105,%106,%107,%108,%109,%110,%111,%112,%113,%114,%115,%116,%117,%118,%119,%120,%121,%122,%123,%124,%125,%126,%127}, %128, %129, p, 1, 1, 0, 1;}\n"
  : "+f"(d[0]),"+f"(d[1]),"+f"(d[2]),"+f"(d[3]),"+f"(d[4]),"+f"(d[5]),"+f"(d[6]),"+f"(d[7]),"+f"(d[8]),"+f"(d[9]),"+f"(d[10]),"+f"(d[11]),"+f"(d[12]),"+f"(d[13]),"+f"(d[14]),"+f"(d[15]),"+f"(d[16]),"+f"(d[17]),"+f"(d[18]),"+f"(d[19]),"+f"(d[20]),"+f"(d[21]),"+f"(d[22]),"+f"(d[23]),"+f"(d[24]),"+f"(d[25]),"+f"(d[26]),"+f"(d[27]),"+f"(d[28]),"+f"(d[29]),"+f"(d[30]),"+f"(d[31]),"+f"(d[32]),"+f"(d[33]),"+f"(d[34]),"+f"(d[35]),"+f"(d[36]),"+f"(d[37]),"+f"(d[38]),"+f"(d[39]),"+f"(d[40]),"+f"(d[41]),"+f"(d[42]),"+f"(d[43]),"+f"(d[44]),"+f"(d[45]),"+f"(d[46]),"+f"(d[47]),"+f"(d[48]),"+f"(d[49]),"+f"(d[50]),"+f"(d[51]),"+f"(d[52]),"+f"(d[53]),"+f"(d[54]),"+f"(d[55]),"+f"(d[56]),"+f"(d[57]),"+f"(d[58]),"+f"(d[59]),"+f"(d[60]),"+f"(d[61]),"+f"(d[62]),"+f"(d[63]),"+f"(d[64]),"+f"(d[65]),"+f"(d[66]),"+f"(d[67]),"+f"(d[68]),"+f"(d[69]),"+f"(d[70]),"+f"(d[71]),"+f"(d[72]),"+f"(d[73]),"+f"(d[74]),"+f"(d[75]),"+f"(d[76]),"+f"(d[77]),"+f"(d[78]),"+f"(d[79]),"+f"(d[80]),"+f"(d[81]),"+f"(d[82]),"+f"(d[83]),"+f"(d[84]),"+f"(d[85]),"+f"(d[86]),"+f"(d[87]),"+f"(d[88]),"+f"(d[89]),"+f"(d[90]),"+f"(d[91]),"+f"(d[92]),"+f"(d[93]),"+f"(d[94]),"+f"(d[95]),"+f"(d[96]),"+f"(d[97]),"+f"(d[98]),"+f"(d[99]),"+f"(d[100]),"+f"(d[101]),"+f"(d[102]),"+f"(d[103]),"+f"(d[104]),"+f"(d[105]),"+f"(d[106]),"+f"(d[107]),"+f"(d[108]),"+f"(d[109]),"+f"(d[110]),"+f"(d[111]),"+f"(d[112]),"+f"(d[113]),"+f"(d[114]),"+f"(d[115]),"+f"(d[116]),"+f"(d[117]),"+f"(d[118]),"+f"(d[119]),"+f"(d[120]),"+f"(d[121]),"+f"(d[122]),"+f"(d[123]),"+f"(d[124]),"+f"(d[125]),"+f"(d[126]),"+f"(d[127])
  : "l"(da), "l"(db), "r"(sc));
}

__device__ __forceinline__ void wg_fence() { asm volatile("wgmma.fence.sync.aligned;" ::: "memory"); }
__device__ __forceinline__ void wg_commit() { asm volatile("wgmma.commit_group.sync.aligned;" ::: "memory"); }
template <int N> __device__ __forceinline__ void wg_wait() { asm volatile("wgmma.wait_group.sync.aligned %0;" ::"n"(N) : "memory"); }
__device__ __forceinline__ uint64_t mkdesc(uint32_t addr, uint32_t lbo, uint32_t sbo, uint32_t swz) {
  return (uint64_t)((addr & 0x3FFFF) >> 4) | ((uint64_t)(lbo >> 4) << 16) | ((uint64_t)(sbo >> 4) << 32) | ((uint64_t)swz << 62);
}
__device__ __forceinline__ void mbar_init(uint32_t a, uint32_t c) { asm volatile("mbarrier.init.shared.b64 [%0], %1;" ::"r"(a), "r"(c) : "memory"); }
__device__ __forceinline__ void mbar_expect_tx(uint32_t a, uint32_t b) { asm volatile("mbarrier.arrive.expect_tx.shared.b64 _, [%0], %1;" ::"r"(a), "r"(b) : "memory"); }
__device__ __forceinline__ void mbar_arrive(uint32_t a) { asm volatile("mbarrier.arrive.shared.b64 _, [%0];" ::"r"(a) : "memory"); }
__device__ __forceinline__ void mbar_arrive_c(uint32_t a, uint32_t n) { asm volatile("mbarrier.arrive.shared::cluster.b64 _, [%0], %1;" ::"r"(a), "r"(n) : "memory"); }
__device__ __forceinline__ void mbar_wait(uint32_t a, uint32_t parity) {
  asm volatile("{.reg .pred p, q; .reg .u32 n; mov.u32 n, 0;\n"
               "W: mbarrier.try_wait.parity.shared.b64 p, [%0], %1;\n"
               "add.u32 n, n, 1; setp.eq.u32 q, n, 0x100000; @q trap; @!p bra.uni W;}" ::"r"(a), "r"(parity) : "memory");
}
__device__ __forceinline__ uint32_t mapa(uint32_t a, uint32_t rank) { uint32_t r; asm("mapa.shared::cluster.u32 %0, %1, %2;" : "=r"(r) : "r"(a), "r"(rank)); return r; }
__device__ __forceinline__ void tma2d(uint32_t dst, const CUtensorMap* m, uint32_t bar, int c0, int c1) {
  asm volatile("cp.async.bulk.tensor.2d.shared::cluster.global.mbarrier::complete_tx::bytes [%0], [%1, {%3,%4}], [%2];"
               ::"r"(dst), "l"(m), "r"(bar), "r"(c0), "r"(c1) : "memory");
}
__device__ __forceinline__ void tma2d_mc(uint32_t dst, const CUtensorMap* m, uint32_t bar, int c0, int c1) {
  asm volatile("cp.async.bulk.tensor.2d.shared::cluster.global.mbarrier::complete_tx::bytes.multicast::cluster [%0], [%1, {%3,%4}], [%2], %5;"
               ::"r"(dst), "l"(m), "r"(bar), "r"(c0), "r"(c1), "h"((uint16_t)3) : "memory");
}
__device__ __forceinline__ void tma3d(uint32_t dst, const CUtensorMap* m, uint32_t bar, int c0, int c1, int c2) {
  asm volatile("cp.async.bulk.tensor.3d.shared::cluster.global.mbarrier::complete_tx::bytes [%0], [%1, {%3,%4,%5}], [%2];"
               ::"r"(dst), "l"(m), "r"(bar), "r"(c0), "r"(c1), "r"(c2) : "memory");
}
__device__ __forceinline__ void tma3d_mc(uint32_t dst, const CUtensorMap* m, uint32_t bar, int c0, int c1, int c2) {
  asm volatile("cp.async.bulk.tensor.3d.shared::cluster.global.mbarrier::complete_tx::bytes.multicast::cluster [%0], [%1, {%3,%4,%5}], [%2], %6;"
               ::"r"(dst), "l"(m), "r"(bar), "r"(c0), "r"(c1), "r"(c2), "h"((uint16_t)3) : "memory");
}
__device__ __forceinline__ void tma_store(const CUtensorMap* m, uint32_t src, int c0, int c1) {
  asm volatile("cp.async.bulk.tensor.2d.global.shared::cta.bulk_group [%0, {%2,%3}], [%1];" ::"l"(m), "r"(src), "r"(c0), "r"(c1) : "memory");
}
__device__ __forceinline__ void bulk_commit() { asm volatile("cp.async.bulk.commit_group;" ::: "memory"); }
__device__ __forceinline__ void bulk_wait_read() { asm volatile("cp.async.bulk.wait_group.read 0;" ::: "memory"); }
__device__ __forceinline__ void bulk_wait() { asm volatile("cp.async.bulk.wait_group 0;" ::: "memory"); }
__device__ __forceinline__ void bulk_g2s(uint32_t dst, const void* src, uint32_t bytes, uint32_t bar) {
  asm volatile("cp.async.bulk.shared::cluster.global.mbarrier::complete_tx::bytes [%0], [%1], %2, [%3];"
               ::"r"(dst), "l"(src), "r"(bytes), "r"(bar) : "memory");
}
__device__ __forceinline__ void prefetch_l2(const void* src, uint32_t bytes) {
  asm volatile("cp.async.bulk.prefetch.L2.global [%0], %1;" ::"l"(src), "r"(bytes) : "memory");
}
__device__ __forceinline__ void prefetch_tmap(const CUtensorMap* m) { asm volatile("prefetch.tensormap [%0];" ::"l"(m) : "memory"); }
__device__ __forceinline__ void fence_async_smem() { asm volatile("fence.proxy.async.shared::cta;" ::: "memory"); }
__device__ __forceinline__ void fence_async_global() { asm volatile("fence.proxy.async.global;" ::: "memory"); }
__device__ __forceinline__ void bar_sync(int id, int n) { asm volatile("bar.sync %0, %1;" ::"r"(id), "r"(n) : "memory"); }
__device__ __forceinline__ void cluster_wait() { asm volatile("barrier.cluster.wait.aligned;" ::: "memory"); }
__device__ __forceinline__ uint32_t lds32(uint32_t a) { uint32_t v; asm volatile("ld.volatile.shared.b32 %0,[%1];" : "=r"(v) : "r"(a)); return v; }
__device__ __forceinline__ uint2 lds64(uint32_t a) { uint2 v; asm volatile("ld.shared.v2.b32 {%0,%1},[%2];" : "=r"(v.x), "=r"(v.y) : "r"(a) : "memory"); return v; }
__device__ __forceinline__ uint4 lds128(uint32_t a) { uint4 v; asm volatile("ld.shared.v4.b32 {%0,%1,%2,%3},[%4];" : "=r"(v.x), "=r"(v.y), "=r"(v.z), "=r"(v.w) : "r"(a) : "memory"); return v; }
__device__ __forceinline__ void sts128(uint32_t a, uint32_t x, uint32_t y, uint32_t z, uint32_t w) { asm volatile("st.shared.v4.b32 [%0],{%1,%2,%3,%4};" ::"r"(a), "r"(x), "r"(y), "r"(z), "r"(w) : "memory"); }
__device__ __forceinline__ void stsm4(uint32_t a, uint32_t x, uint32_t y, uint32_t z, uint32_t w) { asm volatile("stmatrix.sync.aligned.m8n8.x4.shared.b16 [%0],{%1,%2,%3,%4};" ::"r"(a), "r"(x), "r"(y), "r"(z), "r"(w) : "memory"); }
__device__ __forceinline__ uint32_t packbf(float lo, float hi) { uint32_t r; asm("cvt.rn.bf16x2.f32 %0, %1, %2;" : "=r"(r) : "f"(hi), "f"(lo)); return r; }
__device__ __forceinline__ uint32_t packbf_relu(float lo, float hi) { uint32_t r; asm("cvt.rn.relu.bf16x2.f32 %0, %1, %2;" : "=r"(r) : "f"(hi), "f"(lo)); return r; }
__device__ __forceinline__ uint32_t bmul2(uint32_t a, uint32_t b) { uint32_t r; asm("mul.rn.bf16x2 %0, %1, %2;" : "=r"(r) : "r"(a), "r"(b)); return r; }
__device__ __forceinline__ uint32_t bfma2(uint32_t a, uint32_t b, uint32_t c) { uint32_t r; asm("fma.rn.bf16x2 %0, %1, %2, %3;" : "=r"(r) : "r"(a), "r"(b), "r"(c)); return r; }
__device__ __forceinline__ uint32_t badd2(uint32_t a, uint32_t b) { uint32_t r; asm("add.rn.bf16x2 %0, %1, %2;" : "=r"(r) : "r"(a), "r"(b)); return r; }
__device__ __forceinline__ uint32_t bsub2(uint32_t a, uint32_t b) { uint32_t r; asm("sub.rn.bf16x2 %0, %1, %2;" : "=r"(r) : "r"(a), "r"(b)); return r; }
__device__ __forceinline__ float bflo(uint32_t v) { return __uint_as_float(v << 16); }
__device__ __forceinline__ float bfhi(uint32_t v) { return __uint_as_float(v & 0xffff0000u); }
__device__ __forceinline__ uint32_t ldg_relaxed(const uint32_t* p) { uint32_t v; asm volatile("ld.relaxed.gpu.global.b32 %0,[%1];" : "=r"(v) : "l"(p) : "memory"); return v; }
__device__ __forceinline__ uint4 ldg_b128(const void* p) {
  uint4 v;
  asm volatile("{.reg .b128 r; .reg .b64 a, b; ld.relaxed.gpu.global.b128 r, [%4]; mov.b128 {a, b}, r; mov.b64 {%0,%1}, a; mov.b64 {%2,%3}, b;}"
               : "=r"(v.x), "=r"(v.y), "=r"(v.z), "=r"(v.w) : "l"(p) : "memory");
  return v;
}
__device__ __forceinline__ void stg_b128(void* p, uint32_t x, uint32_t y, uint32_t z, uint32_t w) {
  asm volatile("{.reg .b128 r; .reg .b64 a, b; mov.b64 a, {%1,%2}; mov.b64 b, {%3,%4}; mov.b128 r, {a, b}; st.relaxed.gpu.global.b128 [%0], r;}"
               ::"l"(p), "r"(x), "r"(y), "r"(z), "r"(w) : "memory");
}
__device__ __forceinline__ uint4 ldg_cg4(const void* p) { uint4 v; asm volatile("ld.global.cg.v4.b32 {%0,%1,%2,%3},[%4];" : "=r"(v.x), "=r"(v.y), "=r"(v.z), "=r"(v.w) : "l"(p) : "memory"); return v; }
__device__ __forceinline__ float2 ldg_cg2f(const void* p) { float2 v; asm volatile("ld.global.cg.v2.f32 {%0,%1},[%2];" : "=f"(v.x), "=f"(v.y) : "l"(p) : "memory"); return v; }
__device__ __forceinline__ void stg128(void* p, uint32_t x, uint32_t y, uint32_t z, uint32_t w) { asm volatile("st.global.v4.b32 [%0],{%1,%2,%3,%4};" ::"l"(p), "r"(x), "r"(y), "r"(z), "r"(w) : "memory"); }
__device__ __forceinline__ void signal(uint32_t* cnt) { asm volatile("red.release.gpu.global.add.u32 [%0], 1;" ::"l"(cnt) : "memory"); }
__device__ __forceinline__ void wait_count(const uint32_t* cnt, uint32_t target) {
  int it = 0;
  while (true) {
    uint32_t v;
    asm volatile("ld.acquire.gpu.global.b32 %0,[%1];" : "=r"(v) : "l"(cnt) : "memory");
    if ((int)(v - target) >= 0) break;
    __nanosleep(32);
    if (++it > (1 << 21)) __trap();
  }
}

template <int LO, int HI> __device__ __forceinline__ void rename(float* d) {
#pragma unroll
  for (int i = LO; i < HI; i++) { float e; asm volatile("mov.b32 %0, %1;" : "=f"(e) : "f"(d[i])); d[i] = e; }
}
template <int M> __device__ __forceinline__ void drain4(const float* d, uint32_t ya, uint32_t ybar, bool lane0) {
  uint32_t r[4];
#pragma unroll
  for (int q = 0; q < 4; q++) {
    const int mu = M + q;
    float v0 = d[4 * mu], v1 = d[4 * mu + 1];
    if (mu > 0) { v0 += d[4 * mu - 2]; v1 += d[4 * mu - 1]; }
    r[q] = packbf(v0, v1);
  }
  asm volatile("stmatrix.sync.aligned.m8n8.x4.trans.shared.b16 [%0],{%1,%2,%3,%4};" ::"r"(ya + M * 128), "r"(r[0]), "r"(r[1]), "r"(r[2]), "r"(r[3]) : "memory");
  if constexpr ((M & 7) == 4) {
    __syncwarp();
    if (lane0) mbar_arrive(ybar + (M >> 3) * 8);
  }
}
__device__ __forceinline__ void lda(uint32_t* a, uint32_t ua) { a[0] = lds32(ua); a[1] = lds32(ua + 128); a[2] = lds32(ua - 16); a[3] = lds32(ua + 112); }
template <int P, bool FIRST> struct Pass {
  static __device__ __forceinline__ void run(float* d, uint32_t (*a)[4], uint32_t ua, uint64_t db, uint32_t ya, uint32_t ubar, uint32_t ybar, bool lane0) {
    if constexpr (P > 0) rename<8 * (P - 1), 128>(d);
    wg_fence();
    wgmma_rs<256 - 16 * P>(d + 8 * P, a[P & 1], db, P != 0);
    wg_commit();
    if constexpr (P < 15) {
      if constexpr (FIRST && (P & 1)) mbar_wait(ubar + 8 * ((P + 1) / 2), 0);
      lda(a[(P + 1) & 1], ua + (P + 1) * 256);
    }
    if constexpr (P >= 3 && (P & 1)) drain4<2 * P - 6>(d, ya, ybar, lane0);
    wg_wait<0>();
    if constexpr (P < 15) Pass<P + 1, FIRST>::run(d, a, ua, db, ya, ubar, ybar, lane0);
    else { rename<120, 128>(d); drain4<28>(d, ya, ybar, lane0); }
  }
};

__device__ __forceinline__ uint32_t off_T(int r) { return r == 0 ? OFF_T0 : r == 1 ? OFF_T1 : r == 2 ? OFF_T2 : OFF_T3; }
__device__ __forceinline__ uint32_t off_Y(int r) { return r == 1 ? OFF_KVA : r == 2 ? OFF_KVB : OFF_X; }
__device__ __forceinline__ uint32_t off_kv(int st) {
  const int sl = st < 5 ? st : st - 5;
  return sl == 0 ? 0 : sl < 3 ? OFF_KVA + (sl - 1) * KV_SLOT : OFF_KVB + (sl - 3) * KV_SLOT;
}
template <bool FIRST>
__device__ __forceinline__ void conv_round(uint32_t sb, int r, int wg, int w, int lane) {
  float d[128];
  uint32_t a[2][4];
  const int g = lane >> 2, t = lane & 3;
  const uint32_t bar = sb + OFF_BAR, tb = sb + off_T(r);
  const uint32_t ua = tb + wg * UT_SIZE + ((g & 1) ? 0 : UT_COPY) + ((g >> 1) + 8 * w + 8 - t) * 4;
  const uint64_t db = mkdesc(tb + 2 * UT_SIZE + wg * KT_SIZE, 16, 128, 0);
  const uint32_t yb = sb + off_Y(r) + wg * YBUF + w * YW;
  mbar_wait(bar + 8 * (FIRST ? B_UFULL : r == 3 ? B_ZDONE : B_UREST), 0);
  lda(a[0], ua);
  if (lane < 2 * w) sts128(yb + lane * 16, 0, 0, 0, 0);
  mbar_wait(bar + 8 * (B_KFULL + 2 * r + wg), 0);
  if (threadIdx.x == 0) TS(1 + r);
  Pass<0, FIRST>::run(d, a, ua, db, yb + (2 * w + lane) * 16, bar + 8 * B_UFULL, bar + 8 * (B_YFULL + 4 * r), lane == 0);
}
__device__ __forceinline__ uint32_t off_act(int tile, int wg, int b) {
  return b < 2 ? OFF_X + wg * 16384 + b * 8192 : tile == 0 ? (2 * wg + b - 2) * 49152 + 40960 : 180224 + wg * 8192;
}

template <int NT>
__device__ __forceinline__ void gemm1_main(float* out, uint32_t sb, int wg, uint32_t ebar, bool rel, uint32_t hs, bool t3) {
  const uint32_t bar = sb + OFF_BAR;
  float acc[NT / 2];
  const uint64_t da0 = mkdesc(sb + wg * 8192, 16, 1024, 1), db0 = mkdesc(sb + 16384, 8192, 1024, 1);
  mbar_wait(bar + 8 * B_FULL1, 0);
  wg_fence();
#pragma unroll
  for (int kk = 0; kk < 4; kk++) wgmma_ss<NT>(acc, da0 + kk * 2, db0 + kk * 128, kk != 0);
  wg_commit();
#pragma unroll 1
  for (int kb = 1; kb < 16; kb++) {
    const int s = kb & 3;
    mbar_wait(bar + 8 * (B_FULL1 + s), (kb >> 2) & 1);
    const uint64_t da = da0 + s * 3072, db = db0 + s * 3072;
    wg_fence();
#pragma unroll
    for (int kk = 0; kk < 4; kk++) wgmma_ss<NT>(acc, da + kk * 2, db + kk * 128, 1);
    wg_commit();
    wg_wait<1>();
    if (rel) mbar_arrive_c(ebar + 8 * (B_EMPTY1 + ((kb - 1) & 3)), 1);
  }
  mbar_wait(bar + 8 * B_CSFULL, NT == 256 ? 0 : 1);
  uint32_t a[4] = {lds32(hs), lds32(hs + 128), 0, 0};
  if (t3) a[0] = a[1] = 0;
  wg_fence();
  wgmma_rs<NT>(acc, a, mkdesc(sb + OFF_X + wg * 16384, 0, 128, 0), 1);
  wg_commit();
  wg_wait<0>();
#pragma unroll
  for (int i = 0; i < NT / 2; i++) asm volatile("mov.b32 %0, %1;" : "=f"(out[i]) : "f"(acc[i]));
  if (rel) mbar_arrive_c(ebar + 8 * (B_EMPTY1 + 3), 1);
}

__global__ void __cluster_dims__(2, 1, 1) __launch_bounds__(NTHREADS, 1) fused_kernel(const __grid_constant__ Params P) {
  extern __shared__ __align__(1024) unsigned char smem[];
  const uint32_t sb = (uint32_t)__cvta_generic_to_shared(smem);
  const uint32_t bar = sb + OFF_BAR;
  const int tid = threadIdx.x, warp = __shfl_sync(0xffffffffu, tid >> 5, 0), lane = tid & 31;
  const int c = blockIdx.x, m = c & 15, j = c >> 4, rank = c & 1;

  if (lane == 0) {
    if (warp == 8) {
      TS(0);
      mbar_init(bar + 8 * B_KVFULL, 1); mbar_init(bar + 8 * B_KFULL, 2); mbar_init(bar + 8 * (B_KFULL + 1), 2);
      mbar_expect_tx(bar + 8 * B_KVFULL, KV_SLOT);
#pragma unroll 1
      for (int i = 0; i < 2; i++) {
        tma3d(sb + i * KV_BOX, &P.tm_k, bar + 8 * B_KVFULL, 8 * (c & ~1), 16 * i - 1, 0);
        tma3d(sb + (2 + i) * KV_BOX, &P.tm_v, bar + 8 * B_KVFULL, 8 * (c & ~1), 16 * i - 1, 0);
      }
#pragma unroll 1
      for (int i = 0; i < 2; i++) {
        mbar_expect_tx(bar + 8 * (B_KFULL + i), 4080);
        bulk_g2s(sb + OFF_T0 + 2 * UT_SIZE + i * KT_SIZE + 32, P.ssm_k + (size_t)(8 * c + i) * S + 8, 4080, bar + 8 * (B_KFULL + i));
      }
    } else if (warp < 8) {
      const uint32_t cnt = (0x84411881u >> (4 * warp)) & 15;
#pragma unroll
      for (int i = 0; i < 8; i++) mbar_init(bar + 8 * (16 + 8 * warp + i), cnt);
    } else if (warp == 9) {
#pragma unroll
      for (int i = 1; i < 8; i++) { mbar_init(bar + 8 * (B_KVFULL + i), 1); mbar_expect_tx(bar + 8 * (B_KVFULL + i), KV_SLOT); }
    } else if (warp == 10) {
#pragma unroll
      for (int i = 2; i < 8; i++) mbar_init(bar + 8 * (B_KFULL + i), 2);
    }
    asm volatile("fence.mbarrier_init.release.cluster;" ::: "memory");
  }
  if (warp == 11 && lane < 16) sts128(sb + off_T(lane >> 2) + (lane & 3) * UT_COPY, 0, 0, 0, 0);
  __syncthreads();
  asm volatile("barrier.cluster.arrive.relaxed.aligned;" ::: "memory");

  if (warp < 8) {
    if (tid == 32) TS(46);
    if (warp == 0 && lane < 8) {
      const uint4 v = __ldg((const uint4*)(P.ssm_k + (size_t)(8 * c + lane) * S));
      const float k0 = bflo(v.x) + __bfloat162float(P.ssm_D[8 * c + lane]);
      const uint32_t kt = sb + off_T(lane >> 1) + 2 * UT_SIZE + (lane & 1) * KT_SIZE;
      sts128(kt, 0, 0, 0, 0);
      sts128(kt + 16, (v.x & 0xffff0000u) | (packbf(k0, 0.f) & 0xffffu), v.y, v.z, v.w);
      fence_async_smem();
      mbar_arrive(bar + 8 * (B_KFULL + lane));
    }
    __syncwarp();
    cluster_wait();
    const int wg = warp >> 2, w = warp & 3, g = lane >> 2, t = lane & 3;
    conv_round<true>(sb, 0, wg, w, lane);
#pragma unroll 1
    for (int r = 1; r < 4; r++) conv_round<false>(sb, r, wg, w, lane);
    if (tid == 0) TS(5);
    const bool rel = lane == 0 && w < 2;
    const uint32_t ebar = mapa(bar, w & 1);
    const int id = lane >> 3, srow = 16 * w + (lane & 7) + 8 * (id & 1);
    const uint32_t soff = srow * 128, sx = ((id >> 1) ^ (srow & 7)) << 4;
    const uint32_t hs = sb + OFF_HS + (64 * wg + 16 * w + g) * 16;
#pragma unroll 1
    for (int tile = 0; tile < 2; tile++) {
      float acc[128];
      if (tile == 0) {
        gemm1_main<256>(acc, sb, wg, ebar, rel, hs + 4 * t, t == 3);
      } else {
        gemm1_main<192>(acc, sb, wg, ebar, rel, hs + 4 * t, t == 3);
#pragma unroll
        for (int i = 96; i < 128; i++) asm volatile("mov.b32 %0, 0;" : "=f"(acc[i]));
      }
      if (tid == 0) TS(44 + tile);
#pragma unroll
      for (int b = 0; b < 4; b++) {
        if (b == 3 && tile) break;
        if (b == 2) mbar_wait(bar + 8 * (B_EMPTY1 + 3), 0);
        const uint32_t dst = sb + off_act(tile, wg, b) + soff;
#pragma unroll
        for (int p = 0; p < 4; p++) {
          uint32_t o[4];
#pragma unroll
          for (int e = 0; e < 4; e++) {
            const uint32_t u = packbf_relu(acc[32 * b + 8 * p + 2 * e], acc[32 * b + 8 * p + 2 * e + 1]);
            o[e] = bmul2(u, u);
          }
          stsm4(dst + (sx ^ (p << 5)), o[0], o[1], o[2], o[3]);
        }
      }
      fence_async_smem();
      __syncwarp();
      if (lane == 0) mbar_arrive(bar + 8 * (B_ADONE + tile));
      if (tid == 0) TS(6 + tile);
    }
    {
      float acc[64], res[64];
      const uint64_t da0 = mkdesc(sb + wg * 8192, 16, 1024, 1), db0 = mkdesc(sb + 16384, 8192, 1024, 1);
      int s = 0, ph = 0, prev = 0;
#pragma unroll 1
      for (int kb = 0; kb < 56; kb++) {
        mbar_wait(bar + 8 * (B_FULL2 + s), ph);
        const uint64_t da = da0 + s * 2048, db = db0 + s * 2048;
        wg_fence();
#pragma unroll
        for (int kk = 0; kk < 4; kk++) wgmma_ss<128>(acc, da + kk * 2, db + kk * 128, (kb | kk) != 0);
        wg_commit();
        if (kb == 40) {
          const uint32_t* b2p = (const uint32_t*)(P.b2 + 128 * j) + t;
          uint32_t bv[16];
#pragma unroll
          for (int mu = 0; mu < 16; mu++) bv[mu] = __ldg(b2p + 4 * mu);
          mbar_wait(bar + 8 * B_HRES, 0);
#pragma unroll
          for (int h = 0; h < 2; h++) {
            const int row = 64 * wg + 16 * w + 8 * h + g;
            const uint32_t la = sb + OFF_X + row * 256 + t * 64;
            const int sw = (2 * row + (t >> 1)) & 3;
#pragma unroll
            for (int cc = 0; cc < 4; cc++) {
              const uint4 v = lds128(la + ((cc ^ sw) << 4));
              const uint32_t vv[4] = {v.x, v.y, v.z, v.w};
#pragma unroll
              for (int q = 0; q < 4; q++) {
                const int mu = 4 * cc + q;
                const uint32_t hb = badd2(vv[q], bv[mu]);
                res[4 * mu + 2 * h] = bflo(hb);
                res[4 * mu + 2 * h + 1] = bfhi(hb);
              }
            }
          }
        }
        wg_wait<1>();
        if (rel && kb > 0 && kb <= 50) mbar_arrive_c(ebar + 8 * (B_EMPTY2 + prev), 1);
        prev = s;
        if (++s == 6) { s = 0; ph ^= 1; }
      }
      const float sc0 = __uint_as_float(lds32(hs + 12)), sc1 = __uint_as_float(lds32(hs + 140));
      wg_wait<0>();
      rename<0, 64>(acc);
      if (tid == 0) TS(8);
      const uint32_t ob = sb + OFF_X + wg * 16384;
#pragma unroll
      for (int mu = 0; mu < 16; mu += 2) {
        const float* a = acc + 4 * mu;
        const float* q = res + 4 * mu;
        stsm4(ob + (mu >> 3) * 8192 + soff + (sx ^ ((mu & 6) << 4)),
              packbf(fmaf(a[0], sc0, q[0]), fmaf(a[1], sc0, q[1])), packbf(fmaf(a[2], sc1, q[2]), fmaf(a[3], sc1, q[3])),
              packbf(fmaf(a[4], sc0, q[4]), fmaf(a[5], sc0, q[5])), packbf(fmaf(a[6], sc1, q[6]), fmaf(a[7], sc1, q[7])));
      }
      fence_async_smem();
      bar_sync(3 + wg, 128);
      if (w == 0 && lane == 0) {
        tma_store(&P.tm_out, ob, 128 * j, 128 * m + 64 * wg);
        tma_store(&P.tm_out, ob + 8192, 128 * j + 64, 128 * m + 64 * wg);
        bulk_commit();
        bulk_wait_read();
        if (tid == 0) TS(9);
      }
    }
  } else if (warp == 8) {
    cluster_wait();
    if (lane == 0) {
#pragma unroll 1
      for (int i = 1; i < 8; i++) {
        if (i >= 5) mbar_wait(bar + 8 * (B_KVFREE + i - 5), 0);
        const uint32_t dst = sb + off_kv(i) + rank * KV_BOX;
        tma3d_mc(dst, &P.tm_k, bar + 8 * (B_KVFULL + i), 8 * (c & ~1), 32 * i + 16 * rank - 1, 0);
        tma3d_mc(dst + 2 * KV_BOX, &P.tm_v, bar + 8 * (B_KVFULL + i), 8 * (c & ~1), 32 * i + 16 * rank - 1, 0);
      }
      const uint32_t epoch = ldg_relaxed(g_epoch + c) + 1;
      const uint32_t bar0 = mapa(bar, 0), bar1 = mapa(bar, 1);
#pragma unroll 1
      for (int ch = 2; ch < 8; ch++) {
        if (ch == 4) prefetch_l2(P.x + (size_t)(128 * m + 16 * j) * D, 16 * D * 2);
        mbar_expect_tx(bar + 8 * (B_KFULL + ch), 4080);
        bulk_g2s(sb + off_T(ch >> 1) + 2 * UT_SIZE + (ch & 1) * KT_SIZE + 32, P.ssm_k + (size_t)(8 * c + ch) * S + 8, 4080, bar + 8 * (B_KFULL + ch));
      }
      prefetch_tmap(&P.tm_h); prefetch_tmap(&P.tm_w1); prefetch_tmap(&P.tm_act); prefetch_tmap(&P.tm_w2);
      prefetch_tmap(&P.tm_actst); prefetch_tmap(&P.tm_hres); prefetch_tmap(&P.tm_out);
      mbar_wait(bar + 8 * (B_KFULL + 7), 0);
      TS(31);
      prefetch_l2(P.w1 + (size_t)c * 8 * F, 8 * F * 2);
#pragma unroll 1
      for (int it = 0; it < 32; it++) {
        const int s = it & 3, kb = it & 15, tile = it >> 4;
        if (it < 4) {
          mbar_wait(bar + 8 * (it < 2 ? B_ZDONE + 1 : it == 2 ? B_ZDONE + 2 : B_YFULL + 15), 0);
          fence_async_smem();
          mbar_arrive_c(bar0 + 8 * (B_EMPTY1 + s), 2);
          mbar_arrive_c(bar1 + 8 * (B_EMPTY1 + s), 2);
        }
        mbar_wait(bar + 8 * (B_EMPTY1 + s), (it >> 2) & 1);
        const uint32_t sa = sb + s * 49152, fb = bar + 8 * (B_FULL1 + s);
        const int nb = tile ? 3 : 4, n0 = 448 * j + 256 * tile;
        mbar_expect_tx(fb, 16384 + nb * 8192);
#pragma unroll 1
        for (int i = 0; i < nb; i++) tma3d_mc(sa + 16384 + i * 8192 + rank * 4096, &P.tm_w1, fb, n0 + 64 * i, 2 * (kb >> 2), 32 * (kb & 3) + 16 * rank);
        if (it < 16 && (it & 3) == 0) { wait_count(g_hcnt + ((it >> 2) * 16 + m) * 32, epoch * 16); fence_async_global(); TS(11 + (it >> 2)); }
        tma2d(sa, &P.tm_h, fb, 64 * kb, 128 * m);
        if (it == 8) prefetch_l2(P.w2 + (size_t)c * 28 * D, 28 * D * 2);
      }
      int s = 0, ph = 0;
#pragma unroll 1
      for (int kb = 0; kb < 56; kb++) {
        if (kb < 6) mbar_wait(bar + 8 * (B_EMPTY1 + (2 * kb + 1) / 3), 0);
        mbar_wait(bar + 8 * (B_EMPTY2 + s), ph);
        const int col = kb < 32 ? 448 * (kb >> 2) + 64 * (kb & 3) : 448 * ((kb - 32) / 3) + 256 + 64 * ((kb - 32) % 3);
        const uint32_t sa = sb + s * 32768, fb = bar + 8 * (B_FULL2 + s);
        mbar_expect_tx(fb, 32768);
        tma2d_mc(sa + 16384 + rank * 8192, &P.tm_w2, fb, 128 * j + 64 * rank, col);
        if ((kb & 31) == 0) { wait_count(g_acnt + ((kb >> 5) * 16 + m) * 32, epoch * 8); fence_async_global(); TS(15 + (kb >> 5)); }
        tma2d(sa, &P.tm_act, fb, col, 128 * m);
        if (++s == 6) { s = 0; ph ^= 1; }
      }
    }
  } else {
    const int zw = warp - 9;
    {
      uint32_t W[4][4];
      const uint4* wp = (const uint4*)(P.shift_k + (size_t)32 * c);
#pragma unroll
      for (int p = 0; p < 4; p++) {
        const uint4 v = __ldg(wp + p);
        W[0][p] = __byte_perm(v.x, v.z, 0x5410); W[1][p] = __byte_perm(v.x, v.z, 0x7632);
        W[2][p] = __byte_perm(v.y, v.w, 0x5410); W[3][p] = __byte_perm(v.y, v.w, 0x7632);
      }
      cluster_wait();
#pragma unroll 1
      for (int st = zw; st < 8; st += 3) {
        mbar_wait(bar + 8 * (B_KVFULL + st), 0);
        if (lane == 0) TS(48 + st);
        const uint32_t ka = sb + off_kv(st) + (lane >> 4) * KV_BOX + (lane & 15) * 32 + rank * 16;
        uint32_t k[12][4], v[9][4];
#pragma unroll
        for (int i = 0; i < 12; i++) {
          const uint32_t o = i < 4 ? (4 + i) * 544 : (i - 4) * 544 + 32;
          const uint4 a = lds128(ka + o);
          k[i][0] = a.x; k[i][1] = a.y; k[i][2] = a.z; k[i][3] = a.w;
          if (i >= 3) {
            const uint4 b = lds128(ka + 2 * KV_BOX + o);
            v[i - 3][0] = b.x; v[i - 3][1] = b.y; v[i - 3][2] = b.z; v[i - 3][3] = b.w;
          }
        }
#pragma unroll
        for (int p = 0; p < 4; p++) {
          uint32_t u[9];
#pragma unroll
          for (int i = 0; i < 9; i++)
            u[i] = bmul2(bfma2(k[i + 3][p], W[0][p], bfma2(k[i + 2][p], W[1][p], bfma2(k[i + 1][p], W[2][p], bmul2(k[i][p], W[3][p])))), v[i][p]);
          const uint32_t ta = sb + off_T(p) + 16 + (32 * st + lane) * 16;
#pragma unroll
          for (int e = 0; e < 2; e++) {
            const uint32_t sel = e ? 0x7632 : 0x5410;
            sts128(ta + e * UT_SIZE, __byte_perm(u[2], u[1], sel), __byte_perm(u[4], u[3], sel), __byte_perm(u[6], u[5], sel), __byte_perm(u[8], u[7], sel));
            sts128(ta + e * UT_SIZE + UT_COPY, __byte_perm(u[1], u[0], sel), __byte_perm(u[3], u[2], sel), __byte_perm(u[5], u[4], sel), __byte_perm(u[7], u[6], sel));
          }
          if (p == 0) {
            __syncwarp();
            if (lane == 0) mbar_arrive(bar + 8 * (B_UFULL + st));
            if (st < 3 && lane < 2) mbar_arrive_c(mapa(bar + 8 * (B_KVFREE + st), lane), 2);
          }
        }
        __syncwarp();
        if (lane == 0) { mbar_arrive(bar + 8 * B_UREST); TS(56 + st); }
      }
    }
    const uint32_t epoch = ldg_relaxed(g_epoch + c) + 1;
    const uint32_t par = epoch & 1;
    if (zw == 0) {
#pragma unroll 1
      for (int qt = 0; qt < 16; qt++) {
        mbar_wait(bar + 8 * (B_YFULL + qt), 0);
        const uint32_t yb = sb + off_Y(qt >> 2) + (qt & 3) * 1024 + lane * 8;
        uint32_t* zp = g_z + (size_t)((qt >> 2) * NCTA + c) * S + (qt & 3) * 512 + lane * 4;
        uint2 p[4][8];
#pragma unroll
        for (int k = 0; k < 4; k++)
#pragma unroll
          for (int i = 0; i < 8; i++) p[k][i] = lds64(yb + i * YW + k * 256);
#pragma unroll
        for (int k = 0; k < 4; k++) {
          const uint32_t a0 = badd2(badd2(p[k][0].x, p[k][1].x), badd2(p[k][2].x, p[k][3].x));
          const uint32_t a1 = badd2(badd2(p[k][0].y, p[k][1].y), badd2(p[k][2].y, p[k][3].y));
          const uint32_t b0 = badd2(badd2(p[k][4].x, p[k][5].x), badd2(p[k][6].x, p[k][7].x));
          const uint32_t b1 = badd2(badd2(p[k][4].y, p[k][5].y), badd2(p[k][6].y, p[k][7].y));
          stg_b128(zp + k * 128, (__byte_perm(a0, b0, 0x5410) & ~1u) | par, __byte_perm(a0, b0, 0x7632), __byte_perm(a1, b1, 0x5410), __byte_perm(a1, b1, 0x7632));
        }
        if ((qt & 3) == 3) {
          __syncwarp();
          if (lane == 0) { mbar_arrive(bar + 8 * (B_ZDONE + (qt >> 2))); TS(17 + (qt >> 2)); }
        }
      }
#pragma unroll 1
      for (int tile = 0; tile < 2; tile++) {
        const int n0 = 448 * j + 256 * tile;
        if (tile == 0 || m < 12) {
          float cs[8];
#pragma unroll
          for (int i = 0; i < 8; i++) cs[i] = 0.f;
          const __nv_bfloat16* wp = P.w1 + (size_t)(lane >> 1) * F + n0 + 16 * m + 8 * (lane & 1);
#pragma unroll 1
          for (int b = 0; b < 4; b++) {
            uint4 v[16];
#pragma unroll
            for (int i = 0; i < 16; i++) v[i] = __ldg((const uint4*)(wp + (size_t)(16 * b + i) * 16 * F));
#pragma unroll
            for (int i = 0; i < 16; i += 4) {
              const uint32_t a0 = badd2(badd2(v[i].x, v[i + 1].x), badd2(v[i + 2].x, v[i + 3].x)), a1 = badd2(badd2(v[i].y, v[i + 1].y), badd2(v[i + 2].y, v[i + 3].y));
              const uint32_t a2 = badd2(badd2(v[i].z, v[i + 1].z), badd2(v[i + 2].z, v[i + 3].z)), a3 = badd2(badd2(v[i].w, v[i + 1].w), badd2(v[i + 2].w, v[i + 3].w));
              cs[0] += bflo(a0); cs[1] += bfhi(a0); cs[2] += bflo(a1); cs[3] += bfhi(a1);
              cs[4] += bflo(a2); cs[5] += bfhi(a2); cs[6] += bflo(a3); cs[7] += bfhi(a3);
            }
          }
#pragma unroll 1
          for (int o = 2; o < 32; o <<= 1) {
#pragma unroll
            for (int i = 0; i < 8; i++) cs[i] += __shfl_xor_sync(0xffffffffu, cs[i], o);
          }
          if (lane < 2) {
            float4* cp = (float4*)(g_cs + n0 + 16 * m + 8 * lane);
            cp[0] = make_float4(cs[0], cs[1], cs[2], cs[3]);
            cp[1] = make_float4(cs[4], cs[5], cs[6], cs[7]);
          }
          __syncwarp();
          if (lane == 0) signal(g_ccnt + (tile * 8 + j) * 32);
        }
        if (lane == 0) wait_count(g_ccnt + (tile * 8 + j) * 32, epoch * (tile ? 12 : 16));
        __syncwarp();
        if (tile) mbar_wait(bar + 8 * B_XFREE, 0);
#pragma unroll 1
        for (int i = lane; i < (tile ? 96 : 128); i += 32) {
          const float2 cv = ldg_cg2f(g_cs + n0 + 2 * i);
          const uint32_t bv = __ldg((const uint32_t*)(P.b1 + n0) + i);
          const uint32_t hi = packbf(cv.x, cv.y), lo = packbf(cv.x - bflo(hi), cv.y - bfhi(hi));
#pragma unroll
          for (int cp = 0; cp < 2; cp++) {
            sts128(sb + OFF_X + cp * 16384 + i * 32, __byte_perm(hi, lo, 0x5410), __byte_perm(hi, bv, 0x5410), bv & 0xffffu, 0);
            sts128(sb + OFF_X + cp * 16384 + i * 32 + 16, __byte_perm(hi, lo, 0x7632), __byte_perm(hi, bv, 0x7632), bv >> 16, 0);
          }
        }
        if (tile == 0) {
          if (lane == 0) wait_count(g_acnt + (2 * 16 + m) * 32, epoch * 8);
          __syncwarp();
#pragma unroll
          for (int i = 0; i < 4; i++) {
            const uint4 v = ldg_cg4(g_hstat + 128 * m + lane + 32 * i);
            sts128(sb + OFF_HS + (lane + 32 * i) * 16, v.x, v.y, v.z, v.w);
          }
        }
        fence_async_smem();
        __syncwarp();
        if (lane == 0) { mbar_arrive(bar + 8 * B_CSFULL); TS(21 + 19 * tile); }
      }
    } else {
      const int hw = zw - 1, rowb = 128 * m + 16 * j;
      const int q = lane & 3, i0 = 64 * hw + (lane >> 2), row0 = rowb + 4 * q;
      uint32_t xr[4][2][4][4];
#pragma unroll
      for (int a = 0; a < 4; a++)
#pragma unroll
        for (int k = 0; k < 2; k++)
#pragma unroll
          for (int i = 0; i < 4; i++) {
            const uint4 v = __ldg((const uint4*)(P.x + (size_t)(row0 + a) * D) + i0 + 32 * k + 8 * i);
            xr[a][k][i][0] = v.x; xr[a][k][i][1] = v.y; xr[a][k][i][2] = v.z; xr[a][k][i][3] = v.w;
          }
#pragma unroll 1
      for (int pass = 0; pass < 2; pass++) {
        float2* red = (float2*)(smem + OFF_RED);
#pragma unroll
        for (int a = 0; a < 4; a++) {
          const uint32_t pv = __byte_perm(xr[a][0][0][0], 0, 0x1010);
          float t1 = 0.f, t2 = 0.f;
#pragma unroll
          for (int ch = 0; ch < 4; ch++) {
            uint32_t c1 = 0, c2 = 0;
#pragma unroll
            for (int i = 0; i < 8; i++) {
              const uint32_t dd = bsub2(xr[a][ch >> 1][2 * (ch & 1) + (i >> 2)][i & 3], pv);
              c1 = i ? badd2(c1, dd) : dd;
              c2 = i ? bfma2(dd, dd, c2) : bmul2(dd, dd);
            }
            t1 += bflo(c1) + bfhi(c1);
            t2 += bflo(c2) + bfhi(c2);
          }
          const float pf = bflo(pv);
          t2 = fmaf(pf, fmaf(pf, 64.f, 2.f * t1), t2);
          t1 = fmaf(pf, 64.f, t1);
#pragma unroll
          for (int o = 4; o < 32; o <<= 1) { t1 += __shfl_xor_sync(0xffffffffu, t1, o); t2 += __shfl_xor_sync(0xffffffffu, t2, o); }
          if (lane < 4) red[hw * 16 + 4 * q + a] = make_float2(t1, t2);
        }
        bar_sync(1, 64);
        if (pass == 1) {
          if (hw == 0) {
            if (lane < 16) {
              const float2 r0 = red[lane], r1 = red[16 + lane];
              const float mu = (r0.x + r1.x) * (1.f / D);
              const float var = fmaxf(fmaf(-mu, mu, (r0.y + r1.y) * (1.f / D)), 0.f) + 1e-5f;
              const float sd = sqrtf(var);
              const uint32_t hi = packbf(-mu, sd), lo = packbf(-mu - bflo(hi), sd - bfhi(hi));
              stg128(g_hstat + rowb + lane, __byte_perm(hi, 0, 0x1010), __byte_perm(lo, hi, 0x7610), lo >> 16, __float_as_uint(1.f / var));
            }
            __syncwarp();
            if (lane == 0) { signal(g_acnt + (2 * 16 + m) * 32); TS(43); }
          }
          break;
        }
        uint32_t rs2[4], nm2[4];
#pragma unroll
        for (int a = 0; a < 4; a++) {
          const float2 r0 = red[4 * q + a], r1 = red[16 + 4 * q + a];
          const float mu = (r0.x + r1.x) * (1.f / D);
          const float rs = rsqrtf(fmaxf(fmaf(-mu, mu, (r0.y + r1.y) * (1.f / D)), 0.f) + 1e-5f);
          rs2[a] = packbf(rs, rs);
          nm2[a] = packbf(-mu * bflo(rs2[a]), -mu * bflo(rs2[a]));
        }
        if (tid == 320) TS(22);
        const uint32_t* zp0 = g_z + (size_t)i0 * S + row0;
        uint32_t* hp = (uint32_t*)(g_h + (size_t)row0 * D) + i0;
#pragma unroll
        for (int r = 0; r < 4; r++) {
          mbar_wait(bar + 8 * (B_YFULL + 4 * r + (m >> 2)), 0);
#pragma unroll
          for (int k = 0; k < 2; k++) {
            const uint32_t* zp = zp0 + (size_t)(r * NCTA + 32 * k) * S;
            uint4 zv[4];
            int it = 0;
            while (true) {
#pragma unroll
              for (int i = 0; i < 4; i++) zv[i] = ldg_b128(zp + (size_t)8 * i * S);
              const uint32_t bad = ((zv[0].x ^ par) | (zv[1].x ^ par) | (zv[2].x ^ par) | (zv[3].x ^ par)) & 1;
              if (__all_sync(0xffffffffu, bad == 0)) break;
              __nanosleep(100);
              if (++it > (1 << 20)) __trap();
            }
            if (tid == 320 && k == 1) TS(27 + r);
#pragma unroll
            for (int a = 0; a < 4; a++) {
#pragma unroll
              for (int i = 0; i < 4; i++) {
                const uint32_t zz = a == 0 ? zv[i].x : a == 1 ? zv[i].y : a == 2 ? zv[i].z : zv[i].w;
                xr[a][k][i][r] = bfma2(bfma2(xr[a][k][i][r], rs2[a], nm2[a]), zz, xr[a][k][i][r]);
                hp[a * (D / 2) + 128 * r + 32 * k + 8 * i] = xr[a][k][i][r];
              }
            }
          }
          fence_async_global();
          __syncwarp();
          if (tid == 320) TS(23 + r);
          if (lane == 0) signal(g_hcnt + (r * 16 + m) * 32);
          if (tid == 320) TS(32 + r);
        }
      }
      if (hw == 0 && lane == 0) {
        const uint32_t bar0 = mapa(bar, 0), bar1 = mapa(bar, 1);
#pragma unroll 1
        for (int tile = 0; tile < 2; tile++) {
          mbar_wait(bar + 8 * (B_ADONE + tile), 0);
          const int nb = tile ? 6 : 8;
#pragma unroll 1
          for (int i = nb - 1; i >= 0; i--) {
            tma_store(&P.tm_actst, sb + off_act(tile, i & 1, i >> 1), 448 * j + 256 * tile + 64 * (i >> 1), 128 * m + 64 * (i & 1));
            bulk_commit();
            bulk_wait_read();
            if (tile == 1 && i == 4) { mbar_arrive_c(bar0 + 8 * (B_EMPTY2 + 5), 2); mbar_arrive_c(bar1 + 8 * (B_EMPTY2 + 5), 2); }
            if (tile == 0 || i <= 4) __nanosleep(ST_SLEEP);
          }
          if (tile == 0) {
            mbar_arrive_c(bar + 8 * B_XFREE, 4);
#pragma unroll 1
            for (int s = 0; s < 5; s++) { mbar_arrive_c(bar0 + 8 * (B_EMPTY2 + s), 2); mbar_arrive_c(bar1 + 8 * (B_EMPTY2 + s), 2); }
          } else {
            mbar_expect_tx(bar + 8 * B_HRES, 32768);
            tma3d(sb + OFF_X, &P.tm_hres, bar + 8 * B_HRES, 32 * j, 0, 128 * m);
          }
          bulk_wait();
          fence_async_global();
          signal(g_acnt + (tile * 16 + m) * 32);
          TS(41 + tile);
        }
        g_epoch[c] = epoch;
      }
    }
  }
}

typedef CUresult (*PFN_encode)(CUtensorMap*, CUtensorMapDataType, cuuint32_t, void*, const cuuint64_t*, const cuuint64_t*, const cuuint32_t*,
                               const cuuint32_t*, CUtensorMapInterleave, CUtensorMapSwizzle, CUtensorMapL2promotion, CUtensorMapFloatOOBfill);

void encode(PFN_encode enc, CUtensorMap* m, const void* ptr, int rank, const cuuint64_t* dims, const cuuint64_t* strides, const cuuint32_t* box,
            CUtensorMapSwizzle swz) {
  const cuuint32_t es[5] = {1, 1, 1, 1, 1};
  enc(m, CU_TENSOR_MAP_DATA_TYPE_BFLOAT16, rank, (void*)ptr, dims, strides, box, es, CU_TENSOR_MAP_INTERLEAVE_NONE, swz,
      CU_TENSOR_MAP_L2_PROMOTION_L2_128B, CU_TENSOR_MAP_FLOAT_OOB_FILL_NONE);
}

}

extern "C" void kernel_launch(void* const* d_in, const int* in_sizes, int n_in, void* d_out, int out_size) {
  static PFN_encode enc = nullptr;
  static void *p_h = nullptr, *p_act = nullptr;
  if (!enc) {
    cudaDriverEntryPointQueryResult qr;
    cudaGetDriverEntryPoint("cuTensorMapEncodeTiled", (void**)&enc, cudaEnableDefault, &qr);
    cudaGetSymbolAddress(&p_h, g_h);
    cudaGetSymbolAddress(&p_act, g_act);
    cudaFuncSetAttribute(fused_kernel, cudaFuncAttributeMaxDynamicSharedMemorySize, SMEM_BYTES);
  }
  Params P;
  P.x = (const __nv_bfloat16*)d_in[0];
  P.shift_k = (const __nv_bfloat16*)d_in[3];
  P.ssm_k = (const __nv_bfloat16*)d_in[4];
  P.ssm_D = (const __nv_bfloat16*)d_in[5];
  P.w1 = (const __nv_bfloat16*)d_in[7];
  P.b1 = (const __nv_bfloat16*)d_in[8];
  P.w2 = (const __nv_bfloat16*)d_in[9];
  P.b2 = (const __nv_bfloat16*)d_in[10];
  {
    const cuuint64_t dims[3] = {D, S / 8, 8}, str[2] = {8 * D * 2, D * 2};
    const cuuint32_t box[3] = {16, 17, 8};
    encode(enc, &P.tm_k, d_in[1], 3, dims, str, box, CU_TENSOR_MAP_SWIZZLE_NONE);
    encode(enc, &P.tm_v, d_in[2], 3, dims, str, box, CU_TENSOR_MAP_SWIZZLE_NONE);
  }
  {
    const cuuint64_t dims[2] = {D, S}, str[1] = {D * 2};
    const cuuint32_t box[2] = {64, 128}, boxo[2] = {64, 64};
    encode(enc, &P.tm_h, p_h, 2, dims, str, box, CU_TENSOR_MAP_SWIZZLE_128B);
    encode(enc, &P.tm_out, d_out, 2, dims, str, boxo, CU_TENSOR_MAP_SWIZZLE_128B);
  }
  {
    const cuuint64_t dims[3] = {F, 8, D / 8}, str[2] = {F * 2, 8 * F * 2};
    const cuuint32_t box[3] = {64, 2, 16};
    encode(enc, &P.tm_w1, P.w1, 3, dims, str, box, CU_TENSOR_MAP_SWIZZLE_128B);
  }
  {
    const cuuint64_t dims[2] = {F, S}, str[1] = {F * 2};
    const cuuint32_t box[2] = {64, 128}, boxs[2] = {64, 64};
    encode(enc, &P.tm_act, p_act, 2, dims, str, box, CU_TENSOR_MAP_SWIZZLE_128B);
    encode(enc, &P.tm_actst, p_act, 2, dims, str, boxs, CU_TENSOR_MAP_SWIZZLE_128B);
  }
  {
    const cuuint64_t dims[2] = {D, F}, str[1] = {D * 2};
    const cuuint32_t box[2] = {64, 64};
    encode(enc, &P.tm_w2, P.w2, 2, dims, str, box, CU_TENSOR_MAP_SWIZZLE_128B);
  }
  {
    const cuuint64_t dims[3] = {256, 4, S}, str[2] = {512, D * 2};
    const cuuint32_t box[3] = {32, 4, 128};
    encode(enc, &P.tm_hres, p_h, 3, dims, str, box, CU_TENSOR_MAP_SWIZZLE_64B);
  }
  fused_kernel<<<NCTA, NTHREADS, SMEM_BYTES>>>(P);
}
```

```cpp
#include <cuda_runtime.h>
#include <cuda_bf16.h>
#include <cuda.h>
#include <stdint.h>

#define DBG_TS 0
#define KV_GATE 5
#define EXP 0
#define ST_SLEEP 200

namespace {

constexpr int S = 2048, D = 1024, F = 3584;
constexpr int NCTA = 128, NTHREADS = 384;

constexpr int UT_COPY = 1040 * 4;
constexpr int UT_SIZE = 2 * UT_COPY;
constexpr int KT_SIZE = 16 + 4096;
constexpr int T_SIZE = 2 * (UT_SIZE + KT_SIZE);
constexpr int KV_BOX = 17 * 8 * 32;
constexpr int KV_SLOT = 4 * KV_BOX;
constexpr int KV_SIZE = 2 * KV_SLOT;
constexpr int YW = 4096 + 96;
constexpr int YBUF = 4 * YW;
constexpr int OFF_T3 = 196608 - T_SIZE;
constexpr int OFF_KVB = (OFF_T3 - KV_SIZE) & ~127;
constexpr int OFF_T2 = OFF_KVB - T_SIZE;
constexpr int OFF_KVA = (OFF_T2 - KV_SIZE) & ~127;
constexpr int OFF_T1 = OFF_KVA - T_SIZE;
constexpr int OFF_T0 = OFF_T1 - T_SIZE;
constexpr int OFF_X = 196608;
constexpr int OFF_HS = OFF_X + 32768;
constexpr int OFF_RED = OFF_X + 34816;
constexpr int OFF_BAR = OFF_X + 35200;
constexpr int SMEM_BYTES = 232448;
static_assert(OFF_T0 >= KV_SLOT && 2 * YBUF <= KV_SIZE && OFF_X + 2 * YBUF <= OFF_RED && OFF_BAR + 640 <= SMEM_BYTES, "smem map");
static_assert(OFF_T2 >= 98304, "stage 1 must only overlap T0,T1,KVA");
static_assert(OFF_T3 >= 147456, "stage 2 must not overlap T3");

enum {
  B_KVFULL = 0, B_KFULL = 8, B_UFULL = 16, B_YFULL = 24  , B_FULL = 40, B_ZDONE = 44,
  B_CSFULL = 48, B_HRES = 49, B_XFREE = 50, B_SFREE = 51, B_RECV = 52,
  B_EMPTY = 56, B_KVFREE = 60  , B_PEER = 63, B_ADONE = 64, B_UREST = 66
};

struct Params {
  CUtensorMap tm_k, tm_v, tm_h, tm_w1, tm_act, tm_actst, tm_w2, tm_hres, tm_out;
  const __nv_bfloat16 *x, *shift_k, *ssm_k, *ssm_D, *w1, *b1, *w2, *b2;
};

__device__ __align__(1024) uint32_t g_z[4 * NCTA * S];
__device__ __align__(1024) __nv_bfloat16 g_h[S * D];
__device__ __align__(1024) __nv_bfloat16 g_act[S * F];
__device__ __align__(128) uint4 g_hstat[S];
__device__ __align__(128) float g_cs[F];
__device__ __align__(128) uint32_t g_hcnt[4 * 16 * 32];
__device__ __align__(128) uint32_t g_acnt[3 * 16 * 32];
__device__ __align__(128) uint32_t g_ccnt[2 * 8 * 32];
__device__ __align__(128) uint32_t g_epoch[NCTA];
#define TS(slot) do {} while (0)

template<int N> __device__ __forceinline__ void wgmma_rs(float* d, const uint32_t* a, uint64_t db, int sc);
template<int N> __device__ __forceinline__ void wgmma_ss(float* d, uint64_t da, uint64_t db, int sc);
template<> __device__ __forceinline__ void wgmma_rs<16>(float* d, const uint32_t* a, uint64_t db, int sc) {
  asm volatile("{.reg .pred p; setp.ne.b32 p, %13, 0;\n"
  "wgmma.mma_async.sync.aligned.m64n16k16.f32.bf16.bf16 {%0,%1,%2,%3,%4,%5,%6,%7}, {%8,%9,%10,%11}, %12, p, 1, 1, 0;}\n"
  : "+f"(d[0]),"+f"(d[1]),"+f"(d[2]),"+f"(d[3]),"+f"(d[4]),"+f"(d[5]),"+f"(d[6]),"+f"(d[7])
  : "r"(a[0]), "r"(a[1]), "r"(a[2]), "r"(a[3]), "l"(db), "r"(sc));
}
template<> __device__ __forceinline__ void wgmma_rs<32>(float* d, const uint32_t* a, uint64_t db, int sc) {
  asm volatile("{.reg .pred p; setp.ne.b32 p, %21, 0;\n"
  "wgmma.mma_async.sync.aligned.m64n32k16.f32.bf16.bf16 {%0,%1,%2,%3,%4,%5,%6,%7,%8,%9,%10,%11,%12,%13,%14,%15}, {%16,%17,%18,%19}, %20, p, 1, 1, 0;}\n"
  : "+f"(d[0]),"+f"(d[1]),"+f"(d[2]),"+f"(d[3]),"+f"(d[4]),"+f"(d[5]),"+f"(d[6]),"+f"(d[7]),"+f"(d[8]),"+f"(d[9]),"+f"(d[10]),"+f"(d[11]),"+f"(d[12]),"+f"(d[13]),"+f"(d[14]),"+f"(d[15])
  : "r"(a[0]), "r"(a[1]), "r"(a[2]), "r"(a[3]), "l"(db), "r"(sc));
}
template<> __device__ __forceinline__ void wgmma_rs<48>(float* d, const uint32_t* a, uint64_t db, int sc) {
  asm volatile("{.reg .pred p; setp.ne.b32 p, %29, 0;\n"
  "wgmma.mma_async.sync.aligned.m64n48k16.f32.bf16.bf16 {%0,%1,%2,%3,%4,%5,%6,%7,%8,%9,%10,%11,%12,%13,%14,%15,%16,%17,%18,%19,%20,%21,%22,%23}, {%24,%25,%26,%27}, %28, p, 1, 1, 0;}\n"
  : "+f"(d[0]),"+f"(d[1]),"+f"(d[2]),"+f"(d[3]),"+f"(d[4]),"+f"(d[5]),"+f"(d[6]),"+f"(d[7]),"+f"(d[8]),"+f"(d[9]),"+f"(d[10]),"+f"(d[11]),"+f"(d[12]),"+f"(d[13]),"+f"(d[14]),"+f"(d[15]),"+f"(d[16]),"+f"(d[17]),"+f"(d[18]),"+f"(d[19]),"+f"(d[20]),"+f"(d[21]),"+f"(d[22]),"+f"(d[23])
  : "r"(a[0]), "r"(a[1]), "r"(a[2]), "r"(a[3]), "l"(db), "r"(sc));
}
template<> __device__ __forceinline__ void wgmma_rs<64>(float* d, const uint32_t* a, uint64_t db, int sc) {
  asm volatile("{.reg .pred p; setp.ne.b32 p, %37, 0;\n"
  "wgmma.mma_async.sync.aligned.m64n64k16.f32.bf16.bf16 {%0,%1,%2,%3,%4,%5,%6,%7,%8,%9,%10,%11,%12,%13,%14,%15,%16,%17,%18,%19,%20,%21,%22,%23,%24,%25,%26,%27,%28,%29,%30,%31}, {%32,%33,%34,%35}, %36, p, 1, 1, 0;}\n"
  : "+f"(d[0]),"+f"(d[1]),"+f"(d[2]),"+f"(d[3]),"+f"(d[4]),"+f"(d[5]),"+f"(d[6]),"+f"(d[7]),"+f"(d[8]),"+f"(d[9]),"+f"(d[10]),"+f"(d[11]),"+f"(d[12]),"+f"(d[13]),"+f"(d[14]),"+f"(d[15]),"+f"(d[16]),"+f"(d[17]),"+f"(d[18]),"+f"(d[19]),"+f"(d[20]),"+f"(d[21]),"+f"(d[22]),"+f"(d[23]),"+f"(d[24]),"+f"(d[25]),"+f"(d[26]),"+f"(d[27]),"+f"(d[28]),"+f"(d[29]),"+f"(d[30]),"+f"(d[31])
  : "r"(a[0]), "r"(a[1]), "r"(a[2]), "r"(a[3]), "l"(db), "r"(sc));
}
template<> __device__ __forceinline__ void wgmma_rs<80>(float* d, const uint32_t* a, uint64_t db, int sc) {
  asm volatile("{.reg .pred p; setp.ne.b32 p, %45, 0;\n"
  "wgmma.mma_async.sync.aligned.m64n80k16.f32.bf16.bf16 {%0,%1,%2,%3,%4,%5,%6,%7,%8,%9,%10,%11,%12,%13,%14,%15,%16,%17,%18,%19,%20,%21,%22,%23,%24,%25,%26,%27,%28,%29,%30,%31,%32,%33,%34,%35,%36,%37,%38,%39}, {%40,%41,%42,%43}, %44, p, 1, 1, 0;}\n"
  : "+f"(d[0]),"+f"(d[1]),"+f"(d[2]),"+f"(d[3]),"+f"(d[4]),"+f"(d[5]),"+f"(d[6]),"+f"(d[7]),"+f"(d[8]),"+f"(d[9]),"+f"(d[10]),"+f"(d[11]),"+f"(d[12]),"+f"(d[13]),"+f"(d[14]),"+f"(d[15]),"+f"(d[16]),"+f"(d[17]),"+f"(d[18]),"+f"(d[19]),"+f"(d[20]),"+f"(d[21]),"+f"(d[22]),"+f"(d[23]),"+f"(d[24]),"+f"(d[25]),"+f"(d[26]),"+f"(d[27]),"+f"(d[28]),"+f"(d[29]),"+f"(d[30]),"+f"(d[31]),"+f"(d[32]),"+f"(d[33]),"+f"(d[34]),"+f"(d[35]),"+f"(d[36]),"+f"(d[37]),"+f"(d[38]),"+f"(d[39])
  : "r"(a[0]), "r"(a[1]), "r"(a[2]), "r"(a[3]), "l"(db), "r"(sc));
}
template<> __device__ __forceinline__ void wgmma_rs<96>(float* d, const uint32_t* a, uint64_t db, int sc) {
  asm volatile("{.reg .pred p; setp.ne.b32 p, %53, 0;\n"
  "wgmma.mma_async.sync.aligned.m64n96k16.f32.bf16.bf16 {%0,%1,%2,%3,%4,%5,%6,%7,%8,%9,%10,%11,%12,%13,%14,%15,%16,%17,%18,%19,%20,%21,%22,%23,%24,%25,%26,%27,%28,%29,%30,%31,%32,%33,%34,%35,%36,%37,%38,%39,%40,%41,%42,%43,%44,%45,%46,%47}, {%48,%49,%50,%51}, %52, p, 1, 1, 0;}\n"
  : "+f"(d[0]),"+f"(d[1]),"+f"(d[2]),"+f"(d[3]),"+f"(d[4]),"+f"(d[5]),"+f"(d[6]),"+f"(d[7]),"+f"(d[8]),"+f"(d[9]),"+f"(d[10]),"+f"(d[11]),"+f"(d[12]),"+f"(d[13]),"+f"(d[14]),"+f"(d[15]),"+f"(d[16]),"+f"(d[17]),"+f"(d[18]),"+f"(d[19]),"+f"(d[20]),"+f"(d[21]),"+f"(d[22]),"+f"(d[23]),"+f"(d[24]),"+f"(d[25]),"+f"(d[26]),"+f"(d[27]),"+f"(d[28]),"+f"(d[29]),"+f"(d[30]),"+f"(d[31]),"+f"(d[32]),"+f"(d[33]),"+f"(d[34]),"+f"(d[35]),"+f"(d[36]),"+f"(d[37]),"+f"(d[38]),"+f"(d[39]),"+f"(d[40]),"+f"(d[41]),"+f"(d[42]),"+f"(d[43]),"+f"(d[44]),"+f"(d[45]),"+f"(d[46]),"+f"(d[47])
  : "r"(a[0]), "r"(a[1]), "r"(a[2]), "r"(a[3]), "l"(db), "r"(sc));
}
template<> __device__ __forceinline__ void wgmma_rs<112>(float* d, const uint32_t* a, uint64_t db, int sc) {
  asm volatile("{.reg .pred p; setp.ne.b32 p, %61, 0;\n"
  "wgmma.mma_async.sync.aligned.m64n112k16.f32.bf16.bf16 {%0,%1,%2,%3,%4,%5,%6,%7,%8,%9,%10,%11,%12,%13,%14,%15,%16,%17,%18,%19,%20,%21,%22,%23,%24,%25,%26,%27,%28,%29,%30,%31,%32,%33,%34,%35,%36,%37,%38,%39,%40,%41,%42,%43,%44,%45,%46,%47,%48,%49,%50,%51,%52,%53,%54,%55}, {%56,%57,%58,%59}, %60, p, 1, 1, 0;}\n"
  : "+f"(d[0]),"+f"(d[1]),"+f"(d[2]),"+f"(d[3]),"+f"(d[4]),"+f"(d[5]),"+f"(d[6]),"+f"(d[7]),"+f"(d[8]),"+f"(d[9]),"+f"(d[10]),"+f"(d[11]),"+f"(d[12]),"+f"(d[13]),"+f"(d[14]),"+f"(d[15]),"+f"(d[16]),"+f"(d[17]),"+f"(d[18]),"+f"(d[19]),"+f"(d[20]),"+f"(d[21]),"+f"(d[22]),"+f"(d[23]),"+f"(d[24]),"+f"(d[25]),"+f"(d[26]),"+f"(d[27]),"+f"(d[28]),"+f"(d[29]),"+f"(d[30]),"+f"(d[31]),"+f"(d[32]),"+f"(d[33]),"+f"(d[34]),"+f"(d[35]),"+f"(d[36]),"+f"(d[37]),"+f"(d[38]),"+f"(d[39]),"+f"(d[40]),"+f"(d[41]),"+f"(d[42]),"+f"(d[43]),"+f"(d[44]),"+f"(d[45]),"+f"(d[46]),"+f"(d[47]),"+f"(d[48]),"+f"(d[49]),"+f"(d[50]),"+f"(d[51]),"+f"(d[52]),"+f"(d[53]),"+f"(d[54]),"+f"(d[55])
  : "r"(a[0]), "r"(a[1]), "r"(a[2]), "r"(a[3]), "l"(db), "r"(sc));
}
template<> __device__ __forceinline__ void wgmma_rs<128>(float* d, const uint32_t* a, uint64_t db, int sc) {
  asm volatile("{.reg .pred p; setp.ne.b32 p, %69, 0;\n"
  "wgmma.mma_async.sync.aligned.m64n128k16.f32.bf16.bf16 {%0,%1,%2,%3,%4,%5,%6,%7,%8,%9,%10,%11,%12,%13,%14,%15,%16,%17,%18,%19,%20,%21,%22,%23,%24,%25,%26,%27,%28,%29,%30,%31,%32,%33,%34,%35,%36,%37,%38,%39,%40,%41,%42,%43,%44,%45,%46,%47,%48,%49,%50,%51,%52,%53,%54,%55,%56,%57,%58,%59,%60,%61,%62,%63}, {%64,%65,%66,%67}, %68, p, 1, 1, 0;}\n"
  : "+f"(d[0]),"+f"(d[1]),"+f"(d[2]),"+f"(d[3]),"+f"(d[4]),"+f"(d[5]),"+f"(d[6]),"+f"(d[7]),"+f"(d[8]),"+f"(d[9]),"+f"(d[10]),"+f"(d[11]),"+f"(d[12]),"+f"(d[13]),"+f"(d[14]),"+f"(d[15]),"+f"(d[16]),"+f"(d[17]),"+f"(d[18]),"+f"(d[19]),"+f"(d[20]),"+f"(d[21]),"+f"(d[22]),"+f"(d[23]),"+f"(d[24]),"+f"(d[25]),"+f"(d[26]),"+f"(d[27]),"+f"(d[28]),"+f"(d[29]),"+f"(d[30]),"+f"(d[31]),"+f"(d[32]),"+f"(d[33]),"+f"(d[34]),"+f"(d[35]),"+f"(d[36]),"+f"(d[37]),"+f"(d[38]),"+f"(d[39]),"+f"(d[40]),"+f"(d[41]),"+f"(d[42]),"+f"(d[43]),"+f"(d[44]),"+f"(d[45]),"+f"(d[46]),"+f"(d[47]),"+f"(d[48]),"+f"(d[49]),"+f"(d[50]),"+f"(d[51]),"+f"(d[52]),"+f"(d[53]),"+f"(d[54]),"+f"(d[55]),"+f"(d[56]),"+f"(d[57]),"+f"(d[58]),"+f"(d[59]),"+f"(d[60]),"+f"(d[61]),"+f"(d[62]),"+f"(d[63])
  : "r"(a[0]), "r"(a[1]), "r"(a[2]), "r"(a[3]), "l"(db), "r"(sc));
}
template<> __device__ __forceinline__ void wgmma_rs<144>(float* d, const uint32_t* a, uint64_t db, int sc) {
  asm volatile("{.reg .pred p; setp.ne.b32 p, %77, 0;\n"
  "wgmma.mma_async.sync.aligned.m64n144k16.f32.bf16.bf16 {%0,%1,%2,%3,%4,%5,%6,%7,%8,%9,%10,%11,%12,%13,%14,%15,%16,%17,%18,%19,%20,%21,%22,%23,%24,%25,%26,%27,%28,%29,%30,%31,%32,%33,%34,%35,%36,%37,%38,%39,%40,%41,%42,%43,%44,%45,%46,%47,%48,%49,%50,%51,%52,%53,%54,%55,%56,%57,%58,%59,%60,%61,%62,%63,%64,%65,%66,%67,%68,%69,%70,%71}, {%72,%73,%74,%75}, %76, p, 1, 1, 0;}\n"
  : "+f"(d[0]),"+f"(d[1]),"+f"(d[2]),"+f"(d[3]),"+f"(d[4]),"+f"(d[5]),"+f"(d[6]),"+f"(d[7]),"+f"(d[8]),"+f"(d[9]),"+f"(d[10]),"+f"(d[11]),"+f"(d[12]),"+f"(d[13]),"+f"(d[14]),"+f"(d[15]),"+f"(d[16]),"+f"(d[17]),"+f"(d[18]),"+f"(d[19]),"+f"(d[20]),"+f"(d[21]),"+f"(d[22]),"+f"(d[23]),"+f"(d[24]),"+f"(d[25]),"+f"(d[26]),"+f"(d[27]),"+f"(d[28]),"+f"(d[29]),"+f"(d[30]),"+f"(d[31]),"+f"(d[32]),"+f"(d[33]),"+f"(d[34]),"+f"(d[35]),"+f"(d[36]),"+f"(d[37]),"+f"(d[38]),"+f"(d[39]),"+f"(d[40]),"+f"(d[41]),"+f"(d[42]),"+f"(d[43]),"+f"(d[44]),"+f"(d[45]),"+f"(d[46]),"+f"(d[47]),"+f"(d[48]),"+f"(d[49]),"+f"(d[50]),"+f"(d[51]),"+f"(d[52]),"+f"(d[53]),"+f"(d[54]),"+f"(d[55]),"+f"(d[56]),"+f"(d[57]),"+f"(d[58]),"+f"(d[59]),"+f"(d[60]),"+f"(d[61]),"+f"(d[62]),"+f"(d[63]),"+f"(d[64]),"+f"(d[65]),"+f"(d[66]),"+f"(d[67]),"+f"(d[68]),"+f"(d[69]),"+f"(d[70]),"+f"(d[71])
  : "r"(a[0]), "r"(a[1]), "r"(a[2]), "r"(a[3]), "l"(db), "r"(sc));
}
template<> __device__ __forceinline__ void wgmma_rs<160>(float* d, const uint32_t* a, uint64_t db, int sc) {
  asm volatile("{.reg .pred p; setp.ne.b32 p, %85, 0;\n"
  "wgmma.mma_async.sync.aligned.m64n160k16.f32.bf16.bf16 {%0,%1,%2,%3,%4,%5,%6,%7,%8,%9,%10,%11,%12,%13,%14,%15,%16,%17,%18,%19,%20,%21,%22,%23,%24,%25,%26,%27,%28,%29,%30,%31,%32,%33,%34,%35,%36,%37,%38,%39,%40,%41,%42,%43,%44,%45,%46,%47,%48,%49,%50,%51,%52,%53,%54,%55,%56,%57,%58,%59,%60,%61,%62,%63,%64,%65,%66,%67,%68,%69,%70,%71,%72,%73,%74,%75,%76,%77,%78,%79}, {%80,%81,%82,%83}, %84, p, 1, 1, 0;}\n"
  : "+f"(d[0]),"+f"(d[1]),"+f"(d[2]),"+f"(d[3]),"+f"(d[4]),"+f"(d[5]),"+f"(d[6]),"+f"(d[7]),"+f"(d[8]),"+f"(d[9]),"+f"(d[10]),"+f"(d[11]),"+f"(d[12]),"+f"(d[13]),"+f"(d[14]),"+f"(d[15]),"+f"(d[16]),"+f"(d[17]),"+f"(d[18]),"+f"(d[19]),"+f"(d[20]),"+f"(d[21]),"+f"(d[22]),"+f"(d[23]),"+f"(d[24]),"+f"(d[25]),"+f"(d[26]),"+f"(d[27]),"+f"(d[28]),"+f"(d[29]),"+f"(d[30]),"+f"(d[31]),"+f"(d[32]),"+f"(d[33]),"+f"(d[34]),"+f"(d[35]),"+f"(d[36]),"+f"(d[37]),"+f"(d[38]),"+f"(d[39]),"+f"(d[40]),"+f"(d[41]),"+f"(d[42]),"+f"(d[43]),"+f"(d[44]),"+f"(d[45]),"+f"(d[46]),"+f"(d[47]),"+f"(d[48]),"+f"(d[49]),"+f"(d[50]),"+f"(d[51]),"+f"(d[52]),"+f"(d[53]),"+f"(d[54]),"+f"(d[55]),"+f"(d[56]),"+f"(d[57]),"+f"(d[58]),"+f"(d[59]),"+f"(d[60]),"+f"(d[61]),"+f"(d[62]),"+f"(d[63]),"+f"(d[64]),"+f"(d[65]),"+f"(d[66]),"+f"(d[67]),"+f"(d[68]),"+f"(d[69]),"+f"(d[70]),"+f"(d[71]),"+f"(d[72]),"+f"(d[73]),"+f"(d[74]),"+f"(d[75]),"+f"(d[76]),"+f"(d[77]),"+f"(d[78]),"+f"(d[79])
  : "r"(a[0]), "r"(a[1]), "r"(a[2]), "r"(a[3]), "l"(db), "r"(sc));
}
template<> __device__ __forceinline__ void wgmma_rs<176>(float* d, const uint32_t* a, uint64_t db, int sc) {
  asm volatile("{.reg .pred p; setp.ne.b32 p, %93, 0;\n"
  "wgmma.mma_async.sync.aligned.m64n176k16.f32.bf16.bf16 {%0,%1,%2,%3,%4,%5,%6,%7,%8,%9,%10,%11,%12,%13,%14,%15,%16,%17,%18,%19,%20,%21,%22,%23,%24,%25,%26,%27,%28,%29,%30,%31,%32,%33,%34,%35,%36,%37,%38,%39,%40,%41,%42,%43,%44,%45,%46,%47,%48,%49,%50,%51,%52,%53,%54,%55,%56,%57,%58,%59,%60,%61,%62,%63,%64,%65,%66,%67,%68,%69,%70,%71,%72,%73,%74,%75,%76,%77,%78,%79,%80,%81,%82,%83,%84,%85,%86,%87}, {%88,%89,%90,%91}, %92, p, 1, 1, 0;}\n"
  : "+f"(d[0]),"+f"(d[1]),"+f"(d[2]),"+f"(d[3]),"+f"(d[4]),"+f"(d[5]),"+f"(d[6]),"+f"(d[7]),"+f"(d[8]),"+f"(d[9]),"+f"(d[10]),"+f"(d[11]),"+f"(d[12]),"+f"(d[13]),"+f"(d[14]),"+f"(d[15]),"+f"(d[16]),"+f"(d[17]),"+f"(d[18]),"+f"(d[19]),"+f"(d[20]),"+f"(d[21]),"+f"(d[22]),"+f"(d[23]),"+f"(d[24]),"+f"(d[25]),"+f"(d[26]),"+f"(d[27]),"+f"(d[28]),"+f"(d[29]),"+f"(d[30]),"+f"(d[31]),"+f"(d[32]),"+f"(d[33]),"+f"(d[34]),"+f"(d[35]),"+f"(d[36]),"+f"(d[37]),"+f"(d[38]),"+f"(d[39]),"+f"(d[40]),"+f"(d[41]),"+f"(d[42]),"+f"(d[43]),"+f"(d[44]),"+f"(d[45]),"+f"(d[46]),"+f"(d[47]),"+f"(d[48]),"+f"(d[49]),"+f"(d[50]),"+f"(d[51]),"+f"(d[52]),"+f"(d[53]),"+f"(d[54]),"+f"(d[55]),"+f"(d[56]),"+f"(d[57]),"+f"(d[58]),"+f"(d[59]),"+f"(d[60]),"+f"(d[61]),"+f"(d[62]),"+f"(d[63]),"+f"(d[64]),"+f"(d[65]),"+f"(d[66]),"+f"(d[67]),"+f"(d[68]),"+f"(d[69]),"+f"(d[70]),"+f"(d[71]),"+f"(d[72]),"+f"(d[73]),"+f"(d[74]),"+f"(d[75]),"+f"(d[76]),"+f"(d[77]),"+f"(d[78]),"+f"(d[79]),"+f"(d[80]),"+f"(d[81]),"+f"(d[82]),"+f"(d[83]),"+f"(d[84]),"+f"(d[85]),"+f"(d[86]),"+f"(d[87])
  : "r"(a[0]), "r"(a[1]), "r"(a[2]), "r"(a[3]), "l"(db), "r"(sc));
}
template<> __device__ __forceinline__ void wgmma_rs<192>(float* d, const uint32_t* a, uint64_t db, int sc) {
  asm volatile("{.reg .pred p; setp.ne.b32 p, %101, 0;\n"
  "wgmma.mma_async.sync.aligned.m64n192k16.f32.bf16.bf16 {%0,%1,%2,%3,%4,%5,%6,%7,%8,%9,%10,%11,%12,%13,%14,%15,%16,%17,%18,%19,%20,%21,%22,%23,%24,%25,%26,%27,%28,%29,%30,%31,%32,%33,%34,%35,%36,%37,%38,%39,%40,%41,%42,%43,%44,%45,%46,%47,%48,%49,%50,%51,%52,%53,%54,%55,%56,%57,%58,%59,%60,%61,%62,%63,%64,%65,%66,%67,%68,%69,%70,%71,%72,%73,%74,%75,%76,%77,%78,%79,%80,%81,%82,%83,%84,%85,%86,%87,%88,%89,%90,%91,%92,%93,%94,%95}, {%96,%97,%98,%99}, %100, p, 1, 1, 0;}\n"
  : "+f"(d[0]),"+f"(d[1]),"+f"(d[2]),"+f"(d[3]),"+f"(d[4]),"+f"(d[5]),"+f"(d[6]),"+f"(d[7]),"+f"(d[8]),"+f"(d[9]),"+f"(d[10]),"+f"(d[11]),"+f"(d[12]),"+f"(d[13]),"+f"(d[14]),"+f"(d[15]),"+f"(d[16]),"+f"(d[17]),"+f"(d[18]),"+f"(d[19]),"+f"(d[20]),"+f"(d[21]),"+f"(d[22]),"+f"(d[23]),"+f"(d[24]),"+f"(d[25]),"+f"(d[26]),"+f"(d[27]),"+f"(d[28]),"+f"(d[29]),"+f"(d[30]),"+f"(d[31]),"+f"(d[32]),"+f"(d[33]),"+f"(d[34]),"+f"(d[35]),"+f"(d[36]),"+f"(d[37]),"+f"(d[38]),"+f"(d[39]),"+f"(d[40]),"+f"(d[41]),"+f"(d[42]),"+f"(d[43]),"+f"(d[44]),"+f"(d[45]),"+f"(d[46]),"+f"(d[47]),"+f"(d[48]),"+f"(d[49]),"+f"(d[50]),"+f"(d[51]),"+f"(d[52]),"+f"(d[53]),"+f"(d[54]),"+f"(d[55]),"+f"(d[56]),"+f"(d[57]),"+f"(d[58]),"+f"(d[59]),"+f"(d[60]),"+f"(d[61]),"+f"(d[62]),"+f"(d[63]),"+f"(d[64]),"+f"(d[65]),"+f"(d[66]),"+f"(d[67]),"+f"(d[68]),"+f"(d[69]),"+f"(d[70]),"+f"(d[71]),"+f"(d[72]),"+f"(d[73]),"+f"(d[74]),"+f"(d[75]),"+f"(d[76]),"+f"(d[77]),"+f"(d[78]),"+f"(d[79]),"+f"(d[80]),"+f"(d[81]),"+f"(d[82]),"+f"(d[83]),"+f"(d[84]),"+f"(d[85]),"+f"(d[86]),"+f"(d[87]),"+f"(d[88]),"+f"(d[89]),"+f"(d[90]),"+f"(d[91]),"+f"(d[92]),"+f"(d[93]),"+f"(d[94]),"+f"(d[95])
  : "r"(a[0]), "r"(a[1]), "r"(a[2]), "r"(a[3]), "l"(db), "r"(sc));
}
template<> __device__ __forceinline__ void wgmma_rs<208>(float* d, const uint32_t* a, uint64_t db, int sc) {
  asm volatile("{.reg .pred p; setp.ne.b32 p, %109, 0;\n"
  "wgmma.mma_async.sync.aligned.m64n208k16.f32.bf16.bf16 {%0,%1,%2,%3,%4,%5,%6,%7,%8,%9,%10,%11,%12,%13,%14,%15,%16,%17,%18,%19,%20,%21,%22,%23,%24,%25,%26,%27,%28,%29,%30,%31,%32,%33,%34,%35,%36,%37,%38,%39,%40,%41,%42,%43,%44,%45,%46,%47,%48,%49,%50,%51,%52,%53,%54,%55,%56,%57,%58,%59,%60,%61,%62,%63,%64,%65,%66,%67,%68,%69,%70,%71,%72,%73,%74,%75,%76,%77,%78,%79,%80,%81,%82,%83,%84,%85,%86,%87,%88,%89,%90,%91,%92,%93,%94,%95,%96,%97,%98,%99,%100,%101,%102,%103}, {%104,%105,%106,%107}, %108, p, 1, 1, 0;}\n"
  : "+f"(d[0]),"+f"(d[1]),"+f"(d[2]),"+f"(d[3]),"+f"(d[4]),"+f"(d[5]),"+f"(d[6]),"+f"(d[7]),"+f"(d[8]),"+f"(d[9]),"+f"(d[10]),"+f"(d[11]),"+f"(d[12]),"+f"(d[13]),"+f"(d[14]),"+f"(d[15]),"+f"(d[16]),"+f"(d[17]),"+f"(d[18]),"+f"(d[19]),"+f"(d[20]),"+f"(d[21]),"+f"(d[22]),"+f"(d[23]),"+f"(d[24]),"+f"(d[25]),"+f"(d[26]),"+f"(d[27]),"+f"(d[28]),"+f"(d[29]),"+f"(d[30]),"+f"(d[31]),"+f"(d[32]),"+f"(d[33]),"+f"(d[34]),"+f"(d[35]),"+f"(d[36]),"+f"(d[37]),"+f"(d[38]),"+f"(d[39]),"+f"(d[40]),"+f"(d[41]),"+f"(d[42]),"+f"(d[43]),"+f"(d[44]),"+f"(d[45]),"+f"(d[46]),"+f"(d[47]),"+f"(d[48]),"+f"(d[49]),"+f"(d[50]),"+f"(d[51]),"+f"(d[52]),"+f"(d[53]),"+f"(d[54]),"+f"(d[55]),"+f"(d[56]),"+f"(d[57]),"+f"(d[58]),"+f"(d[59]),"+f"(d[60]),"+f"(d[61]),"+f"(d[62]),"+f"(d[63]),"+f"(d[64]),"+f"(d[65]),"+f"(d[66]),"+f"(d[67]),"+f"(d[68]),"+f"(d[69]),"+f"(d[70]),"+f"(d[71]),"+f"(d[72]),"+f"(d[73]),"+f"(d[74]),"+f"(d[75]),"+f"(d[76]),"+f"(d[77]),"+f"(d[78]),"+f"(d[79]),"+f"(d[80]),"+f"(d[81]),"+f"(d[82]),"+f"(d[83]),"+f"(d[84]),"+f"(d[85]),"+f"(d[86]),"+f"(d[87]),"+f"(d[88]),"+f"(d[89]),"+f"(d[90]),"+f"(d[91]),"+f"(d[92]),"+f"(d[93]),"+f"(d[94]),"+f"(d[95]),"+f"(d[96]),"+f"(d[97]),"+f"(d[98]),"+f"(d[99]),"+f"(d[100]),"+f"(d[101]),"+f"(d[102]),"+f"(d[103])
  : "r"(a[0]), "r"(a[1]), "r"(a[2]), "r"(a[3]), "l"(db), "r"(sc));
}
template<> __device__ __forceinline__ void wgmma_rs<224>(float* d, const uint32_t* a, uint64_t db, int sc) {
  asm volatile("{.reg .pred p; setp.ne.b32 p, %117, 0;\n"
  "wgmma.mma_async.sync.aligned.m64n224k16.f32.bf16.bf16 {%0,%1,%2,%3,%4,%5,%6,%7,%8,%9,%10,%11,%12,%13,%14,%15,%16,%17,%18,%19,%20,%21,%22,%23,%24,%25,%26,%27,%28,%29,%30,%31,%32,%33,%34,%35,%36,%37,%38,%39,%40,%41,%42,%43,%44,%45,%46,%47,%48,%49,%50,%51,%52,%53,%54,%55,%56,%57,%58,%59,%60,%61,%62,%63,%64,%65,%66,%67,%68,%69,%70,%71,%72,%73,%74,%75,%76,%77,%78,%79,%80,%81,%82,%83,%84,%85,%86,%87,%88,%89,%90,%91,%92,%93,%94,%95,%96,%97,%98,%99,%100,%101,%102,%103,%104,%105,%106,%107,%108,%109,%110,%111}, {%112,%113,%114,%115}, %116, p, 1, 1, 0;}\n"
  : "+f"(d[0]),"+f"(d[1]),"+f"(d[2]),"+f"(d[3]),"+f"(d[4]),"+f"(d[5]),"+f"(d[6]),"+f"(d[7]),"+f"(d[8]),"+f"(d[9]),"+f"(d[10]),"+f"(d[11]),"+f"(d[12]),"+f"(d[13]),"+f"(d[14]),"+f"(d[15]),"+f"(d[16]),"+f"(d[17]),"+f"(d[18]),"+f"(d[19]),"+f"(d[20]),"+f"(d[21]),"+f"(d[22]),"+f"(d[23]),"+f"(d[24]),"+f"(d[25]),"+f"(d[26]),"+f"(d[27]),"+f"(d[28]),"+f"(d[29]),"+f"(d[30]),"+f"(d[31]),"+f"(d[32]),"+f"(d[33]),"+f"(d[34]),"+f"(d[35]),"+f"(d[36]),"+f"(d[37]),"+f"(d[38]),"+f"(d[39]),"+f"(d[40]),"+f"(d[41]),"+f"(d[42]),"+f"(d[43]),"+f"(d[44]),"+f"(d[45]),"+f"(d[46]),"+f"(d[47]),"+f"(d[48]),"+f"(d[49]),"+f"(d[50]),"+f"(d[51]),"+f"(d[52]),"+f"(d[53]),"+f"(d[54]),"+f"(d[55]),"+f"(d[56]),"+f"(d[57]),"+f"(d[58]),"+f"(d[59]),"+f"(d[60]),"+f"(d[61]),"+f"(d[62]),"+f"(d[63]),"+f"(d[64]),"+f"(d[65]),"+f"(d[66]),"+f"(d[67]),"+f"(d[68]),"+f"(d[69]),"+f"(d[70]),"+f"(d[71]),"+f"(d[72]),"+f"(d[73]),"+f"(d[74]),"+f"(d[75]),"+f"(d[76]),"+f"(d[77]),"+f"(d[78]),"+f"(d[79]),"+f"(d[80]),"+f"(d[81]),"+f"(d[82]),"+f"(d[83]),"+f"(d[84]),"+f"(d[85]),"+f"(d[86]),"+f"(d[87]),"+f"(d[88]),"+f"(d[89]),"+f"(d[90]),"+f"(d[91]),"+f"(d[92]),"+f"(d[93]),"+f"(d[94]),"+f"(d[95]),"+f"(d[96]),"+f"(d[97]),"+f"(d[98]),"+f"(d[99]),"+f"(d[100]),"+f"(d[101]),"+f"(d[102]),"+f"(d[103]),"+f"(d[104]),"+f"(d[105]),"+f"(d[106]),"+f"(d[107]),"+f"(d[108]),"+f"(d[109]),"+f"(d[110]),"+f"(d[111])
  : "r"(a[0]), "r"(a[1]), "r"(a[2]), "r"(a[3]), "l"(db), "r"(sc));
}
template<> __device__ __forceinline__ void wgmma_rs<240>(float* d, const uint32_t* a, uint64_t db, int sc) {
  asm volatile("{.reg .pred p; setp.ne.b32 p, %125, 0;\n"
  "wgmma.mma_async.sync.aligned.m64n240k16.f32.bf16.bf16 {%0,%1,%2,%3,%4,%5,%6,%7,%8,%9,%10,%11,%12,%13,%14,%15,%16,%17,%18,%19,%20,%21,%22,%23,%24,%25,%26,%27,%28,%29,%30,%31,%32,%33,%34,%35,%36,%37,%38,%39,%40,%41,%42,%43,%44,%45,%46,%47,%48,%49,%50,%51,%52,%53,%54,%55,%56,%57,%58,%59,%60,%61,%62,%63,%64,%65,%66,%67,%68,%69,%70,%71,%72,%73,%74,%75,%76,%77,%78,%79,%80,%81,%82,%83,%84,%85,%86,%87,%88,%89,%90,%91,%92,%93,%94,%95,%96,%97,%98,%99,%100,%101,%102,%103,%104,%105,%106,%107,%108,%109,%110,%111,%112,%113,%114,%115,%116,%117,%118,%119}, {%120,%121,%122,%123}, %124, p, 1, 1, 0;}\n"
  : "+f"(d[0]),"+f"(d[1]),"+f"(d[2]),"+f"(d[3]),"+f"(d[4]),"+f"(d[5]),"+f"(d[6]),"+f"(d[7]),"+f"(d[8]),"+f"(d[9]),"+f"(d[10]),"+f"(d[11]),"+f"(d[12]),"+f"(d[13]),"+f"(d[14]),"+f"(d[15]),"+f"(d[16]),"+f"(d[17]),"+f"(d[18]),"+f"(d[19]),"+f"(d[20]),"+f"(d[21]),"+f"(d[22]),"+f"(d[23]),"+f"(d[24]),"+f"(d[25]),"+f"(d[26]),"+f"(d[27]),"+f"(d[28]),"+f"(d[29]),"+f"(d[30]),"+f"(d[31]),"+f"(d[32]),"+f"(d[33]),"+f"(d[34]),"+f"(d[35]),"+f"(d[36]),"+f"(d[37]),"+f"(d[38]),"+f"(d[39]),"+f"(d[40]),"+f"(d[41]),"+f"(d[42]),"+f"(d[43]),"+f"(d[44]),"+f"(d[45]),"+f"(d[46]),"+f"(d[47]),"+f"(d[48]),"+f"(d[49]),"+f"(d[50]),"+f"(d[51]),"+f"(d[52]),"+f"(d[53]),"+f"(d[54]),"+f"(d[55]),"+f"(d[56]),"+f"(d[57]),"+f"(d[58]),"+f"(d[59]),"+f"(d[60]),"+f"(d[61]),"+f"(d[62]),"+f"(d[63]),"+f"(d[64]),"+f"(d[65]),"+f"(d[66]),"+f"(d[67]),"+f"(d[68]),"+f"(d[69]),"+f"(d[70]),"+f"(d[71]),"+f"(d[72]),"+f"(d[73]),"+f"(d[74]),"+f"(d[75]),"+f"(d[76]),"+f"(d[77]),"+f"(d[78]),"+f"(d[79]),"+f"(d[80]),"+f"(d[81]),"+f"(d[82]),"+f"(d[83]),"+f"(d[84]),"+f"(d[85]),"+f"(d[86]),"+f"(d[87]),"+f"(d[88]),"+f"(d[89]),"+f"(d[90]),"+f"(d[91]),"+f"(d[92]),"+f"(d[93]),"+f"(d[94]),"+f"(d[95]),"+f"(d[96]),"+f"(d[97]),"+f"(d[98]),"+f"(d[99]),"+f"(d[100]),"+f"(d[101]),"+f"(d[102]),"+f"(d[103]),"+f"(d[104]),"+f"(d[105]),"+f"(d[106]),"+f"(d[107]),"+f"(d[108]),"+f"(d[109]),"+f"(d[110]),"+f"(d[111]),"+f"(d[112]),"+f"(d[113]),"+f"(d[114]),"+f"(d[115]),"+f"(d[116]),"+f"(d[117]),"+f"(d[118]),"+f"(d[119])
  : "r"(a[0]), "r"(a[1]), "r"(a[2]), "r"(a[3]), "l"(db), "r"(sc));
}
template<> __device__ __forceinline__ void wgmma_rs<256>(float* d, const uint32_t* a, uint64_t db, int sc) {
  asm volatile("{.reg .pred p; setp.ne.b32 p, %133, 0;\n"
  "wgmma.mma_async.sync.aligned.m64n256k16.f32.bf16.bf16 {%0,%1,%2,%3,%4,%5,%6,%7,%8,%9,%10,%11,%12,%13,%14,%15,%16,%17,%18,%19,%20,%21,%22,%23,%24,%25,%26,%27,%28,%29,%30,%31,%32,%33,%34,%35,%36,%37,%38,%39,%40,%41,%42,%43,%44,%45,%46,%47,%48,%49,%50,%51,%52,%53,%54,%55,%56,%57,%58,%59,%60,%61,%62,%63,%64,%65,%66,%67,%68,%69,%70,%71,%72,%73,%74,%75,%76,%77,%78,%79,%80,%81,%82,%83,%84,%85,%86,%87,%88,%89,%90,%91,%92,%93,%94,%95,%96,%97,%98,%99,%100,%101,%102,%103,%104,%105,%106,%107,%108,%109,%110,%111,%112,%113,%114,%115,%116,%117,%118,%119,%120,%121,%122,%123,%124,%125,%126,%127}, {%128,%129,%130,%131}, %132, p, 1, 1, 0;}\n"
  : "+f"(d[0]),"+f"(d[1]),"+f"(d[2]),"+f"(d[3]),"+f"(d[4]),"+f"(d[5]),"+f"(d[6]),"+f"(d[7]),"+f"(d[8]),"+f"(d[9]),"+f"(d[10]),"+f"(d[11]),"+f"(d[12]),"+f"(d[13]),"+f"(d[14]),"+f"(d[15]),"+f"(d[16]),"+f"(d[17]),"+f"(d[18]),"+f"(d[19]),"+f"(d[20]),"+f"(d[21]),"+f"(d[22]),"+f"(d[23]),"+f"(d[24]),"+f"(d[25]),"+f"(d[26]),"+f"(d[27]),"+f"(d[28]),"+f"(d[29]),"+f"(d[30]),"+f"(d[31]),"+f"(d[32]),"+f"(d[33]),"+f"(d[34]),"+f"(d[35]),"+f"(d[36]),"+f"(d[37]),"+f"(d[38]),"+f"(d[39]),"+f"(d[40]),"+f"(d[41]),"+f"(d[42]),"+f"(d[43]),"+f"(d[44]),"+f"(d[45]),"+f"(d[46]),"+f"(d[47]),"+f"(d[48]),"+f"(d[49]),"+f"(d[50]),"+f"(d[51]),"+f"(d[52]),"+f"(d[53]),"+f"(d[54]),"+f"(d[55]),"+f"(d[56]),"+f"(d[57]),"+f"(d[58]),"+f"(d[59]),"+f"(d[60]),"+f"(d[61]),"+f"(d[62]),"+f"(d[63]),"+f"(d[64]),"+f"(d[65]),"+f"(d[66]),"+f"(d[67]),"+f"(d[68]),"+f"(d[69]),"+f"(d[70]),"+f"(d[71]),"+f"(d[72]),"+f"(d[73]),"+f"(d[74]),"+f"(d[75]),"+f"(d[76]),"+f"(d[77]),"+f"(d[78]),"+f"(d[79]),"+f"(d[80]),"+f"(d[81]),"+f"(d[82]),"+f"(d[83]),"+f"(d[84]),"+f"(d[85]),"+f"(d[86]),"+f"(d[87]),"+f"(d[88]),"+f"(d[89]),"+f"(d[90]),"+f"(d[91]),"+f"(d[92]),"+f"(d[93]),"+f"(d[94]),"+f"(d[95]),"+f"(d[96]),"+f"(d[97]),"+f"(d[98]),"+f"(d[99]),"+f"(d[100]),"+f"(d[101]),"+f"(d[102]),"+f"(d[103]),"+f"(d[104]),"+f"(d[105]),"+f"(d[106]),"+f"(d[107]),"+f"(d[108]),"+f"(d[109]),"+f"(d[110]),"+f"(d[111]),"+f"(d[112]),"+f"(d[113]),"+f"(d[114]),"+f"(d[115]),"+f"(d[116]),"+f"(d[117]),"+f"(d[118]),"+f"(d[119]),"+f"(d[120]),"+f"(d[121]),"+f"(d[122]),"+f"(d[123]),"+f"(d[124]),"+f"(d[125]),"+f"(d[126]),"+f"(d[127])
  : "r"(a[0]), "r"(a[1]), "r"(a[2]), "r"(a[3]), "l"(db), "r"(sc));
}
template<> __device__ __forceinline__ void wgmma_ss<128>(float* d, uint64_t da, uint64_t db, int sc) {
  asm volatile("{.reg .pred p; setp.ne.b32 p, %66, 0;\n"
  "wgmma.mma_async.sync.aligned.m64n128k16.f32.bf16.bf16 {%0,%1,%2,%3,%4,%5,%6,%7,%8,%9,%10,%11,%12,%13,%14,%15,%16,%17,%18,%19,%20,%21,%22,%23,%24,%25,%26,%27,%28,%29,%30,%31,%32,%33,%34,%35,%36,%37,%38,%39,%40,%41,%42,%43,%44,%45,%46,%47,%48,%49,%50,%51,%52,%53,%54,%55,%56,%57,%58,%59,%60,%61,%62,%63}, %64, %65, p, 1, 1, 0, 1;}\n"
  : "+f"(d[0]),"+f"(d[1]),"+f"(d[2]),"+f"(d[3]),"+f"(d[4]),"+f"(d[5]),"+f"(d[6]),"+f"(d[7]),"+f"(d[8]),"+f"(d[9]),"+f"(d[10]),"+f"(d[11]),"+f"(d[12]),"+f"(d[13]),"+f"(d[14]),"+f"(d[15]),"+f"(d[16]),"+f"(d[17]),"+f"(d[18]),"+f"(d[19]),"+f"(d[20]),"+f"(d[21]),"+f"(d[22]),"+f"(d[23]),"+f"(d[24]),"+f"(d[25]),"+f"(d[26]),"+f"(d[27]),"+f"(d[28]),"+f"(d[29]),"+f"(d[30]),"+f"(d[31]),"+f"(d[32]),"+f"(d[33]),"+f"(d[34]),"+f"(d[35]),"+f"(d[36]),"+f"(d[37]),"+f"(d[38]),"+f"(d[39]),"+f"(d[40]),"+f"(d[41]),"+f"(d[42]),"+f"(d[43]),"+f"(d[44]),"+f"(d[45]),"+f"(d[46]),"+f"(d[47]),"+f"(d[48]),"+f"(d[49]),"+f"(d[50]),"+f"(d[51]),"+f"(d[52]),"+f"(d[53]),"+f"(d[54]),"+f"(d[55]),"+f"(d[56]),"+f"(d[57]),"+f"(d[58]),"+f"(d[59]),"+f"(d[60]),"+f"(d[61]),"+f"(d[62]),"+f"(d[63])
  : "l"(da), "l"(db), "r"(sc));
}
template<> __device__ __forceinline__ void wgmma_ss<192>(float* d, uint64_t da, uint64_t db, int sc) {
  asm volatile("{.reg .pred p; setp.ne.b32 p, %98, 0;\n"
  "wgmma.mma_async.sync.aligned.m64n192k16.f32.bf16.bf16 {%0,%1,%2,%3,%4,%5,%6,%7,%8,%9,%10,%11,%12,%13,%14,%15,%16,%17,%18,%19,%20,%21,%22,%23,%24,%25,%26,%27,%28,%29,%30,%31,%32,%33,%34,%35,%36,%37,%38,%39,%40,%41,%42,%43,%44,%45,%46,%47,%48,%49,%50,%51,%52,%53,%54,%55,%56,%57,%58,%59,%60,%61,%62,%63,%64,%65,%66,%67,%68,%69,%70,%71,%72,%73,%74,%75,%76,%77,%78,%79,%80,%81,%82,%83,%84,%85,%86,%87,%88,%89,%90,%91,%92,%93,%94,%95}, %96, %97, p, 1, 1, 0, 1;}\n"
  : "+f"(d[0]),"+f"(d[1]),"+f"(d[2]),"+f"(d[3]),"+f"(d[4]),"+f"(d[5]),"+f"(d[6]),"+f"(d[7]),"+f"(d[8]),"+f"(d[9]),"+f"(d[10]),"+f"(d[11]),"+f"(d[12]),"+f"(d[13]),"+f"(d[14]),"+f"(d[15]),"+f"(d[16]),"+f"(d[17]),"+f"(d[18]),"+f"(d[19]),"+f"(d[20]),"+f"(d[21]),"+f"(d[22]),"+f"(d[23]),"+f"(d[24]),"+f"(d[25]),"+f"(d[26]),"+f"(d[27]),"+f"(d[28]),"+f"(d[29]),"+f"(d[30]),"+f"(d[31]),"+f"(d[32]),"+f"(d[33]),"+f"(d[34]),"+f"(d[35]),"+f"(d[36]),"+f"(d[37]),"+f"(d[38]),"+f"(d[39]),"+f"(d[40]),"+f"(d[41]),"+f"(d[42]),"+f"(d[43]),"+f"(d[44]),"+f"(d[45]),"+f"(d[46]),"+f"(d[47]),"+f"(d[48]),"+f"(d[49]),"+f"(d[50]),"+f"(d[51]),"+f"(d[52]),"+f"(d[53]),"+f"(d[54]),"+f"(d[55]),"+f"(d[56]),"+f"(d[57]),"+f"(d[58]),"+f"(d[59]),"+f"(d[60]),"+f"(d[61]),"+f"(d[62]),"+f"(d[63]),"+f"(d[64]),"+f"(d[65]),"+f"(d[66]),"+f"(d[67]),"+f"(d[68]),"+f"(d[69]),"+f"(d[70]),"+f"(d[71]),"+f"(d[72]),"+f"(d[73]),"+f"(d[74]),"+f"(d[75]),"+f"(d[76]),"+f"(d[77]),"+f"(d[78]),"+f"(d[79]),"+f"(d[80]),"+f"(d[81]),"+f"(d[82]),"+f"(d[83]),"+f"(d[84]),"+f"(d[85]),"+f"(d[86]),"+f"(d[87]),"+f"(d[88]),"+f"(d[89]),"+f"(d[90]),"+f"(d[91]),"+f"(d[92]),"+f"(d[93]),"+f"(d[94]),"+f"(d[95])
  : "l"(da), "l"(db), "r"(sc));
}
template<> __device__ __forceinline__ void wgmma_ss<256>(float* d, uint64_t da, uint64_t db, int sc) {
  asm volatile("{.reg .pred p; setp.ne.b32 p, %130, 0;\n"
  "wgmma.mma_async.sync.aligned.m64n256k16.f32.bf16.bf16 {%0,%1,%2,%3,%4,%5,%6,%7,%8,%9,%10,%11,%12,%13,%14,%15,%16,%17,%18,%19,%20,%21,%22,%23,%24,%25,%26,%27,%28,%29,%30,%31,%32,%33,%34,%35,%36,%37,%38,%39,%40,%41,%42,%43,%44,%45,%46,%47,%48,%49,%50,%51,%52,%53,%54,%55,%56,%57,%58,%59,%60,%61,%62,%63,%64,%65,%66,%67,%68,%69,%70,%71,%72,%73,%74,%75,%76,%77,%78,%79,%80,%81,%82,%83,%84,%85,%86,%87,%88,%89,%90,%91,%92,%93,%94,%95,%96,%97,%98,%99,%100,%101,%102,%103,%104,%105,%106,%107,%108,%109,%110,%111,%112,%113,%114,%115,%116,%117,%118,%119,%120,%121,%122,%123,%124,%125,%126,%127}, %128, %129, p, 1, 1, 0, 1;}\n"
  : "+f"(d[0]),"+f"(d[1]),"+f"(d[2]),"+f"(d[3]),"+f"(d[4]),"+f"(d[5]),"+f"(d[6]),"+f"(d[7]),"+f"(d[8]),"+f"(d[9]),"+f"(d[10]),"+f"(d[11]),"+f"(d[12]),"+f"(d[13]),"+f"(d[14]),"+f"(d[15]),"+f"(d[16]),"+f"(d[17]),"+f"(d[18]),"+f"(d[19]),"+f"(d[20]),"+f"(d[21]),"+f"(d[22]),"+f"(d[23]),"+f"(d[24]),"+f"(d[25]),"+f"(d[26]),"+f"(d[27]),"+f"(d[28]),"+f"(d[29]),"+f"(d[30]),"+f"(d[31]),"+f"(d[32]),"+f"(d[33]),"+f"(d[34]),"+f"(d[35]),"+f"(d[36]),"+f"(d[37]),"+f"(d[38]),"+f"(d[39]),"+f"(d[40]),"+f"(d[41]),"+f"(d[42]),"+f"(d[43]),"+f"(d[44]),"+f"(d[45]),"+f"(d[46]),"+f"(d[47]),"+f"(d[48]),"+f"(d[49]),"+f"(d[50]),"+f"(d[51]),"+f"(d[52]),"+f"(d[53]),"+f"(d[54]),"+f"(d[55]),"+f"(d[56]),"+f"(d[57]),"+f"(d[58]),"+f"(d[59]),"+f"(d[60]),"+f"(d[61]),"+f"(d[62]),"+f"(d[63]),"+f"(d[64]),"+f"(d[65]),"+f"(d[66]),"+f"(d[67]),"+f"(d[68]),"+f"(d[69]),"+f"(d[70]),"+f"(d[71]),"+f"(d[72]),"+f"(d[73]),"+f"(d[74]),"+f"(d[75]),"+f"(d[76]),"+f"(d[77]),"+f"(d[78]),"+f"(d[79]),"+f"(d[80]),"+f"(d[81]),"+f"(d[82]),"+f"(d[83]),"+f"(d[84]),"+f"(d[85]),"+f"(d[86]),"+f"(d[87]),"+f"(d[88]),"+f"(d[89]),"+f"(d[90]),"+f"(d[91]),"+f"(d[92]),"+f"(d[93]),"+f"(d[94]),"+f"(d[95]),"+f"(d[96]),"+f"(d[97]),"+f"(d[98]),"+f"(d[99]),"+f"(d[100]),"+f"(d[101]),"+f"(d[102]),"+f"(d[103]),"+f"(d[104]),"+f"(d[105]),"+f"(d[106]),"+f"(d[107]),"+f"(d[108]),"+f"(d[109]),"+f"(d[110]),"+f"(d[111]),"+f"(d[112]),"+f"(d[113]),"+f"(d[114]),"+f"(d[115]),"+f"(d[116]),"+f"(d[117]),"+f"(d[118]),"+f"(d[119]),"+f"(d[120]),"+f"(d[121]),"+f"(d[122]),"+f"(d[123]),"+f"(d[124]),"+f"(d[125]),"+f"(d[126]),"+f"(d[127])
  : "l"(da), "l"(db), "r"(sc));
}

__device__ __forceinline__ void wg_fence() { asm volatile("wgmma.fence.sync.aligned;" ::: "memory"); }
__device__ __forceinline__ void wg_commit() { asm volatile("wgmma.commit_group.sync.aligned;" ::: "memory"); }
template <int N> __device__ __forceinline__ void wg_wait() { asm volatile("wgmma.wait_group.sync.aligned %0;" ::"n"(N) : "memory"); }
__device__ __forceinline__ uint64_t mkdesc(uint32_t addr, uint32_t lbo, uint32_t sbo, uint32_t swz) {
  return (uint64_t)((addr & 0x3FFFF) >> 4) | ((uint64_t)(lbo >> 4) << 16) | ((uint64_t)(sbo >> 4) << 32) | ((uint64_t)swz << 62);
}
__device__ __forceinline__ void mbar_init(uint32_t a, uint32_t c) { asm volatile("mbarrier.init.shared.b64 [%0], %1;" ::"r"(a), "r"(c) : "memory"); }
__device__ __forceinline__ void mbar_expect_tx(uint32_t a, uint32_t b) { asm volatile("mbarrier.arrive.expect_tx.shared.b64 _, [%0], %1;" ::"r"(a), "r"(b) : "memory"); }
__device__ __forceinline__ void mbar_arrive(uint32_t a) { asm volatile("mbarrier.arrive.shared.b64 _, [%0];" ::"r"(a) : "memory"); }
__device__ __forceinline__ void mbar_arrive_c(uint32_t a, uint32_t n) { asm volatile("mbarrier.arrive.shared::cluster.b64 _, [%0], %1;" ::"r"(a), "r"(n) : "memory"); }
__device__ __forceinline__ void mbar_wait(uint32_t a, uint32_t parity) {
  asm volatile("{.reg .pred p, q; .reg .u32 n; mov.u32 n, 0;\n"
               "W: mbarrier.try_wait.parity.shared.b64 p, [%0], %1;\n"
               "add.u32 n, n, 1; setp.eq.u32 q, n, 0x100000; @q trap; @!p bra.uni W;}" ::"r"(a), "r"(parity) : "memory");
}
__device__ __forceinline__ uint32_t mapa(uint32_t a, uint32_t rank) { uint32_t r; asm("mapa.shared::cluster.u32 %0, %1, %2;" : "=r"(r) : "r"(a), "r"(rank)); return r; }
__device__ __forceinline__ void tma2d(uint32_t dst, const CUtensorMap* m, uint32_t bar, int c0, int c1) {
  asm volatile("cp.async.bulk.tensor.2d.shared::cluster.global.mbarrier::complete_tx::bytes [%0], [%1, {%3,%4}], [%2];"
               ::"r"(dst), "l"(m), "r"(bar), "r"(c0), "r"(c1) : "memory");
}
__device__ __forceinline__ void tma3d(uint32_t dst, const CUtensorMap* m, uint32_t bar, int c0, int c1, int c2) {
  asm volatile("cp.async.bulk.tensor.3d.shared::cluster.global.mbarrier::complete_tx::bytes [%0], [%1, {%3,%4,%5}], [%2];"
               ::"r"(dst), "l"(m), "r"(bar), "r"(c0), "r"(c1), "r"(c2) : "memory");
}
__device__ __forceinline__ void tma3d_mc(uint32_t dst, const CUtensorMap* m, uint32_t bar, int c0, int c1, int c2) {
  asm volatile("cp.async.bulk.tensor.3d.shared::cluster.global.mbarrier::complete_tx::bytes.multicast::cluster [%0], [%1, {%3,%4,%5}], [%2], %6;"
               ::"r"(dst), "l"(m), "r"(bar), "r"(c0), "r"(c1), "r"(c2), "h"((uint16_t)3) : "memory");
}
__device__ __forceinline__ void tma_store(const CUtensorMap* m, uint32_t src, int c0, int c1) {
  asm volatile("cp.async.bulk.tensor.2d.global.shared::cta.bulk_group [%0, {%2,%3}], [%1];" ::"l"(m), "r"(src), "r"(c0), "r"(c1) : "memory");
}
__device__ __forceinline__ void bulk_commit() { asm volatile("cp.async.bulk.commit_group;" ::: "memory"); }
__device__ __forceinline__ void bulk_wait_read() { asm volatile("cp.async.bulk.wait_group.read 0;" ::: "memory"); }
__device__ __forceinline__ void bulk_wait() { asm volatile("cp.async.bulk.wait_group 0;" ::: "memory"); }
__device__ __forceinline__ void bulk_g2s(uint32_t dst, const void* src, uint32_t bytes, uint32_t bar) {
  asm volatile("cp.async.bulk.shared::cluster.global.mbarrier::complete_tx::bytes [%0], [%1], %2, [%3];"
               ::"r"(dst), "l"(src), "r"(bytes), "r"(bar) : "memory");
}
__device__ __forceinline__ void prefetch_l2(const void* src, uint32_t bytes) {
  asm volatile("cp.async.bulk.prefetch.L2.global [%0], %1;" ::"l"(src), "r"(bytes) : "memory");
}
__device__ __forceinline__ void prefetch_tmap(const CUtensorMap* m) { asm volatile("prefetch.tensormap [%0];" ::"l"(m) : "memory"); }
__device__ __forceinline__ void fence_async_smem() { asm volatile("fence.proxy.async.shared::cta;" ::: "memory"); }
__device__ __forceinline__ void fence_async_global() { asm volatile("fence.proxy.async.global;" ::: "memory"); }
__device__ __forceinline__ void bar_sync(int id, int n) { asm volatile("bar.sync %0, %1;" ::"r"(id), "r"(n) : "memory"); }
__device__ __forceinline__ void cluster_wait() { asm volatile("barrier.cluster.wait.aligned;" ::: "memory"); }
__device__ __forceinline__ uint32_t lds32(uint32_t a) { uint32_t v; asm volatile("ld.volatile.shared.b32 %0,[%1];" : "=r"(v) : "r"(a)); return v; }
__device__ __forceinline__ uint2 lds64(uint32_t a) { uint2 v; asm volatile("ld.shared.v2.b32 {%0,%1},[%2];" : "=r"(v.x), "=r"(v.y) : "r"(a) : "memory"); return v; }
__device__ __forceinline__ uint4 lds128(uint32_t a) { uint4 v; asm volatile("ld.shared.v4.b32 {%0,%1,%2,%3},[%4];" : "=r"(v.x), "=r"(v.y), "=r"(v.z), "=r"(v.w) : "r"(a) : "memory"); return v; }
__device__ __forceinline__ void sts128(uint32_t a, uint32_t x, uint32_t y, uint32_t z, uint32_t w) { asm volatile("st.shared.v4.b32 [%0],{%1,%2,%3,%4};" ::"r"(a), "r"(x), "r"(y), "r"(z), "r"(w) : "memory"); }
__device__ __forceinline__ void stsm4(uint32_t a, uint32_t x, uint32_t y, uint32_t z, uint32_t w) { asm volatile("stmatrix.sync.aligned.m8n8.x4.shared.b16 [%0],{%1,%2,%3,%4};" ::"r"(a), "r"(x), "r"(y), "r"(z), "r"(w) : "memory"); }
__device__ __forceinline__ void st_async128(uint32_t a, uint32_t bar, uint32_t x, uint32_t y, uint32_t z, uint32_t w) {
  asm volatile("st.async.weak.shared::cluster.mbarrier::complete_tx::bytes.v4.b32 [%0],{%2,%3,%4,%5},[%1];" ::"r"(a), "r"(bar), "r"(x), "r"(y), "r"(z), "r"(w) : "memory");
}
__device__ __forceinline__ uint32_t packbf(float lo, float hi) { uint32_t r; asm("cvt.rn.bf16x2.f32 %0, %1, %2;" : "=r"(r) : "f"(hi), "f"(lo)); return r; }
__device__ __forceinline__ uint32_t packbf_relu(float lo, float hi) { uint32_t r; asm("cvt.rn.relu.bf16x2.f32 %0, %1, %2;" : "=r"(r) : "f"(hi), "f"(lo)); return r; }
__device__ __forceinline__ uint32_t bmul2(uint32_t a, uint32_t b) { uint32_t r; asm("mul.rn.bf16x2 %0, %1, %2;" : "=r"(r) : "r"(a), "r"(b)); return r; }
__device__ __forceinline__ uint32_t bfma2(uint32_t a, uint32_t b, uint32_t c) { uint32_t r; asm("fma.rn.bf16x2 %0, %1, %2, %3;" : "=r"(r) : "r"(a), "r"(b), "r"(c)); return r; }
__device__ __forceinline__ uint32_t badd2(uint32_t a, uint32_t b) { uint32_t r; asm("add.rn.bf16x2 %0, %1, %2;" : "=r"(r) : "r"(a), "r"(b)); return r; }
__device__ __forceinline__ uint32_t bsub2(uint32_t a, uint32_t b) { uint32_t r; asm("sub.rn.bf16x2 %0, %1, %2;" : "=r"(r) : "r"(a), "r"(b)); return r; }
__device__ __forceinline__ float bflo(uint32_t v) { return __uint_as_float(v << 16); }
__device__ __forceinline__ float bfhi(uint32_t v) { return __uint_as_float(v & 0xffff0000u); }
__device__ __forceinline__ uint32_t ldg_relaxed(const uint32_t* p) { uint32_t v; asm volatile("ld.relaxed.gpu.global.b32 %0,[%1];" : "=r"(v) : "l"(p) : "memory"); return v; }
__device__ __forceinline__ uint4 ldg_b128(const void* p) {
  uint4 v;
  asm volatile("{.reg .b128 r; .reg .b64 a, b; ld.relaxed.gpu.global.b128 r, [%4]; mov.b128 {a, b}, r; mov.b64 {%0,%1}, a; mov.b64 {%2,%3}, b;}"
               : "=r"(v.x), "=r"(v.y), "=r"(v.z), "=r"(v.w) : "l"(p) : "memory");
  return v;
}
__device__ __forceinline__ void stg_b128(void* p, uint32_t x, uint32_t y, uint32_t z, uint32_t w) {
  asm volatile("{.reg .b128 r; .reg .b64 a, b; mov.b64 a, {%1,%2}; mov.b64 b, {%3,%4}; mov.b128 r, {a, b}; st.relaxed.gpu.global.b128 [%0], r;}"
               ::"l"(p), "r"(x), "r"(y), "r"(z), "r"(w) : "memory");
}
__device__ __forceinline__ uint4 ldg_cg4(const void* p) { uint4 v; asm volatile("ld.global.cg.v4.b32 {%0,%1,%2,%3},[%4];" : "=r"(v.x), "=r"(v.y), "=r"(v.z), "=r"(v.w) : "l"(p) : "memory"); return v; }
__device__ __forceinline__ float2 ldg_cg2f(const void* p) { float2 v; asm volatile("ld.global.cg.v2.f32 {%0,%1},[%2];" : "=f"(v.x), "=f"(v.y) : "l"(p) : "memory"); return v; }
__device__ __forceinline__ void stg128(void* p, uint32_t x, uint32_t y, uint32_t z, uint32_t w) { asm volatile("st.global.v4.b32 [%0],{%1,%2,%3,%4};" ::"l"(p), "r"(x), "r"(y), "r"(z), "r"(w) : "memory"); }
__device__ __forceinline__ void signal(uint32_t* cnt) { asm volatile("red.release.gpu.global.add.u32 [%0], 1;" ::"l"(cnt) : "memory"); }
__device__ __forceinline__ void wait_count(const uint32_t* cnt, uint32_t target) {
  int it = 0;
  while (true) {
    uint32_t v;
    asm volatile("ld.acquire.gpu.global.b32 %0,[%1];" : "=r"(v) : "l"(cnt) : "memory");
    if ((int)(v - target) >= 0) break;
    __nanosleep(32);
    if (++it > (1 << 21)) __trap();
  }
}

template <int LO, int HI> __device__ __forceinline__ void rename(float* d) {
#pragma unroll
  for (int i = LO; i < HI; i++) { float e; asm volatile("mov.b32 %0, %1;" : "=f"(e) : "f"(d[i])); d[i] = e; }
}
template <int M> __device__ __forceinline__ void drain4(const float* d, uint32_t ya, uint32_t ybar, bool lane0) {
  uint32_t r[4];
#pragma unroll
  for (int q = 0; q < 4; q++) {
    const int mu = M + q;
    float v0 = d[4 * mu], v1 = d[4 * mu + 1];
    if (mu > 0) { v0 += d[4 * mu - 2]; v1 += d[4 * mu - 1]; }
    r[q] = packbf(v0, v1);
  }
  asm volatile("stmatrix.sync.aligned.m8n8.x4.trans.shared.b16 [%0],{%1,%2,%3,%4};" ::"r"(ya + M * 128), "r"(r[0]), "r"(r[1]), "r"(r[2]), "r"(r[3]) : "memory");
  if constexpr ((M & 7) == 4) {
    __syncwarp();
    if (lane0) mbar_arrive(ybar + (M >> 3) * 8);
  }
}
__device__ __forceinline__ void lda(uint32_t* a, uint32_t ua) { a[0] = lds32(ua); a[1] = lds32(ua + 128); a[2] = lds32(ua - 16); a[3] = lds32(ua + 112); }
template <int P, bool FIRST> struct Pass {
  static __device__ __forceinline__ void run(float* d, uint32_t (*a)[4], uint32_t ua, uint64_t db, uint32_t ya, uint32_t ubar, uint32_t ybar, bool lane0) {
    if constexpr (P > 0) rename<8 * (P - 1), 128>(d);
    wg_fence();
    wgmma_rs<256 - 16 * P>(d + 8 * P, a[P & 1], db, P != 0);
    wg_commit();
    if constexpr (P < 15) {
      if constexpr (FIRST && (P & 1)) mbar_wait(ubar + 8 * ((P + 1) / 2), 0);
      lda(a[(P + 1) & 1], ua + (P + 1) * 256);
    }
    if constexpr (P >= 3 && (P & 1)) drain4<2 * P - 6>(d, ya, ybar, lane0);
    wg_wait<0>();
    if constexpr (P < 15) Pass<P + 1, FIRST>::run(d, a, ua, db, ya, ubar, ybar, lane0);
    else { rename<120, 128>(d); drain4<28>(d, ya, ybar, lane0); }
  }
};

__device__ __forceinline__ uint32_t off_T(int r) { return r == 0 ? OFF_T0 : r == 1 ? OFF_T1 : r == 2 ? OFF_T2 : OFF_T3; }
__device__ __forceinline__ uint32_t off_Y(int r) { return r == 1 ? OFF_KVA : r == 2 ? OFF_KVB : OFF_X; }
__device__ __forceinline__ uint32_t off_kv(int st) {
  const int sl = st < 5 ? st : st - 5;
  return sl == 0 ? 0 : sl < 3 ? OFF_KVA + (sl - 1) * KV_SLOT : OFF_KVB + (sl - 3) * KV_SLOT;
}
template <bool FIRST>
__device__ __forceinline__ void conv_round(uint32_t sb, int r, int wg, int w, int lane) {
  float d[128];
  uint32_t a[2][4];
  const int g = lane >> 2, t = lane & 3;
  const uint32_t bar = sb + OFF_BAR, tb = sb + off_T(r);
  const uint32_t ua = tb + wg * UT_SIZE + ((g & 1) ? 0 : UT_COPY) + ((g >> 1) + 8 * w + 8 - t) * 4;
  const uint64_t db = mkdesc(tb + 2 * UT_SIZE + wg * KT_SIZE, 16, 128, 0);
  const uint32_t yb = sb + off_Y(r) + wg * YBUF + w * YW;
  mbar_wait(bar + 8 * (FIRST ? B_UFULL : r == 3 ? B_ZDONE : B_UREST), 0);
  lda(a[0], ua);
  if (lane < 2 * w) sts128(yb + lane * 16, 0, 0, 0, 0);
  mbar_wait(bar + 8 * (B_KFULL + 2 * r + wg), 0);
  if (threadIdx.x == 0) TS(1 + r);
  Pass<0, FIRST>::run(d, a, ua, db, yb + (2 * w + lane) * 16, bar + 8 * B_UFULL, bar + 8 * (B_YFULL + 4 * r), lane == 0);
}
__device__ __forceinline__ uint32_t off_act(int tile, int wg, int b) {
  return b < 2 ? OFF_X + wg * 16384 + b * 8192 : tile == 0 ? (2 * wg + b - 2) * 49152 + 40960 : 180224 + wg * 8192;
}

template <int NT>
__device__ __forceinline__ void mainloop(float* acc, uint32_t sb, int wg, bool rel, int nkb) {
  const uint32_t bar = sb + OFF_BAR;
  const uint64_t da0 = mkdesc(sb + wg * 8192, 16, 1024, 1), db0 = mkdesc(sb + 16384, 8192, 1024, 1);
  mbar_wait(bar + 8 * B_FULL, 0);
  wg_fence();
#pragma unroll
  for (int kk = 0; kk < 4; kk++) wgmma_ss<NT>(acc, da0 + kk * 2, db0 + kk * 128, kk != 0);
  wg_commit();
#pragma unroll 1
  for (int kb = 1; kb < nkb; kb++) {
    const int s = kb & 3;
    mbar_wait(bar + 8 * (B_FULL + s), (kb >> 2) & 1);
    const uint64_t da = da0 + s * 3072, db = db0 + s * 3072;
    wg_fence();
#pragma unroll
    for (int kk = 0; kk < 4; kk++) wgmma_ss<NT>(acc, da + kk * 2, db + kk * 128, 1);
    wg_commit();
    wg_wait<1>();
    if (rel) mbar_arrive(bar + 8 * (B_EMPTY + ((kb - 1) & 3)));
  }
}
template <int NT>
__device__ __forceinline__ void gemm1_main(float* out, uint32_t sb, int wg, bool rel, uint32_t hs, bool t3) {
  const uint32_t bar = sb + OFF_BAR;
  float acc[NT / 2];
  mainloop<NT>(acc, sb, wg, rel, 16);
  mbar_wait(bar + 8 * B_CSFULL, NT == 256 ? 0 : 1);
  uint32_t a[4] = {lds32(hs), lds32(hs + 128), 0, 0};
  if (t3) a[0] = a[1] = 0;
  wg_fence();
  wgmma_rs<NT>(acc, a, mkdesc(sb + OFF_X + wg * 16384, 0, 128, 0), 1);
  wg_commit();
  wg_wait<1>();
  if (rel) mbar_arrive(bar + 8 * (B_EMPTY + 3));
  wg_wait<0>();
#pragma unroll
  for (int i = 0; i < NT / 2; i++) asm volatile("mov.b32 %0, %1;" : "=f"(out[i]) : "f"(acc[i]));
}

__global__ void __cluster_dims__(2, 1, 1) __launch_bounds__(NTHREADS, 1) fused_kernel(const __grid_constant__ Params P) {
  extern __shared__ __align__(1024) unsigned char smem[];
  const uint32_t sb = (uint32_t)__cvta_generic_to_shared(smem);
  const uint32_t bar = sb + OFF_BAR;
  const int tid = threadIdx.x, warp = __shfl_sync(0xffffffffu, tid >> 5, 0), lane = tid & 31;
  const int c = blockIdx.x, rank = c & 1, m = (c >> 1) & 15, j = 2 * (c >> 5) + rank;

  if (lane == 0) {
    if (warp == 8) {
      TS(0);
      mbar_init(bar + 8 * B_KVFULL, 1); mbar_init(bar + 8 * B_KFULL, 2); mbar_init(bar + 8 * (B_KFULL + 1), 2);
      mbar_expect_tx(bar + 8 * B_KVFULL, KV_SLOT);
#pragma unroll 1
      for (int i = 0; i < 2; i++) {
        tma3d(sb + i * KV_BOX, &P.tm_k, bar + 8 * B_KVFULL, 8 * (c & ~1), 16 * i - 1, 0);
        tma3d(sb + (2 + i) * KV_BOX, &P.tm_v, bar + 8 * B_KVFULL, 8 * (c & ~1), 16 * i - 1, 0);
      }
#pragma unroll 1
      for (int i = 0; i < 2; i++) {
        mbar_expect_tx(bar + 8 * (B_KFULL + i), 4080);
        bulk_g2s(sb + OFF_T0 + 2 * UT_SIZE + i * KT_SIZE + 32, P.ssm_k + (size_t)(8 * c + i) * S + 8, 4080, bar + 8 * (B_KFULL + i));
      }
    } else if (warp < 8) {
      const uint32_t cnt = (0x18211881u >> (4 * warp)) & 15;
#pragma unroll
      for (int i = 0; i < 8; i++) mbar_init(bar + 8 * (16 + 8 * warp + i), cnt);
      if (warp == 4) mbar_expect_tx(bar + 8 * B_RECV, 32768);
    } else if (warp == 9) {
#pragma unroll
      for (int i = 1; i < 8; i++) { mbar_init(bar + 8 * (B_KVFULL + i), 1); mbar_expect_tx(bar + 8 * (B_KVFULL + i), KV_SLOT); }
    } else if (warp == 10) {
#pragma unroll
      for (int i = 2; i < 8; i++) mbar_init(bar + 8 * (B_KFULL + i), 2);
    }
    asm volatile("fence.mbarrier_init.release.cluster;" ::: "memory");
  }
  if (warp == 11 && lane < 16) sts128(sb + off_T(lane >> 2) + (lane & 3) * UT_COPY, 0, 0, 0, 0);
  __syncthreads();
  asm volatile("barrier.cluster.arrive.relaxed.aligned;" ::: "memory");

  if (warp < 8) {
    if (tid == 32) TS(46);
    if (warp == 0 && lane < 8) {
      const uint4 v = __ldg((const uint4*)(P.ssm_k + (size_t)(8 * c + lane) * S));
      const float k0 = bflo(v.x) + __bfloat162float(P.ssm_D[8 * c + lane]);
      const uint32_t kt = sb + off_T(lane >> 1) + 2 * UT_SIZE + (lane & 1) * KT_SIZE;
      sts128(kt, 0, 0, 0, 0);
      sts128(kt + 16, (v.x & 0xffff0000u) | (packbf(k0, 0.f) & 0xffffu), v.y, v.z, v.w);
      fence_async_smem();
      mbar_arrive(bar + 8 * (B_KFULL + lane));
    }
    __syncwarp();
    cluster_wait();
    const int wg = warp >> 2, w = warp & 3, g = lane >> 2, t = lane & 3;
    conv_round<true>(sb, 0, wg, w, lane);
#pragma unroll 1
    for (int r = 1; r < 4; r++) conv_round<false>(sb, r, wg, w, lane);
    if (tid == 0) TS(5);
    const bool rel = lane == 0 && w == 0;
    const int id = lane >> 3, srow = 16 * w + (lane & 7) + 8 * (id & 1);
    const uint32_t soff = srow * 128, sx = ((id >> 1) ^ (srow & 7)) << 4;
    const uint32_t hs = sb + OFF_HS + (64 * wg + 16 * w + g) * 16;
#pragma unroll 1
    for (int tile = 0; tile < 2; tile++) {
      float acc[128];
      if (tile == 0) {
        gemm1_main<256>(acc, sb, wg, rel, hs + 4 * t, t == 3);
      } else {
        gemm1_main<192>(acc, sb, wg, rel, hs + 4 * t, t == 3);
#pragma unroll
        for (int i = 96; i < 128; i++) asm volatile("mov.b32 %0, 0;" : "=f"(acc[i]));
      }
      if (tid == 0) TS(44 + tile);
#pragma unroll
      for (int b = 0; b < 4; b++) {
        if (b == 3 && tile) break;
        if (b == 2) mbar_wait(bar + 8 * (B_EMPTY + 3), 1);
        const uint32_t dst = sb + off_act(tile, wg, b) + soff;
#pragma unroll
        for (int p = 0; p < 4; p++) {
          uint32_t o[4];
#pragma unroll
          for (int e = 0; e < 4; e++) {
            const uint32_t u = packbf_relu(acc[32 * b + 8 * p + 2 * e], acc[32 * b + 8 * p + 2 * e + 1]);
            o[e] = bmul2(u, u);
          }
          stsm4(dst + (sx ^ (p << 5)), o[0], o[1], o[2], o[3]);
        }
      }
      fence_async_smem();
      __syncwarp();
      if (lane == 0) mbar_arrive(bar + 8 * (B_ADONE + tile));
      if (tid == 0) TS(6 + tile);
    }
    {
      float acc[64], res[64];
      {
        float big[128];
        mainloop<256>(big, sb, wg, rel, 26);
        wg_wait<0>();
#pragma unroll
        for (int i = 0; i < 64; i++) { asm volatile("mov.b32 %0, %1;" : "=f"(acc[i]) : "f"(big[i])); asm volatile("mov.b32 %0, %1;" : "=f"(res[i]) : "f"(big[64 + i])); }
      }
      if (rel) { mbar_arrive(bar + 8 * (B_EMPTY + 1)); mbar_arrive_c(mapa(bar + 8 * B_PEER, rank ^ 1), 1); }
      if (tid == 0) TS(47);
      const uint64_t da0 = mkdesc(sb + wg * 8192, 16, 1024, 1), db0 = mkdesc(sb + 16384, 8192, 1024, 1);
      const uint32_t ro = (2 + wg) * 49152 + 32768 + (tid & 127) * 16;
#pragma unroll
      for (int kb = 26; kb < 30; kb++) {
        const int s = kb & 3;
        mbar_wait(bar + 8 * (B_FULL + s), (kb >> 2) & 1);
        wg_fence();
#pragma unroll
        for (int kk = 0; kk < 4; kk++) wgmma_ss<128>(acc, da0 + s * 3072 + kk * 2, db0 + s * 3072 + kk * 128, 1);
        wg_commit();
        if (kb == 27 || kb == 28) {
          const uint32_t pb = mapa(sb, rank ^ 1);
          if (kb == 27) mbar_wait(bar + 8 * B_PEER, 0);
#pragma unroll
          for (int i = 4 * (kb - 27); i < 4 * (kb - 27) + 4; i++)
            st_async128(pb + ro + i * 2048, pb + OFF_BAR + 8 * B_RECV, packbf(res[8 * i], res[8 * i + 1]), packbf(res[8 * i + 2], res[8 * i + 3]),
                        packbf(res[8 * i + 4], res[8 * i + 5]), packbf(res[8 * i + 6], res[8 * i + 7]));
        }
      }
      const float sc0 = __uint_as_float(lds32(hs + 12)), sc1 = __uint_as_float(lds32(hs + 140));
      {
        const uint32_t* b2p = (const uint32_t*)(P.b2 + 128 * j) + t;
        uint32_t hb[32];
#pragma unroll
        for (int mu = 0; mu < 16; mu++) hb[2 * mu] = __ldg(b2p + 4 * mu);
        mbar_wait(bar + 8 * B_HRES, 0);
#pragma unroll
        for (int h = 1; h >= 0; h--) {
          const int row = 64 * wg + 16 * w + 8 * h + g;
          const uint32_t la = sb + OFF_X + row * 256 + t * 64;
          const int sw = (2 * row + (t >> 1)) & 3;
#pragma unroll
          for (int cc = 0; cc < 4; cc++) {
            const uint4 v = lds128(la + ((cc ^ sw) << 4));
            hb[8 * cc + h] = badd2(v.x, hb[8 * cc]); hb[8 * cc + 2 + h] = badd2(v.y, hb[8 * cc + 2]);
            hb[8 * cc + 4 + h] = badd2(v.z, hb[8 * cc + 4]); hb[8 * cc + 6 + h] = badd2(v.w, hb[8 * cc + 6]);
          }
        }
        mbar_wait(bar + 8 * B_RECV, 0);
#pragma unroll
        for (int i = 0; i < 8; i++) {
          const uint4 v = lds128(sb + ro + i * 2048);
          const uint32_t vv[4] = {v.x, v.y, v.z, v.w};
#pragma unroll
          for (int e = 0; e < 4; e++) {
            const float sc = (e & 1) ? sc1 : sc0;
            res[8 * i + 2 * e] = fmaf(bflo(vv[e]), sc, bflo(hb[4 * i + e]));
            res[8 * i + 2 * e + 1] = fmaf(bfhi(vv[e]), sc, bfhi(hb[4 * i + e]));
          }
        }
      }
      bar_sync(3 + wg, 128);
      wg_wait<0>();
      rename<0, 64>(acc);
      if (tid == 0) TS(8);
      const uint32_t ob = sb + OFF_X + wg * 16384;
#pragma unroll
      for (int mu = 0; mu < 16; mu += 2) {
        const float* a = acc + 4 * mu;
        const float* q = res + 4 * mu;
        stsm4(ob + (mu >> 3) * 8192 + soff + (sx ^ ((mu & 6) << 4)),
              packbf(fmaf(a[0], sc0, q[0]), fmaf(a[1], sc0, q[1])), packbf(fmaf(a[2], sc1, q[2]), fmaf(a[3], sc1, q[3])),
              packbf(fmaf(a[4], sc0, q[4]), fmaf(a[5], sc0, q[5])), packbf(fmaf(a[6], sc1, q[6]), fmaf(a[7], sc1, q[7])));
      }
      fence_async_smem();
      bar_sync(3 + wg, 128);
      if (w == 0 && lane == 0) {
        tma_store(&P.tm_out, ob, 128 * j, 128 * m + 64 * wg);
        tma_store(&P.tm_out, ob + 8192, 128 * j + 64, 128 * m + 64 * wg);
        bulk_commit();
        bulk_wait_read();
        if (tid == 0) TS(9);
      }
    }
  } else if (warp == 8) {
    cluster_wait();
    if (lane == 0) {
#pragma unroll 1
      for (int i = 1; i < 8; i++) {
        if (i >= 5) mbar_wait(bar + 8 * (B_KVFREE + i - 5), 0);
        const uint32_t dst = sb + off_kv(i) + rank * KV_BOX;
        tma3d_mc(dst, &P.tm_k, bar + 8 * (B_KVFULL + i), 8 * (c & ~1), 32 * i + 16 * rank - 1, 0);
        tma3d_mc(dst + 2 * KV_BOX, &P.tm_v, bar + 8 * (B_KVFULL + i), 8 * (c & ~1), 32 * i + 16 * rank - 1, 0);
      }
      const uint32_t epoch = ldg_relaxed(g_epoch + c) + 1;
      mbar_wait(bar + 8 * (B_KVFULL + KV_GATE), 0);
#pragma unroll 1
      for (int ch = 2; ch < 8; ch++) {
        if (ch == 4) prefetch_l2(P.x + (size_t)(128 * m + 16 * j) * D, 16 * D * 2);
        mbar_expect_tx(bar + 8 * (B_KFULL + ch), 4080);
        bulk_g2s(sb + off_T(ch >> 1) + 2 * UT_SIZE + (ch & 1) * KT_SIZE + 32, P.ssm_k + (size_t)(8 * c + ch) * S + 8, 4080, bar + 8 * (B_KFULL + ch));
      }
      prefetch_tmap(&P.tm_h); prefetch_tmap(&P.tm_w1); prefetch_tmap(&P.tm_act); prefetch_tmap(&P.tm_w2);
      prefetch_tmap(&P.tm_actst); prefetch_tmap(&P.tm_hres); prefetch_tmap(&P.tm_out);
      mbar_wait(bar + 8 * (B_KFULL + 7), 0);
      TS(31);
      prefetch_l2(P.w1 + (size_t)c * 8 * F, 8 * F * 2);
#pragma unroll 1
      for (int it = 0; it < 32; it++) {
        const int s = it & 3, kb = it & 15, tile = it >> 4;
        mbar_wait(bar + 8 * (it < 2 ? B_ZDONE + 1 : it == 2 ? B_ZDONE + 2 : it == 3 ? B_YFULL + 15 : B_EMPTY + s), it < 4 ? 0 : ((it >> 2) - 1) & 1);
        if (it < 4) fence_async_smem();
        const uint32_t sa = sb + s * 49152, fb = bar + 8 * (B_FULL + s);
        const int nb = tile ? 3 : 4, n0 = 448 * j + 256 * tile;
        mbar_expect_tx(fb, 16384 + nb * 8192);
#pragma unroll 1
        for (int i = 0; i < nb; i++) tma3d(sa + 16384 + i * 8192, &P.tm_w1, fb, n0 + 64 * i, 2 * (kb >> 2), 32 * (kb & 3));
        if (it < 16 && (it & 3) == 0) { wait_count(g_hcnt + ((it >> 2) * 16 + m) * 32, epoch * 8); fence_async_global(); TS(11 + (it >> 2)); }
        tma2d(sa, &P.tm_h, fb, 64 * kb, 128 * m);
        if (it == 8) prefetch_l2(P.w2 + (size_t)c * 28 * D, 28 * D * 2);
      }
      mbar_wait(bar + 8 * B_XFREE, 0);
#pragma unroll 1
      for (int kb = 0; kb < 30; kb++) {
        const int s = kb & 3;
        mbar_wait(bar + 8 * (B_EMPTY + s), ((kb >> 2) + 1) & 1);
        if (kb == 3) mbar_wait(bar + 8 * B_SFREE, 0);
        const int t1 = kb < 26 ? 10 * rank + kb - 16 : kb - 6;
        const int col = kb < 16 ? 448 * (4 * rank + (kb >> 2)) + 64 * (kb & 3) : 448 * (t1 / 3) + 256 + 64 * (t1 % 3);
        const uint32_t sa = sb + s * 49152, fb = bar + 8 * (B_FULL + s);
        const int nb = kb < 26 ? 4 : 2;
        mbar_expect_tx(fb, 16384 + nb * 8192);
#pragma unroll 1
        for (int i = 0; i < nb; i++) tma2d(sa + 16384 + i * 8192, &P.tm_w2, fb, 128 * (j ^ (i >> 1)) + 64 * (i & 1), col);
        if ((kb & 15) == 0) { wait_count(g_acnt + ((kb >> 4) * 16 + m) * 32, epoch * 8); fence_async_global(); TS(15 + (kb >> 4)); }
        tma2d(sa, &P.tm_act, fb, col, 128 * m);
      }
    }
  } else {
    const int zw = warp - 9;
    {
      uint32_t W[4][4];
      const uint4* wp = (const uint4*)(P.shift_k + (size_t)32 * c);
#pragma unroll
      for (int p = 0; p < 4; p++) {
        const uint4 v = __ldg(wp + p);
        W[0][p] = __byte_perm(v.x, v.z, 0x5410); W[1][p] = __byte_perm(v.x, v.z, 0x7632);
        W[2][p] = __byte_perm(v.y, v.w, 0x5410); W[3][p] = __byte_perm(v.y, v.w, 0x7632);
      }
      cluster_wait();
#pragma unroll 1
      for (int st = zw; st < 8; st += 3) {
        mbar_wait(bar + 8 * (B_KVFULL + st), 0);
        if (lane == 0) TS(48 + st);
        const uint32_t ka = sb + off_kv(st) + (lane >> 4) * KV_BOX + (lane & 15) * 32 + rank * 16;
        uint32_t k[12][4], v[9][4];
#pragma unroll
        for (int i = 0; i < 12; i++) {
          const uint32_t o = i < 4 ? (4 + i) * 544 : (i - 4) * 544 + 32;
          const uint4 a = lds128(ka + o);
          k[i][0] = a.x; k[i][1] = a.y; k[i][2] = a.z; k[i][3] = a.w;
          if (i >= 3) {
            const uint4 b = lds128(ka + 2 * KV_BOX + o);
            v[i - 3][0] = b.x; v[i - 3][1] = b.y; v[i - 3][2] = b.z; v[i - 3][3] = b.w;
          }
        }
#pragma unroll
        for (int p = 0; p < 4; p++) {
          uint32_t u[9];
#pragma unroll
          for (int i = 0; i < 9; i++)
            u[i] = bmul2(bfma2(k[i + 3][p], W[0][p], bfma2(k[i + 2][p], W[1][p], bfma2(k[i + 1][p], W[2][p], bmul2(k[i][p], W[3][p])))), v[i][p]);
          const uint32_t ta = sb + off_T(p) + 16 + (32 * st + lane) * 16;
#pragma unroll
          for (int e = 0; e < 2; e++) {
            const uint32_t sel = e ? 0x7632 : 0x5410;
            sts128(ta + e * UT_SIZE, __byte_perm(u[2], u[1], sel), __byte_perm(u[4], u[3], sel), __byte_perm(u[6], u[5], sel), __byte_perm(u[8], u[7], sel));
            sts128(ta + e * UT_SIZE + UT_COPY, __byte_perm(u[1], u[0], sel), __byte_perm(u[3], u[2], sel), __byte_perm(u[5], u[4], sel), __byte_perm(u[7], u[6], sel));
          }
          if (p == 0) {
            __syncwarp();
            if (lane == 0) mbar_arrive(bar + 8 * (B_UFULL + st));
            if (st < 3 && lane < 2) mbar_arrive_c(mapa(bar + 8 * (B_KVFREE + st), lane), 1);
          }
        }
        __syncwarp();
        if (lane == 0) { mbar_arrive(bar + 8 * B_UREST); TS(56 + st); }
      }
    }
    const uint32_t epoch = ldg_relaxed(g_epoch + c) + 1;
    const uint32_t par = epoch & 1;
    if (zw == 0) {
#pragma unroll 1
      for (int qt = 0; qt < 16; qt++) {
        mbar_wait(bar + 8 * (B_YFULL + qt), 0);
        const uint32_t yb = sb + off_Y(qt >> 2) + (qt & 3) * 1024 + lane * 8;
        uint32_t* zp = g_z + (size_t)((qt >> 2) * NCTA + c) * S + (qt & 3) * 512 + lane * 4;
        uint2 p[4][8];
#pragma unroll
        for (int k = 0; k < 4; k++)
#pragma unroll
          for (int i = 0; i < 8; i++) p[k][i] = lds64(yb + i * YW + k * 256);
#pragma unroll
        for (int k = 0; k < 4; k++) {
          const uint32_t a0 = badd2(badd2(p[k][0].x, p[k][1].x), badd2(p[k][2].x, p[k][3].x));
          const uint32_t a1 = badd2(badd2(p[k][0].y, p[k][1].y), badd2(p[k][2].y, p[k][3].y));
          const uint32_t b0 = badd2(badd2(p[k][4].x, p[k][5].x), badd2(p[k][6].x, p[k][7].x));
          const uint32_t b1 = badd2(badd2(p[k][4].y, p[k][5].y), badd2(p[k][6].y, p[k][7].y));
          stg_b128(zp + k * 128, (__byte_perm(a0, b0, 0x5410) & ~1u) | par, __byte_perm(a0, b0, 0x7632), __byte_perm(a1, b1, 0x5410), __byte_perm(a1, b1, 0x7632));
        }
        if ((qt & 3) == 3) {
          __syncwarp();
          if (lane == 0) { mbar_arrive(bar + 8 * (B_ZDONE + (qt >> 2))); TS(17 + (qt >> 2)); }
        }
      }
#pragma unroll 1
      for (int tile = 0; tile < 2; tile++) {
        const int n0 = 448 * j + 256 * tile;
        if (tile == 0 || m < 12) {
          float cs[8];
#pragma unroll
          for (int i = 0; i < 8; i++) cs[i] = 0.f;
          const __nv_bfloat16* wp = P.w1 + (size_t)(lane >> 1) * F + n0 + 16 * m + 8 * (lane & 1);
#pragma unroll 1
          for (int b = 0; b < 4; b++) {
            uint4 v[16];
#pragma unroll
            for (int i = 0; i < 16; i++) v[i] = __ldg((const uint4*)(wp + (size_t)(16 * b + i) * 16 * F));
#pragma unroll
            for (int i = 0; i < 16; i += 4) {
              const uint32_t a0 = badd2(badd2(v[i].x, v[i + 1].x), badd2(v[i + 2].x, v[i + 3].x)), a1 = badd2(badd2(v[i].y, v[i + 1].y), badd2(v[i + 2].y, v[i + 3].y));
              const uint32_t a2 = badd2(badd2(v[i].z, v[i + 1].z), badd2(v[i + 2].z, v[i + 3].z)), a3 = badd2(badd2(v[i].w, v[i + 1].w), badd2(v[i + 2].w, v[i + 3].w));
              cs[0] += bflo(a0); cs[1] += bfhi(a0); cs[2] += bflo(a1); cs[3] += bfhi(a1);
              cs[4] += bflo(a2); cs[5] += bfhi(a2); cs[6] += bflo(a3); cs[7] += bfhi(a3);
            }
          }
#pragma unroll 1
          for (int o = 2; o < 32; o <<= 1) {
#pragma unroll
            for (int i = 0; i < 8; i++) cs[i] += __shfl_xor_sync(0xffffffffu, cs[i], o);
          }
          if (lane < 2) {
            float4* cp = (float4*)(g_cs + n0 + 16 * m + 8 * lane);
            cp[0] = make_float4(cs[0], cs[1], cs[2], cs[3]);
            cp[1] = make_float4(cs[4], cs[5], cs[6], cs[7]);
          }
          __syncwarp();
          if (lane == 0) signal(g_ccnt + (tile * 8 + j) * 32);
        }
        if (lane == 0) wait_count(g_ccnt + (tile * 8 + j) * 32, epoch * (tile ? 12 : 16));
        __syncwarp();
        float2 cv[4];
        uint32_t bv[4];
#pragma unroll
        for (int i = 0; i < 4; i++) {
          const int n = min(lane + 32 * i, tile ? 95 : 127);
          cv[i] = ldg_cg2f(g_cs + n0 + 2 * n);
          bv[i] = __ldg((const uint32_t*)(P.b1 + n0) + n);
        }
        if (tile) mbar_wait(bar + 8 * B_XFREE, 0);
#pragma unroll
        for (int i = 0; i < 4; i++) {
          const uint32_t hi = packbf(cv[i].x, cv[i].y), lo = packbf(cv[i].x - bflo(hi), cv[i].y - bfhi(hi));
#pragma unroll
          for (int cp = 0; cp < 2; cp++) {
            const uint32_t da = sb + OFF_X + cp * 16384 + (lane + 32 * i) * 32;
            sts128(da, __byte_perm(hi, lo, 0x5410), __byte_perm(hi, bv[i], 0x5410), bv[i] & 0xffffu, 0);
            sts128(da + 16, __byte_perm(hi, lo, 0x7632), __byte_perm(hi, bv[i], 0x7632), bv[i] >> 16, 0);
          }
        }
        if (tile == 0) {
          if (lane == 0) wait_count(g_acnt + (2 * 16 + m) * 32, epoch * 8);
          __syncwarp();
#pragma unroll
          for (int i = 0; i < 4; i++) {
            const uint4 v = ldg_cg4(g_hstat + 128 * m + lane + 32 * i);
            sts128(sb + OFF_HS + (lane + 32 * i) * 16, v.x, v.y, v.z, v.w);
          }
        }
        fence_async_smem();
        __syncwarp();
        if (lane == 0) { mbar_arrive(bar + 8 * B_CSFULL); TS(21 + 19 * tile); }
      }
    } else {
      const int hw = zw - 1, rowb = 128 * m + 16 * j;
      const int q = lane & 3, i0 = 64 * hw + (lane >> 2), row0 = rowb + 4 * q;
      mbar_wait(bar + 8 * (B_KFULL + 5), 0);
#pragma unroll 1
      for (int pass = 0; pass < 2; pass++) {
        uint32_t xr[4][2][4][4];
        const uint4* src = (const uint4*)((pass ? g_h : P.x) + (size_t)row0 * D) + i0;
#pragma unroll
        for (int a = 0; a < 4; a++)
#pragma unroll
          for (int k = 0; k < 2; k++)
#pragma unroll
            for (int i = 0; i < 4; i++) {
              const uint4 v = ldg_cg4(src + a * (D / 8) + 32 * k + 8 * i);
              xr[a][k][i][0] = v.x; xr[a][k][i][1] = v.y; xr[a][k][i][2] = v.z; xr[a][k][i][3] = v.w;
            }
        float2* red = (float2*)(smem + OFF_RED);
#pragma unroll
        for (int a = 0; a < 4; a++) {
          const uint32_t pv = __byte_perm(xr[a][0][0][0], 0, 0x1010);
          float t1 = 0.f, t2 = 0.f;
#pragma unroll
          for (int ch = 0; ch < 4; ch++) {
            uint32_t c1 = 0, c2 = 0;
#pragma unroll
            for (int i = 0; i < 8; i++) {
              const uint32_t dd = bsub2(xr[a][ch >> 1][2 * (ch & 1) + (i >> 2)][i & 3], pv);
              c1 = i ? badd2(c1, dd) : dd;
              c2 = i ? bfma2(dd, dd, c2) : bmul2(dd, dd);
            }
            t1 += bflo(c1) + bfhi(c1);
            t2 += bflo(c2) + bfhi(c2);
          }
          const float pf = bflo(pv);
          t2 = fmaf(pf, fmaf(pf, 64.f, 2.f * t1), t2);
          t1 = fmaf(pf, 64.f, t1);
#pragma unroll
          for (int o = 4; o < 32; o <<= 1) { t1 += __shfl_xor_sync(0xffffffffu, t1, o); t2 += __shfl_xor_sync(0xffffffffu, t2, o); }
          if (lane < 4) red[hw * 16 + 4 * q + a] = make_float2(t1, t2);
        }
        bar_sync(1, 64);
        if (pass == 1) {
          if (hw == 0) {
            if (lane < 16) {
              const float2 r0 = red[lane], r1 = red[16 + lane];
              const float mu = (r0.x + r1.x) * (1.f / D);
              const float var = fmaxf(fmaf(-mu, mu, (r0.y + r1.y) * (1.f / D)), 0.f) + 1e-5f;
              const float sd = sqrtf(var);
              const uint32_t hi = packbf(-mu, sd), lo = packbf(-mu - bflo(hi), sd - bfhi(hi));
              stg128(g_hstat + rowb + lane, __byte_perm(hi, 0, 0x1010), __byte_perm(lo, hi, 0x7610), lo >> 16, __float_as_uint(1.f / var));
            }
            __syncwarp();
            if (lane == 0) { signal(g_acnt + (2 * 16 + m) * 32); TS(43); }
          }
          break;
        }
        uint32_t rs2[4], nm2[4];
#pragma unroll
        for (int a = 0; a < 4; a++) {
          const float2 r0 = red[4 * q + a], r1 = red[16 + 4 * q + a];
          const float mu = (r0.x + r1.x) * (1.f / D);
          const float rs = rsqrtf(fmaxf(fmaf(-mu, mu, (r0.y + r1.y) * (1.f / D)), 0.f) + 1e-5f);
          rs2[a] = packbf(rs, rs);
          nm2[a] = packbf(-mu * bflo(rs2[a]), -mu * bflo(rs2[a]));
        }
        if (tid == 320) TS(22);
        const uint32_t* zp0 = g_z + (size_t)i0 * S + row0;
        uint32_t* hp = (uint32_t*)(g_h + (size_t)row0 * D) + i0;
        uint4 zv[2][4];
        mbar_wait(bar + 8 * (B_YFULL + (m >> 2)), 0);
#pragma unroll
        for (int i = 0; i < 4; i++) zv[0][i] = ldg_b128(zp0 + (size_t)8 * i * S);
#pragma unroll
        for (int r = 0; r < 4; r++) {
#pragma unroll
          for (int k = 0; k < 2; k++) {
            const uint32_t* zp = zp0 + (size_t)(r * NCTA + 32 * k) * S;
            int it = 0;
            while (true) {
              const uint32_t bad = ((zv[k][0].x ^ par) | (zv[k][1].x ^ par) | (zv[k][2].x ^ par) | (zv[k][3].x ^ par)) & 1;
              if (__all_sync(0xffffffffu, bad == 0)) break;
              mbar_wait(bar + 8 * (B_YFULL + 4 * r + (m >> 2)), 0);
              __nanosleep(100);
#pragma unroll
              for (int i = 0; i < 4; i++) zv[k][i] = ldg_b128(zp + (size_t)8 * i * S);
              if (++it > (1 << 20)) __trap();
            }
            if (tid == 320 && k == 1) TS(27 + r);
#pragma unroll
            for (int i = 0; i < 4; i++) {
              hp[0 * (D / 2) + 128 * r + 32 * k + 8 * i] = bfma2(bfma2(xr[0][k][i][r], rs2[0], nm2[0]), zv[k][i].x, xr[0][k][i][r]);
              hp[1 * (D / 2) + 128 * r + 32 * k + 8 * i] = bfma2(bfma2(xr[1][k][i][r], rs2[1], nm2[1]), zv[k][i].y, xr[1][k][i][r]);
              hp[2 * (D / 2) + 128 * r + 32 * k + 8 * i] = bfma2(bfma2(xr[2][k][i][r], rs2[2], nm2[2]), zv[k][i].z, xr[2][k][i][r]);
              hp[3 * (D / 2) + 128 * r + 32 * k + 8 * i] = bfma2(bfma2(xr[3][k][i][r], rs2[3], nm2[3]), zv[k][i].w, xr[3][k][i][r]);
              if (r == 0 && k == 0) zv[1][i] = ldg_b128(zp + (size_t)(32 + 8 * i) * S);
            }
          }
          if (r < 3) {
#pragma unroll
            for (int k = 0; k < 2; k++)
#pragma unroll
              for (int i = 0; i < 4; i++) zv[k][i] = ldg_b128(zp0 + (size_t)((r + 1) * NCTA + 32 * k + 8 * i) * S);
          }
          fence_async_global();
          if (tid == 320) TS(23 + r);
          if (hw == (r & 1) || r == 3) {
            bar_sync(5 + r, 64);
            if (hw == (r & 1) && lane == 0) { signal(g_hcnt + (r * 16 + m) * 32); TS(32 + r); }
          } else {
            asm volatile("bar.arrive %0, 64;" ::"r"(5 + r) : "memory");
          }
        }
      }
      if (hw == 0 && lane == 0) {
#pragma unroll 1
        for (int tile = 0; tile < 2; tile++) {
          mbar_wait(bar + 8 * (B_ADONE + tile), 0);
          const int nb = tile ? 6 : 8;
#pragma unroll 1
          for (int i = nb - 1; i >= 0; i--) {
            if (!(EXP & 1) || tile == 0) tma_store(&P.tm_actst, sb + off_act(tile, i & 1, i >> 1), 448 * j + 256 * tile + 64 * (i >> 1), 128 * m + 64 * (i & 1));
            bulk_commit();
            bulk_wait_read();
            if (tile == 1 && i == 4) mbar_arrive(bar + 8 * B_SFREE);
            if (tile == 0 || i <= 4) __nanosleep(ST_SLEEP);
          }
          if (tile == 0) {
            mbar_arrive(bar + 8 * B_XFREE);
          } else {
            mbar_expect_tx(bar + 8 * B_HRES, 32768);
            tma3d(sb + OFF_X, &P.tm_hres, bar + 8 * B_HRES, 32 * j, 0, 128 * m);
          }
          bulk_wait();
          fence_async_global();
          signal(g_acnt + (tile * 16 + m) * 32);
          TS(41 + tile);
        }
        g_epoch[c] = epoch;
      }
    }
  }
}

typedef CUresult (*PFN_encode)(CUtensorMap*, CUtensorMapDataType, cuuint32_t, void*, const cuuint64_t*, const cuuint64_t*, const cuuint32_t*,
                               const cuuint32_t*, CUtensorMapInterleave, CUtensorMapSwizzle, CUtensorMapL2promotion, CUtensorMapFloatOOBfill);

void encode(PFN_encode enc, CUtensorMap* m, const void* ptr, int rank, const cuuint64_t* dims, const cuuint64_t* strides, const cuuint32_t* box,
            CUtensorMapSwizzle swz) {
  const cuuint32_t es[5] = {1, 1, 1, 1, 1};
  enc(m, CU_TENSOR_MAP_DATA_TYPE_BFLOAT16, rank, (void*)ptr, dims, strides, box, es, CU_TENSOR_MAP_INTERLEAVE_NONE, swz,
      CU_TENSOR_MAP_L2_PROMOTION_L2_128B, CU_TENSOR_MAP_FLOAT_OOB_FILL_NONE);
}

}

extern "C" void kernel_launch(void* const* d_in, const int* in_sizes, int n_in, void* d_out, int out_size) {
  static PFN_encode enc = nullptr;
  static void *p_h = nullptr, *p_act = nullptr;
  if (!enc) {
    cudaDriverEntryPointQueryResult qr;
    cudaGetDriverEntryPoint("cuTensorMapEncodeTiled", (void**)&enc, cudaEnableDefault, &qr);
    cudaGetSymbolAddress(&p_h, g_h);
    cudaGetSymbolAddress(&p_act, g_act);
    cudaFuncSetAttribute(fused_kernel, cudaFuncAttributeMaxDynamicSharedMemorySize, SMEM_BYTES);
  }
  Params P;
  P.x = (const __nv_bfloat16*)d_in[0];
  P.shift_k = (const __nv_bfloat16*)d_in[3];
  P.ssm_k = (const __nv_bfloat16*)d_in[4];
  P.ssm_D = (const __nv_bfloat16*)d_in[5];
  P.w1 = (const __nv_bfloat16*)d_in[7];
  P.b1 = (const __nv_bfloat16*)d_in[8];
  P.w2 = (const __nv_bfloat16*)d_in[9];
  P.b2 = (const __nv_bfloat16*)d_in[10];
  {
    const cuuint64_t dims[3] = {D, S / 8, 8}, str[2] = {8 * D * 2, D * 2};
    const cuuint32_t box[3] = {16, 17, 8};
    encode(enc, &P.tm_k, d_in[1], 3, dims, str, box, CU_TENSOR_MAP_SWIZZLE_NONE);
    encode(enc, &P.tm_v, d_in[2], 3, dims, str, box, CU_TENSOR_MAP_SWIZZLE_NONE);
  }
  {
    const cuuint64_t dims[2] = {D, S}, str[1] = {D * 2};
    const cuuint32_t box[2] = {64, 128}, boxo[2] = {64, 64};
    encode(enc, &P.tm_h, p_h, 2, dims, str, box, CU_TENSOR_MAP_SWIZZLE_128B);
    encode(enc, &P.tm_out, d_out, 2, dims, str, boxo, CU_TENSOR_MAP_SWIZZLE_128B);
  }
  {
    const cuuint64_t dims[3] = {F, 8, D / 8}, str[2] = {F * 2, 8 * F * 2};
    const cuuint32_t box[3] = {64, 2, 32};
    encode(enc, &P.tm_w1, P.w1, 3, dims, str, box, CU_TENSOR_MAP_SWIZZLE_128B);
  }
  {
    const cuuint64_t dims[2] = {F, S}, str[1] = {F * 2};
    const cuuint32_t box[2] = {64, 128}, boxs[2] = {64, 64};
    encode(enc, &P.tm_act, p_act, 2, dims, str, box, CU_TENSOR_MAP_SWIZZLE_128B);
    encode(enc, &P.tm_actst, p_act, 2, dims, str, boxs, CU_TENSOR_MAP_SWIZZLE_128B);
  }
  {
    const cuuint64_t dims[2] = {D, F}, str[1] = {D * 2};
    const cuuint32_t box[2] = {64, 64};
    encode(enc, &P.tm_w2, P.w2, 2, dims, str, box, CU_TENSOR_MAP_SWIZZLE_128B);
  }
  {
    const cuuint64_t dims[3] = {256, 4, S}, str[2] = {512, D * 2};
    const cuuint32_t box[3] = {32, 4, 128};
    encode(enc, &P.tm_hres, p_h, 3, dims, str, box, CU_TENSOR_MAP_SWIZZLE_64B);
  }
  fused_kernel<<<NCTA, NTHREADS, SMEM_BYTES>>>(P);
}
```

```cpp
#include <cuda_runtime.h>
#include <cuda_bf16.h>
#include <cuda.h>
#include <stdint.h>

#define DBG_TS 0
#define KV_GATE 5
#define JGROUP 0
#define EXP 0
#define ST_SLEEP 200

namespace {

constexpr int S = 2048, D = 1024, F = 3584;
constexpr int NCTA = 128, NTHREADS = 384;

constexpr int UT_COPY = 1040 * 4;
constexpr int UT_SIZE = 2 * UT_COPY;
constexpr int KT_SIZE = 16 + 4096;
constexpr int T_SIZE = 2 * (UT_SIZE + KT_SIZE);
constexpr int KV_BOX = 17 * 8 * 32;
constexpr int KV_SLOT = 4 * KV_BOX;
constexpr int KV_SIZE = 2 * KV_SLOT;
constexpr int YW = 4096 + 96;
constexpr int YBUF = 4 * YW;
constexpr int OFF_T3 = 196608 - T_SIZE;
constexpr int OFF_KVB = (OFF_T3 - KV_SIZE) & ~127;
constexpr int OFF_T2 = OFF_KVB - T_SIZE;
constexpr int OFF_KVA = (OFF_T2 - KV_SIZE) & ~127;
constexpr int OFF_T1 = OFF_KVA - T_SIZE;
constexpr int OFF_T0 = OFF_T1 - T_SIZE;
constexpr int OFF_X = 196608;
constexpr int OFF_HS = OFF_X + 32768;
constexpr int OFF_RED = OFF_X + 34816;
constexpr int OFF_BAR = OFF_X + 35200;
constexpr int SMEM_BYTES = 232448;
static_assert(OFF_T0 >= KV_SLOT && 2 * YBUF <= KV_SIZE && OFF_X + 2 * YBUF <= OFF_RED && OFF_BAR + 640 <= SMEM_BYTES, "smem map");
static_assert(OFF_T2 >= 98304, "stage 1 must only overlap T0,T1,KVA");
static_assert(OFF_T3 >= 147456, "stage 2 must not overlap T3");

enum {
  B_KVFULL = 0, B_KFULL = 8, B_UFULL = 16, B_YFULL = 24  , B_FULL = 40, B_ZDONE = 44,
  B_CSFULL = 48, B_HRES = 49, B_XFREE = 50, B_SFREE = 51, B_RECV = 52, B_PEER = 53,
  B_EMPTY = 56, B_KVFREE = 60  , B_ADONE = 64, B_UREST = 66
};

struct Params {
  CUtensorMap tm_k, tm_v, tm_h, tm_w1, tm_act, tm_actst, tm_w2, tm_hres, tm_out;
  const __nv_bfloat16 *x, *shift_k, *ssm_k, *ssm_D, *w1, *b1, *w2, *b2;
};

__device__ __align__(1024) uint32_t g_z[4 * NCTA * S];
__device__ __align__(1024) __nv_bfloat16 g_h[S * D];
__device__ __align__(1024) __nv_bfloat16 g_act[S * F];
__device__ __align__(128) uint4 g_hstat[S];
__device__ __align__(128) uint4 g_baug[F];
__device__ __align__(128) uint32_t g_hcnt[4 * 16 * 32];
__device__ __align__(128) uint32_t g_acnt[2 * 16 * 32];
__device__ __align__(128) uint32_t g_epoch[NCTA];
#define TS(slot) do {} while (0)

template<int N> __device__ __forceinline__ void wgmma_rs(float* d, const uint32_t* a, uint64_t db, int sc);
template<int N> __device__ __forceinline__ void wgmma_ss(float* d, uint64_t da, uint64_t db, int sc);
template<> __device__ __forceinline__ void wgmma_rs<16>(float* d, const uint32_t* a, uint64_t db, int sc) {
  asm volatile("{.reg .pred p; setp.ne.b32 p, %13, 0;\n"
  "wgmma.mma_async.sync.aligned.m64n16k16.f32.bf16.bf16 {%0,%1,%2,%3,%4,%5,%6,%7}, {%8,%9,%10,%11}, %12, p, 1, 1, 0;}\n"
  : "+f"(d[0]),"+f"(d[1]),"+f"(d[2]),"+f"(d[3]),"+f"(d[4]),"+f"(d[5]),"+f"(d[6]),"+f"(d[7])
  : "r"(a[0]), "r"(a[1]), "r"(a[2]), "r"(a[3]), "l"(db), "r"(sc));
}
template<> __device__ __forceinline__ void wgmma_rs<32>(float* d, const uint32_t* a, uint64_t db, int sc) {
  asm volatile("{.reg .pred p; setp.ne.b32 p, %21, 0;\n"
  "wgmma.mma_async.sync.aligned.m64n32k16.f32.bf16.bf16 {%0,%1,%2,%3,%4,%5,%6,%7,%8,%9,%10,%11,%12,%13,%14,%15}, {%16,%17,%18,%19}, %20, p, 1, 1, 0;}\n"
  : "+f"(d[0]),"+f"(d[1]),"+f"(d[2]),"+f"(d[3]),"+f"(d[4]),"+f"(d[5]),"+f"(d[6]),"+f"(d[7]),"+f"(d[8]),"+f"(d[9]),"+f"(d[10]),"+f"(d[11]),"+f"(d[12]),"+f"(d[13]),"+f"(d[14]),"+f"(d[15])
  : "r"(a[0]), "r"(a[1]), "r"(a[2]), "r"(a[3]), "l"(db), "r"(sc));
}
template<> __device__ __forceinline__ void wgmma_rs<48>(float* d, const uint32_t* a, uint64_t db, int sc) {
  asm volatile("{.reg .pred p; setp.ne.b32 p, %29, 0;\n"
  "wgmma.mma_async.sync.aligned.m64n48k16.f32.bf16.bf16 {%0,%1,%2,%3,%4,%5,%6,%7,%8,%9,%10,%11,%12,%13,%14,%15,%16,%17,%18,%19,%20,%21,%22,%23}, {%24,%25,%26,%27}, %28, p, 1, 1, 0;}\n"
  : "+f"(d[0]),"+f"(d[1]),"+f"(d[2]),"+f"(d[3]),"+f"(d[4]),"+f"(d[5]),"+f"(d[6]),"+f"(d[7]),"+f"(d[8]),"+f"(d[9]),"+f"(d[10]),"+f"(d[11]),"+f"(d[12]),"+f"(d[13]),"+f"(d[14]),"+f"(d[15]),"+f"(d[16]),"+f"(d[17]),"+f"(d[18]),"+f"(d[19]),"+f"(d[20]),"+f"(d[21]),"+f"(d[22]),"+f"(d[23])
  : "r"(a[0]), "r"(a[1]), "r"(a[2]), "r"(a[3]), "l"(db), "r"(sc));
}
template<> __device__ __forceinline__ void wgmma_rs<64>(float* d, const uint32_t* a, uint64_t db, int sc) {
  asm volatile("{.reg .pred p; setp.ne.b32 p, %37, 0;\n"
  "wgmma.mma_async.sync.aligned.m64n64k16.f32.bf16.bf16 {%0,%1,%2,%3,%4,%5,%6,%7,%8,%9,%10,%11,%12,%13,%14,%15,%16,%17,%18,%19,%20,%21,%22,%23,%24,%25,%26,%27,%28,%29,%30,%31}, {%32,%33,%34,%35}, %36, p, 1, 1, 0;}\n"
  : "+f"(d[0]),"+f"(d[1]),"+f"(d[2]),"+f"(d[3]),"+f"(d[4]),"+f"(d[5]),"+f"(d[6]),"+f"(d[7]),"+f"(d[8]),"+f"(d[9]),"+f"(d[10]),"+f"(d[11]),"+f"(d[12]),"+f"(d[13]),"+f"(d[14]),"+f"(d[15]),"+f"(d[16]),"+f"(d[17]),"+f"(d[18]),"+f"(d[19]),"+f"(d[20]),"+f"(d[21]),"+f"(d[22]),"+f"(d[23]),"+f"(d[24]),"+f"(d[25]),"+f"(d[26]),"+f"(d[27]),"+f"(d[28]),"+f"(d[29]),"+f"(d[30]),"+f"(d[31])
  : "r"(a[0]), "r"(a[1]), "r"(a[2]), "r"(a[3]), "l"(db), "r"(sc));
}
template<> __device__ __forceinline__ void wgmma_rs<80>(float* d, const uint32_t* a, uint64_t db, int sc) {
  asm volatile("{.reg .pred p; setp.ne.b32 p, %45, 0;\n"
  "wgmma.mma_async.sync.aligned.m64n80k16.f32.bf16.bf16 {%0,%1,%2,%3,%4,%5,%6,%7,%8,%9,%10,%11,%12,%13,%14,%15,%16,%17,%18,%19,%20,%21,%22,%23,%24,%25,%26,%27,%28,%29,%30,%31,%32,%33,%34,%35,%36,%37,%38,%39}, {%40,%41,%42,%43}, %44, p, 1, 1, 0;}\n"
  : "+f"(d[0]),"+f"(d[1]),"+f"(d[2]),"+f"(d[3]),"+f"(d[4]),"+f"(d[5]),"+f"(d[6]),"+f"(d[7]),"+f"(d[8]),"+f"(d[9]),"+f"(d[10]),"+f"(d[11]),"+f"(d[12]),"+f"(d[13]),"+f"(d[14]),"+f"(d[15]),"+f"(d[16]),"+f"(d[17]),"+f"(d[18]),"+f"(d[19]),"+f"(d[20]),"+f"(d[21]),"+f"(d[22]),"+f"(d[23]),"+f"(d[24]),"+f"(d[25]),"+f"(d[26]),"+f"(d[27]),"+f"(d[28]),"+f"(d[29]),"+f"(d[30]),"+f"(d[31]),"+f"(d[32]),"+f"(d[33]),"+f"(d[34]),"+f"(d[35]),"+f"(d[36]),"+f"(d[37]),"+f"(d[38]),"+f"(d[39])
  : "r"(a[0]), "r"(a[1]), "r"(a[2]), "r"(a[3]), "l"(db), "r"(sc));
}
template<> __device__ __forceinline__ void wgmma_rs<96>(float* d, const uint32_t* a, uint64_t db, int sc) {
  asm volatile("{.reg .pred p; setp.ne.b32 p, %53, 0;\n"
  "wgmma.mma_async.sync.aligned.m64n96k16.f32.bf16.bf16 {%0,%1,%2,%3,%4,%5,%6,%7,%8,%9,%10,%11,%12,%13,%14,%15,%16,%17,%18,%19,%20,%21,%22,%23,%24,%25,%26,%27,%28,%29,%30,%31,%32,%33,%34,%35,%36,%37,%38,%39,%40,%41,%42,%43,%44,%45,%46,%47}, {%48,%49,%50,%51}, %52, p, 1, 1, 0;}\n"
  : "+f"(d[0]),"+f"(d[1]),"+f"(d[2]),"+f"(d[3]),"+f"(d[4]),"+f"(d[5]),"+f"(d[6]),"+f"(d[7]),"+f"(d[8]),"+f"(d[9]),"+f"(d[10]),"+f"(d[11]),"+f"(d[12]),"+f"(d[13]),"+f"(d[14]),"+f"(d[15]),"+f"(d[16]),"+f"(d[17]),"+f"(d[18]),"+f"(d[19]),"+f"(d[20]),"+f"(d[21]),"+f"(d[22]),"+f"(d[23]),"+f"(d[24]),"+f"(d[25]),"+f"(d[26]),"+f"(d[27]),"+f"(d[28]),"+f"(d[29]),"+f"(d[30]),"+f"(d[31]),"+f"(d[32]),"+f"(d[33]),"+f"(d[34]),"+f"(d[35]),"+f"(d[36]),"+f"(d[37]),"+f"(d[38]),"+f"(d[39]),"+f"(d[40]),"+f"(d[41]),"+f"(d[42]),"+f"(d[43]),"+f"(d[44]),"+f"(d[45]),"+f"(d[46]),"+f"(d[47])
  : "r"(a[0]), "r"(a[1]), "r"(a[2]), "r"(a[3]), "l"(db), "r"(sc));
}
template<> __device__ __forceinline__ void wgmma_rs<112>(float* d, const uint32_t* a, uint64_t db, int sc) {
  asm volatile("{.reg .pred p; setp.ne.b32 p, %61, 0;\n"
  "wgmma.mma_async.sync.aligned.m64n112k16.f32.bf16.bf16 {%0,%1,%2,%3,%4,%5,%6,%7,%8,%9,%10,%11,%12,%13,%14,%15,%16,%17,%18,%19,%20,%21,%22,%23,%24,%25,%26,%27,%28,%29,%30,%31,%32,%33,%34,%35,%36,%37,%38,%39,%40,%41,%42,%43,%44,%45,%46,%47,%48,%49,%50,%51,%52,%53,%54,%55}, {%56,%57,%58,%59}, %60, p, 1, 1, 0;}\n"
  : "+f"(d[0]),"+f"(d[1]),"+f"(d[2]),"+f"(d[3]),"+f"(d[4]),"+f"(d[5]),"+f"(d[6]),"+f"(d[7]),"+f"(d[8]),"+f"(d[9]),"+f"(d[10]),"+f"(d[11]),"+f"(d[12]),"+f"(d[13]),"+f"(d[14]),"+f"(d[15]),"+f"(d[16]),"+f"(d[17]),"+f"(d[18]),"+f"(d[19]),"+f"(d[20]),"+f"(d[21]),"+f"(d[22]),"+f"(d[23]),"+f"(d[24]),"+f"(d[25]),"+f"(d[26]),"+f"(d[27]),"+f"(d[28]),"+f"(d[29]),"+f"(d[30]),"+f"(d[31]),"+f"(d[32]),"+f"(d[33]),"+f"(d[34]),"+f"(d[35]),"+f"(d[36]),"+f"(d[37]),"+f"(d[38]),"+f"(d[39]),"+f"(d[40]),"+f"(d[41]),"+f"(d[42]),"+f"(d[43]),"+f"(d[44]),"+f"(d[45]),"+f"(d[46]),"+f"(d[47]),"+f"(d[48]),"+f"(d[49]),"+f"(d[50]),"+f"(d[51]),"+f"(d[52]),"+f"(d[53]),"+f"(d[54]),"+f"(d[55])
  : "r"(a[0]), "r"(a[1]), "r"(a[2]), "r"(a[3]), "l"(db), "r"(sc));
}
template<> __device__ __forceinline__ void wgmma_rs<128>(float* d, const uint32_t* a, uint64_t db, int sc) {
  asm volatile("{.reg .pred p; setp.ne.b32 p, %69, 0;\n"
  "wgmma.mma_async.sync.aligned.m64n128k16.f32.bf16.bf16 {%0,%1,%2,%3,%4,%5,%6,%7,%8,%9,%10,%11,%12,%13,%14,%15,%16,%17,%18,%19,%20,%21,%22,%23,%24,%25,%26,%27,%28,%29,%30,%31,%32,%33,%34,%35,%36,%37,%38,%39,%40,%41,%42,%43,%44,%45,%46,%47,%48,%49,%50,%51,%52,%53,%54,%55,%56,%57,%58,%59,%60,%61,%62,%63}, {%64,%65,%66,%67}, %68, p, 1, 1, 0;}\n"
  : "+f"(d[0]),"+f"(d[1]),"+f"(d[2]),"+f"(d[3]),"+f"(d[4]),"+f"(d[5]),"+f"(d[6]),"+f"(d[7]),"+f"(d[8]),"+f"(d[9]),"+f"(d[10]),"+f"(d[11]),"+f"(d[12]),"+f"(d[13]),"+f"(d[14]),"+f"(d[15]),"+f"(d[16]),"+f"(d[17]),"+f"(d[18]),"+f"(d[19]),"+f"(d[20]),"+f"(d[21]),"+f"(d[22]),"+f"(d[23]),"+f"(d[24]),"+f"(d[25]),"+f"(d[26]),"+f"(d[27]),"+f"(d[28]),"+f"(d[29]),"+f"(d[30]),"+f"(d[31]),"+f"(d[32]),"+f"(d[33]),"+f"(d[34]),"+f"(d[35]),"+f"(d[36]),"+f"(d[37]),"+f"(d[38]),"+f"(d[39]),"+f"(d[40]),"+f"(d[41]),"+f"(d[42]),"+f"(d[43]),"+f"(d[44]),"+f"(d[45]),"+f"(d[46]),"+f"(d[47]),"+f"(d[48]),"+f"(d[49]),"+f"(d[50]),"+f"(d[51]),"+f"(d[52]),"+f"(d[53]),"+f"(d[54]),"+f"(d[55]),"+f"(d[56]),"+f"(d[57]),"+f"(d[58]),"+f"(d[59]),"+f"(d[60]),"+f"(d[61]),"+f"(d[62]),"+f"(d[63])
  : "r"(a[0]), "r"(a[1]), "r"(a[2]), "r"(a[3]), "l"(db), "r"(sc));
}
template<> __device__ __forceinline__ void wgmma_rs<144>(float* d, const uint32_t* a, uint64_t db, int sc) {
  asm volatile("{.reg .pred p; setp.ne.b32 p, %77, 0;\n"
  "wgmma.mma_async.sync.aligned.m64n144k16.f32.bf16.bf16 {%0,%1,%2,%3,%4,%5,%6,%7,%8,%9,%10,%11,%12,%13,%14,%15,%16,%17,%18,%19,%20,%21,%22,%23,%24,%25,%26,%27,%28,%29,%30,%31,%32,%33,%34,%35,%36,%37,%38,%39,%40,%41,%42,%43,%44,%45,%46,%47,%48,%49,%50,%51,%52,%53,%54,%55,%56,%57,%58,%59,%60,%61,%62,%63,%64,%65,%66,%67,%68,%69,%70,%71}, {%72,%73,%74,%75}, %76, p, 1, 1, 0;}\n"
  : "+f"(d[0]),"+f"(d[1]),"+f"(d[2]),"+f"(d[3]),"+f"(d[4]),"+f"(d[5]),"+f"(d[6]),"+f"(d[7]),"+f"(d[8]),"+f"(d[9]),"+f"(d[10]),"+f"(d[11]),"+f"(d[12]),"+f"(d[13]),"+f"(d[14]),"+f"(d[15]),"+f"(d[16]),"+f"(d[17]),"+f"(d[18]),"+f"(d[19]),"+f"(d[20]),"+f"(d[21]),"+f"(d[22]),"+f"(d[23]),"+f"(d[24]),"+f"(d[25]),"+f"(d[26]),"+f"(d[27]),"+f"(d[28]),"+f"(d[29]),"+f"(d[30]),"+f"(d[31]),"+f"(d[32]),"+f"(d[33]),"+f"(d[34]),"+f"(d[35]),"+f"(d[36]),"+f"(d[37]),"+f"(d[38]),"+f"(d[39]),"+f"(d[40]),"+f"(d[41]),"+f"(d[42]),"+f"(d[43]),"+f"(d[44]),"+f"(d[45]),"+f"(d[46]),"+f"(d[47]),"+f"(d[48]),"+f"(d[49]),"+f"(d[50]),"+f"(d[51]),"+f"(d[52]),"+f"(d[53]),"+f"(d[54]),"+f"(d[55]),"+f"(d[56]),"+f"(d[57]),"+f"(d[58]),"+f"(d[59]),"+f"(d[60]),"+f"(d[61]),"+f"(d[62]),"+f"(d[63]),"+f"(d[64]),"+f"(d[65]),"+f"(d[66]),"+f"(d[67]),"+f"(d[68]),"+f"(d[69]),"+f"(d[70]),"+f"(d[71])
  : "r"(a[0]), "r"(a[1]), "r"(a[2]), "r"(a[3]), "l"(db), "r"(sc));
}
template<> __device__ __forceinline__ void wgmma_rs<160>(float* d, const uint32_t* a, uint64_t db, int sc) {
  asm volatile("{.reg .pred p; setp.ne.b32 p, %85, 0;\n"
  "wgmma.mma_async.sync.aligned.m64n160k16.f32.bf16.bf16 {%0,%1,%2,%3,%4,%5,%6,%7,%8,%9,%10,%11,%12,%13,%14,%15,%16,%17,%18,%19,%20,%21,%22,%23,%24,%25,%26,%27,%28,%29,%30,%31,%32,%33,%34,%35,%36,%37,%38,%39,%40,%41,%42,%43,%44,%45,%46,%47,%48,%49,%50,%51,%52,%53,%54,%55,%56,%57,%58,%59,%60,%61,%62,%63,%64,%65,%66,%67,%68,%69,%70,%71,%72,%73,%74,%75,%76,%77,%78,%79}, {%80,%81,%82,%83}, %84, p, 1, 1, 0;}\n"
  : "+f"(d[0]),"+f"(d[1]),"+f"(d[2]),"+f"(d[3]),"+f"(d[4]),"+f"(d[5]),"+f"(d[6]),"+f"(d[7]),"+f"(d[8]),"+f"(d[9]),"+f"(d[10]),"+f"(d[11]),"+f"(d[12]),"+f"(d[13]),"+f"(d[14]),"+f"(d[15]),"+f"(d[16]),"+f"(d[17]),"+f"(d[18]),"+f"(d[19]),"+f"(d[20]),"+f"(d[21]),"+f"(d[22]),"+f"(d[23]),"+f"(d[24]),"+f"(d[25]),"+f"(d[26]),"+f"(d[27]),"+f"(d[28]),"+f"(d[29]),"+f"(d[30]),"+f"(d[31]),"+f"(d[32]),"+f"(d[33]),"+f"(d[34]),"+f"(d[35]),"+f"(d[36]),"+f"(d[37]),"+f"(d[38]),"+f"(d[39]),"+f"(d[40]),"+f"(d[41]),"+f"(d[42]),"+f"(d[43]),"+f"(d[44]),"+f"(d[45]),"+f"(d[46]),"+f"(d[47]),"+f"(d[48]),"+f"(d[49]),"+f"(d[50]),"+f"(d[51]),"+f"(d[52]),"+f"(d[53]),"+f"(d[54]),"+f"(d[55]),"+f"(d[56]),"+f"(d[57]),"+f"(d[58]),"+f"(d[59]),"+f"(d[60]),"+f"(d[61]),"+f"(d[62]),"+f"(d[63]),"+f"(d[64]),"+f"(d[65]),"+f"(d[66]),"+f"(d[67]),"+f"(d[68]),"+f"(d[69]),"+f"(d[70]),"+f"(d[71]),"+f"(d[72]),"+f"(d[73]),"+f"(d[74]),"+f"(d[75]),"+f"(d[76]),"+f"(d[77]),"+f"(d[78]),"+f"(d[79])
  : "r"(a[0]), "r"(a[1]), "r"(a[2]), "r"(a[3]), "l"(db), "r"(sc));
}
template<> __device__ __forceinline__ void wgmma_rs<176>(float* d, const uint32_t* a, uint64_t db, int sc) {
  asm volatile("{.reg .pred p; setp.ne.b32 p, %93, 0;\n"
  "wgmma.mma_async.sync.aligned.m64n176k16.f32.bf16.bf16 {%0,%1,%2,%3,%4,%5,%6,%7,%8,%9,%10,%11,%12,%13,%14,%15,%16,%17,%18,%19,%20,%21,%22,%23,%24,%25,%26,%27,%28,%29,%30,%31,%32,%33,%34,%35,%36,%37,%38,%39,%40,%41,%42,%43,%44,%45,%46,%47,%48,%49,%50,%51,%52,%53,%54,%55,%56,%57,%58,%59,%60,%61,%62,%63,%64,%65,%66,%67,%68,%69,%70,%71,%72,%73,%74,%75,%76,%77,%78,%79,%80,%81,%82,%83,%84,%85,%86,%87}, {%88,%89,%90,%91}, %92, p, 1, 1, 0;}\n"
  : "+f"(d[0]),"+f"(d[1]),"+f"(d[2]),"+f"(d[3]),"+f"(d[4]),"+f"(d[5]),"+f"(d[6]),"+f"(d[7]),"+f"(d[8]),"+f"(d[9]),"+f"(d[10]),"+f"(d[11]),"+f"(d[12]),"+f"(d[13]),"+f"(d[14]),"+f"(d[15]),"+f"(d[16]),"+f"(d[17]),"+f"(d[18]),"+f"(d[19]),"+f"(d[20]),"+f"(d[21]),"+f"(d[22]),"+f"(d[23]),"+f"(d[24]),"+f"(d[25]),"+f"(d[26]),"+f"(d[27]),"+f"(d[28]),"+f"(d[29]),"+f"(d[30]),"+f"(d[31]),"+f"(d[32]),"+f"(d[33]),"+f"(d[34]),"+f"(d[35]),"+f"(d[36]),"+f"(d[37]),"+f"(d[38]),"+f"(d[39]),"+f"(d[40]),"+f"(d[41]),"+f"(d[42]),"+f"(d[43]),"+f"(d[44]),"+f"(d[45]),"+f"(d[46]),"+f"(d[47]),"+f"(d[48]),"+f"(d[49]),"+f"(d[50]),"+f"(d[51]),"+f"(d[52]),"+f"(d[53]),"+f"(d[54]),"+f"(d[55]),"+f"(d[56]),"+f"(d[57]),"+f"(d[58]),"+f"(d[59]),"+f"(d[60]),"+f"(d[61]),"+f"(d[62]),"+f"(d[63]),"+f"(d[64]),"+f"(d[65]),"+f"(d[66]),"+f"(d[67]),"+f"(d[68]),"+f"(d[69]),"+f"(d[70]),"+f"(d[71]),"+f"(d[72]),"+f"(d[73]),"+f"(d[74]),"+f"(d[75]),"+f"(d[76]),"+f"(d[77]),"+f"(d[78]),"+f"(d[79]),"+f"(d[80]),"+f"(d[81]),"+f"(d[82]),"+f"(d[83]),"+f"(d[84]),"+f"(d[85]),"+f"(d[86]),"+f"(d[87])
  : "r"(a[0]), "r"(a[1]), "r"(a[2]), "r"(a[3]), "l"(db), "r"(sc));
}
template<> __device__ __forceinline__ void wgmma_rs<192>(float* d, const uint32_t* a, uint64_t db, int sc) {
  asm volatile("{.reg .pred p; setp.ne.b32 p, %101, 0;\n"
  "wgmma.mma_async.sync.aligned.m64n192k16.f32.bf16.bf16 {%0,%1,%2,%3,%4,%5,%6,%7,%8,%9,%10,%11,%12,%13,%14,%15,%16,%17,%18,%19,%20,%21,%22,%23,%24,%25,%26,%27,%28,%29,%30,%31,%32,%33,%34,%35,%36,%37,%38,%39,%40,%41,%42,%43,%44,%45,%46,%47,%48,%49,%50,%51,%52,%53,%54,%55,%56,%57,%58,%59,%60,%61,%62,%63,%64,%65,%66,%67,%68,%69,%70,%71,%72,%73,%74,%75,%76,%77,%78,%79,%80,%81,%82,%83,%84,%85,%86,%87,%88,%89,%90,%91,%92,%93,%94,%95}, {%96,%97,%98,%99}, %100, p, 1, 1, 0;}\n"
  : "+f"(d[0]),"+f"(d[1]),"+f"(d[2]),"+f"(d[3]),"+f"(d[4]),"+f"(d[5]),"+f"(d[6]),"+f"(d[7]),"+f"(d[8]),"+f"(d[9]),"+f"(d[10]),"+f"(d[11]),"+f"(d[12]),"+f"(d[13]),"+f"(d[14]),"+f"(d[15]),"+f"(d[16]),"+f"(d[17]),"+f"(d[18]),"+f"(d[19]),"+f"(d[20]),"+f"(d[21]),"+f"(d[22]),"+f"(d[23]),"+f"(d[24]),"+f"(d[25]),"+f"(d[26]),"+f"(d[27]),"+f"(d[28]),"+f"(d[29]),"+f"(d[30]),"+f"(d[31]),"+f"(d[32]),"+f"(d[33]),"+f"(d[34]),"+f"(d[35]),"+f"(d[36]),"+f"(d[37]),"+f"(d[38]),"+f"(d[39]),"+f"(d[40]),"+f"(d[41]),"+f"(d[42]),"+f"(d[43]),"+f"(d[44]),"+f"(d[45]),"+f"(d[46]),"+f"(d[47]),"+f"(d[48]),"+f"(d[49]),"+f"(d[50]),"+f"(d[51]),"+f"(d[52]),"+f"(d[53]),"+f"(d[54]),"+f"(d[55]),"+f"(d[56]),"+f"(d[57]),"+f"(d[58]),"+f"(d[59]),"+f"(d[60]),"+f"(d[61]),"+f"(d[62]),"+f"(d[63]),"+f"(d[64]),"+f"(d[65]),"+f"(d[66]),"+f"(d[67]),"+f"(d[68]),"+f"(d[69]),"+f"(d[70]),"+f"(d[71]),"+f"(d[72]),"+f"(d[73]),"+f"(d[74]),"+f"(d[75]),"+f"(d[76]),"+f"(d[77]),"+f"(d[78]),"+f"(d[79]),"+f"(d[80]),"+f"(d[81]),"+f"(d[82]),"+f"(d[83]),"+f"(d[84]),"+f"(d[85]),"+f"(d[86]),"+f"(d[87]),"+f"(d[88]),"+f"(d[89]),"+f"(d[90]),"+f"(d[91]),"+f"(d[92]),"+f"(d[93]),"+f"(d[94]),"+f"(d[95])
  : "r"(a[0]), "r"(a[1]), "r"(a[2]), "r"(a[3]), "l"(db), "r"(sc));
}
template<> __device__ __forceinline__ void wgmma_rs<208>(float* d, const uint32_t* a, uint64_t db, int sc) {
  asm volatile("{.reg .pred p; setp.ne.b32 p, %109, 0;\n"
  "wgmma.mma_async.sync.aligned.m64n208k16.f32.bf16.bf16 {%0,%1,%2,%3,%4,%5,%6,%7,%8,%9,%10,%11,%12,%13,%14,%15,%16,%17,%18,%19,%20,%21,%22,%23,%24,%25,%26,%27,%28,%29,%30,%31,%32,%33,%34,%35,%36,%37,%38,%39,%40,%41,%42,%43,%44,%45,%46,%47,%48,%49,%50,%51,%52,%53,%54,%55,%56,%57,%58,%59,%60,%61,%62,%63,%64,%65,%66,%67,%68,%69,%70,%71,%72,%73,%74,%75,%76,%77,%78,%79,%80,%81,%82,%83,%84,%85,%86,%87,%88,%89,%90,%91,%92,%93,%94,%95,%96,%97,%98,%99,%100,%101,%102,%103}, {%104,%105,%106,%107}, %108, p, 1, 1, 0;}\n"
  : "+f"(d[0]),"+f"(d[1]),"+f"(d[2]),"+f"(d[3]),"+f"(d[4]),"+f"(d[5]),"+f"(d[6]),"+f"(d[7]),"+f"(d[8]),"+f"(d[9]),"+f"(d[10]),"+f"(d[11]),"+f"(d[12]),"+f"(d[13]),"+f"(d[14]),"+f"(d[15]),"+f"(d[16]),"+f"(d[17]),"+f"(d[18]),"+f"(d[19]),"+f"(d[20]),"+f"(d[21]),"+f"(d[22]),"+f"(d[23]),"+f"(d[24]),"+f"(d[25]),"+f"(d[26]),"+f"(d[27]),"+f"(d[28]),"+f"(d[29]),"+f"(d[30]),"+f"(d[31]),"+f"(d[32]),"+f"(d[33]),"+f"(d[34]),"+f"(d[35]),"+f"(d[36]),"+f"(d[37]),"+f"(d[38]),"+f"(d[39]),"+f"(d[40]),"+f"(d[41]),"+f"(d[42]),"+f"(d[43]),"+f"(d[44]),"+f"(d[45]),"+f"(d[46]),"+f"(d[47]),"+f"(d[48]),"+f"(d[49]),"+f"(d[50]),"+f"(d[51]),"+f"(d[52]),"+f"(d[53]),"+f"(d[54]),"+f"(d[55]),"+f"(d[56]),"+f"(d[57]),"+f"(d[58]),"+f"(d[59]),"+f"(d[60]),"+f"(d[61]),"+f"(d[62]),"+f"(d[63]),"+f"(d[64]),"+f"(d[65]),"+f"(d[66]),"+f"(d[67]),"+f"(d[68]),"+f"(d[69]),"+f"(d[70]),"+f"(d[71]),"+f"(d[72]),"+f"(d[73]),"+f"(d[74]),"+f"(d[75]),"+f"(d[76]),"+f"(d[77]),"+f"(d[78]),"+f"(d[79]),"+f"(d[80]),"+f"(d[81]),"+f"(d[82]),"+f"(d[83]),"+f"(d[84]),"+f"(d[85]),"+f"(d[86]),"+f"(d[87]),"+f"(d[88]),"+f"(d[89]),"+f"(d[90]),"+f"(d[91]),"+f"(d[92]),"+f"(d[93]),"+f"(d[94]),"+f"(d[95]),"+f"(d[96]),"+f"(d[97]),"+f"(d[98]),"+f"(d[99]),"+f"(d[100]),"+f"(d[101]),"+f"(d[102]),"+f"(d[103])
  : "r"(a[0]), "r"(a[1]), "r"(a[2]), "r"(a[3]), "l"(db), "r"(sc));
}
template<> __device__ __forceinline__ void wgmma_rs<224>(float* d, const uint32_t* a, uint64_t db, int sc) {
  asm volatile("{.reg .pred p; setp.ne.b32 p, %117, 0;\n"
  "wgmma.mma_async.sync.aligned.m64n224k16.f32.bf16.bf16 {%0,%1,%2,%3,%4,%5,%6,%7,%8,%9,%10,%11,%12,%13,%14,%15,%16,%17,%18,%19,%20,%21,%22,%23,%24,%25,%26,%27,%28,%29,%30,%31,%32,%33,%34,%35,%36,%37,%38,%39,%40,%41,%42,%43,%44,%45,%46,%47,%48,%49,%50,%51,%52,%53,%54,%55,%56,%57,%58,%59,%60,%61,%62,%63,%64,%65,%66,%67,%68,%69,%70,%71,%72,%73,%74,%75,%76,%77,%78,%79,%80,%81,%82,%83,%84,%85,%86,%87,%88,%89,%90,%91,%92,%93,%94,%95,%96,%97,%98,%99,%100,%101,%102,%103,%104,%105,%106,%107,%108,%109,%110,%111}, {%112,%113,%114,%115}, %116, p, 1, 1, 0;}\n"
  : "+f"(d[0]),"+f"(d[1]),"+f"(d[2]),"+f"(d[3]),"+f"(d[4]),"+f"(d[5]),"+f"(d[6]),"+f"(d[7]),"+f"(d[8]),"+f"(d[9]),"+f"(d[10]),"+f"(d[11]),"+f"(d[12]),"+f"(d[13]),"+f"(d[14]),"+f"(d[15]),"+f"(d[16]),"+f"(d[17]),"+f"(d[18]),"+f"(d[19]),"+f"(d[20]),"+f"(d[21]),"+f"(d[22]),"+f"(d[23]),"+f"(d[24]),"+f"(d[25]),"+f"(d[26]),"+f"(d[27]),"+f"(d[28]),"+f"(d[29]),"+f"(d[30]),"+f"(d[31]),"+f"(d[32]),"+f"(d[33]),"+f"(d[34]),"+f"(d[35]),"+f"(d[36]),"+f"(d[37]),"+f"(d[38]),"+f"(d[39]),"+f"(d[40]),"+f"(d[41]),"+f"(d[42]),"+f"(d[43]),"+f"(d[44]),"+f"(d[45]),"+f"(d[46]),"+f"(d[47]),"+f"(d[48]),"+f"(d[49]),"+f"(d[50]),"+f"(d[51]),"+f"(d[52]),"+f"(d[53]),"+f"(d[54]),"+f"(d[55]),"+f"(d[56]),"+f"(d[57]),"+f"(d[58]),"+f"(d[59]),"+f"(d[60]),"+f"(d[61]),"+f"(d[62]),"+f"(d[63]),"+f"(d[64]),"+f"(d[65]),"+f"(d[66]),"+f"(d[67]),"+f"(d[68]),"+f"(d[69]),"+f"(d[70]),"+f"(d[71]),"+f"(d[72]),"+f"(d[73]),"+f"(d[74]),"+f"(d[75]),"+f"(d[76]),"+f"(d[77]),"+f"(d[78]),"+f"(d[79]),"+f"(d[80]),"+f"(d[81]),"+f"(d[82]),"+f"(d[83]),"+f"(d[84]),"+f"(d[85]),"+f"(d[86]),"+f"(d[87]),"+f"(d[88]),"+f"(d[89]),"+f"(d[90]),"+f"(d[91]),"+f"(d[92]),"+f"(d[93]),"+f"(d[94]),"+f"(d[95]),"+f"(d[96]),"+f"(d[97]),"+f"(d[98]),"+f"(d[99]),"+f"(d[100]),"+f"(d[101]),"+f"(d[102]),"+f"(d[103]),"+f"(d[104]),"+f"(d[105]),"+f"(d[106]),"+f"(d[107]),"+f"(d[108]),"+f"(d[109]),"+f"(d[110]),"+f"(d[111])
  : "r"(a[0]), "r"(a[1]), "r"(a[2]), "r"(a[3]), "l"(db), "r"(sc));
}
template<> __device__ __forceinline__ void wgmma_rs<240>(float* d, const uint32_t* a, uint64_t db, int sc) {
  asm volatile("{.reg .pred p; setp.ne.b32 p, %125, 0;\n"
  "wgmma.mma_async.sync.aligned.m64n240k16.f32.bf16.bf16 {%0,%1,%2,%3,%4,%5,%6,%7,%8,%9,%10,%11,%12,%13,%14,%15,%16,%17,%18,%19,%20,%21,%22,%23,%24,%25,%26,%27,%28,%29,%30,%31,%32,%33,%34,%35,%36,%37,%38,%39,%40,%41,%42,%43,%44,%45,%46,%47,%48,%49,%50,%51,%52,%53,%54,%55,%56,%57,%58,%59,%60,%61,%62,%63,%64,%65,%66,%67,%68,%69,%70,%71,%72,%73,%74,%75,%76,%77,%78,%79,%80,%81,%82,%83,%84,%85,%86,%87,%88,%89,%90,%91,%92,%93,%94,%95,%96,%97,%98,%99,%100,%101,%102,%103,%104,%105,%106,%107,%108,%109,%110,%111,%112,%113,%114,%115,%116,%117,%118,%119}, {%120,%121,%122,%123}, %124, p, 1, 1, 0;}\n"
  : "+f"(d[0]),"+f"(d[1]),"+f"(d[2]),"+f"(d[3]),"+f"(d[4]),"+f"(d[5]),"+f"(d[6]),"+f"(d[7]),"+f"(d[8]),"+f"(d[9]),"+f"(d[10]),"+f"(d[11]),"+f"(d[12]),"+f"(d[13]),"+f"(d[14]),"+f"(d[15]),"+f"(d[16]),"+f"(d[17]),"+f"(d[18]),"+f"(d[19]),"+f"(d[20]),"+f"(d[21]),"+f"(d[22]),"+f"(d[23]),"+f"(d[24]),"+f"(d[25]),"+f"(d[26]),"+f"(d[27]),"+f"(d[28]),"+f"(d[29]),"+f"(d[30]),"+f"(d[31]),"+f"(d[32]),"+f"(d[33]),"+f"(d[34]),"+f"(d[35]),"+f"(d[36]),"+f"(d[37]),"+f"(d[38]),"+f"(d[39]),"+f"(d[40]),"+f"(d[41]),"+f"(d[42]),"+f"(d[43]),"+f"(d[44]),"+f"(d[45]),"+f"(d[46]),"+f"(d[47]),"+f"(d[48]),"+f"(d[49]),"+f"(d[50]),"+f"(d[51]),"+f"(d[52]),"+f"(d[53]),"+f"(d[54]),"+f"(d[55]),"+f"(d[56]),"+f"(d[57]),"+f"(d[58]),"+f"(d[59]),"+f"(d[60]),"+f"(d[61]),"+f"(d[62]),"+f"(d[63]),"+f"(d[64]),"+f"(d[65]),"+f"(d[66]),"+f"(d[67]),"+f"(d[68]),"+f"(d[69]),"+f"(d[70]),"+f"(d[71]),"+f"(d[72]),"+f"(d[73]),"+f"(d[74]),"+f"(d[75]),"+f"(d[76]),"+f"(d[77]),"+f"(d[78]),"+f"(d[79]),"+f"(d[80]),"+f"(d[81]),"+f"(d[82]),"+f"(d[83]),"+f"(d[84]),"+f"(d[85]),"+f"(d[86]),"+f"(d[87]),"+f"(d[88]),"+f"(d[89]),"+f"(d[90]),"+f"(d[91]),"+f"(d[92]),"+f"(d[93]),"+f"(d[94]),"+f"(d[95]),"+f"(d[96]),"+f"(d[97]),"+f"(d[98]),"+f"(d[99]),"+f"(d[100]),"+f"(d[101]),"+f"(d[102]),"+f"(d[103]),"+f"(d[104]),"+f"(d[105]),"+f"(d[106]),"+f"(d[107]),"+f"(d[108]),"+f"(d[109]),"+f"(d[110]),"+f"(d[111]),"+f"(d[112]),"+f"(d[113]),"+f"(d[114]),"+f"(d[115]),"+f"(d[116]),"+f"(d[117]),"+f"(d[118]),"+f"(d[119])
  : "r"(a[0]), "r"(a[1]), "r"(a[2]), "r"(a[3]), "l"(db), "r"(sc));
}
template<> __device__ __forceinline__ void wgmma_rs<256>(float* d, const uint32_t* a, uint64_t db, int sc) {
  asm volatile("{.reg .pred p; setp.ne.b32 p, %133, 0;\n"
  "wgmma.mma_async.sync.aligned.m64n256k16.f32.bf16.bf16 {%0,%1,%2,%3,%4,%5,%6,%7,%8,%9,%10,%11,%12,%13,%14,%15,%16,%17,%18,%19,%20,%21,%22,%23,%24,%25,%26,%27,%28,%29,%30,%31,%32,%33,%34,%35,%36,%37,%38,%39,%40,%41,%42,%43,%44,%45,%46,%47,%48,%49,%50,%51,%52,%53,%54,%55,%56,%57,%58,%59,%60,%61,%62,%63,%64,%65,%66,%67,%68,%69,%70,%71,%72,%73,%74,%75,%76,%77,%78,%79,%80,%81,%82,%83,%84,%85,%86,%87,%88,%89,%90,%91,%92,%93,%94,%95,%96,%97,%98,%99,%100,%101,%102,%103,%104,%105,%106,%107,%108,%109,%110,%111,%112,%113,%114,%115,%116,%117,%118,%119,%120,%121,%122,%123,%124,%125,%126,%127}, {%128,%129,%130,%131}, %132, p, 1, 1, 0;}\n"
  : "+f"(d[0]),"+f"(d[1]),"+f"(d[2]),"+f"(d[3]),"+f"(d[4]),"+f"(d[5]),"+f"(d[6]),"+f"(d[7]),"+f"(d[8]),"+f"(d[9]),"+f"(d[10]),"+f"(d[11]),"+f"(d[12]),"+f"(d[13]),"+f"(d[14]),"+f"(d[15]),"+f"(d[16]),"+f"(d[17]),"+f"(d[18]),"+f"(d[19]),"+f"(d[20]),"+f"(d[21]),"+f"(d[22]),"+f"(d[23]),"+f"(d[24]),"+f"(d[25]),"+f"(d[26]),"+f"(d[27]),"+f"(d[28]),"+f"(d[29]),"+f"(d[30]),"+f"(d[31]),"+f"(d[32]),"+f"(d[33]),"+f"(d[34]),"+f"(d[35]),"+f"(d[36]),"+f"(d[37]),"+f"(d[38]),"+f"(d[39]),"+f"(d[40]),"+f"(d[41]),"+f"(d[42]),"+f"(d[43]),"+f"(d[44]),"+f"(d[45]),"+f"(d[46]),"+f"(d[47]),"+f"(d[48]),"+f"(d[49]),"+f"(d[50]),"+f"(d[51]),"+f"(d[52]),"+f"(d[53]),"+f"(d[54]),"+f"(d[55]),"+f"(d[56]),"+f"(d[57]),"+f"(d[58]),"+f"(d[59]),"+f"(d[60]),"+f"(d[61]),"+f"(d[62]),"+f"(d[63]),"+f"(d[64]),"+f"(d[65]),"+f"(d[66]),"+f"(d[67]),"+f"(d[68]),"+f"(d[69]),"+f"(d[70]),"+f"(d[71]),"+f"(d[72]),"+f"(d[73]),"+f"(d[74]),"+f"(d[75]),"+f"(d[76]),"+f"(d[77]),"+f"(d[78]),"+f"(d[79]),"+f"(d[80]),"+f"(d[81]),"+f"(d[82]),"+f"(d[83]),"+f"(d[84]),"+f"(d[85]),"+f"(d[86]),"+f"(d[87]),"+f"(d[88]),"+f"(d[89]),"+f"(d[90]),"+f"(d[91]),"+f"(d[92]),"+f"(d[93]),"+f"(d[94]),"+f"(d[95]),"+f"(d[96]),"+f"(d[97]),"+f"(d[98]),"+f"(d[99]),"+f"(d[100]),"+f"(d[101]),"+f"(d[102]),"+f"(d[103]),"+f"(d[104]),"+f"(d[105]),"+f"(d[106]),"+f"(d[107]),"+f"(d[108]),"+f"(d[109]),"+f"(d[110]),"+f"(d[111]),"+f"(d[112]),"+f"(d[113]),"+f"(d[114]),"+f"(d[115]),"+f"(d[116]),"+f"(d[117]),"+f"(d[118]),"+f"(d[119]),"+f"(d[120]),"+f"(d[121]),"+f"(d[122]),"+f"(d[123]),"+f"(d[124]),"+f"(d[125]),"+f"(d[126]),"+f"(d[127])
  : "r"(a[0]), "r"(a[1]), "r"(a[2]), "r"(a[3]), "l"(db), "r"(sc));
}
template<> __device__ __forceinline__ void wgmma_ss<128>(float* d, uint64_t da, uint64_t db, int sc) {
  asm volatile("{.reg .pred p; setp.ne.b32 p, %66, 0;\n"
  "wgmma.mma_async.sync.aligned.m64n128k16.f32.bf16.bf16 {%0,%1,%2,%3,%4,%5,%6,%7,%8,%9,%10,%11,%12,%13,%14,%15,%16,%17,%18,%19,%20,%21,%22,%23,%24,%25,%26,%27,%28,%29,%30,%31,%32,%33,%34,%35,%36,%37,%38,%39,%40,%41,%42,%43,%44,%45,%46,%47,%48,%49,%50,%51,%52,%53,%54,%55,%56,%57,%58,%59,%60,%61,%62,%63}, %64, %65, p, 1, 1, 0, 1;}\n"
  : "+f"(d[0]),"+f"(d[1]),"+f"(d[2]),"+f"(d[3]),"+f"(d[4]),"+f"(d[5]),"+f"(d[6]),"+f"(d[7]),"+f"(d[8]),"+f"(d[9]),"+f"(d[10]),"+f"(d[11]),"+f"(d[12]),"+f"(d[13]),"+f"(d[14]),"+f"(d[15]),"+f"(d[16]),"+f"(d[17]),"+f"(d[18]),"+f"(d[19]),"+f"(d[20]),"+f"(d[21]),"+f"(d[22]),"+f"(d[23]),"+f"(d[24]),"+f"(d[25]),"+f"(d[26]),"+f"(d[27]),"+f"(d[28]),"+f"(d[29]),"+f"(d[30]),"+f"(d[31]),"+f"(d[32]),"+f"(d[33]),"+f"(d[34]),"+f"(d[35]),"+f"(d[36]),"+f"(d[37]),"+f"(d[38]),"+f"(d[39]),"+f"(d[40]),"+f"(d[41]),"+f"(d[42]),"+f"(d[43]),"+f"(d[44]),"+f"(d[45]),"+f"(d[46]),"+f"(d[47]),"+f"(d[48]),"+f"(d[49]),"+f"(d[50]),"+f"(d[51]),"+f"(d[52]),"+f"(d[53]),"+f"(d[54]),"+f"(d[55]),"+f"(d[56]),"+f"(d[57]),"+f"(d[58]),"+f"(d[59]),"+f"(d[60]),"+f"(d[61]),"+f"(d[62]),"+f"(d[63])
  : "l"(da), "l"(db), "r"(sc));
}
template<> __device__ __forceinline__ void wgmma_ss<192>(float* d, uint64_t da, uint64_t db, int sc) {
  asm volatile("{.reg .pred p; setp.ne.b32 p, %98, 0;\n"
  "wgmma.mma_async.sync.aligned.m64n192k16.f32.bf16.bf16 {%0,%1,%2,%3,%4,%5,%6,%7,%8,%9,%10,%11,%12,%13,%14,%15,%16,%17,%18,%19,%20,%21,%22,%23,%24,%25,%26,%27,%28,%29,%30,%31,%32,%33,%34,%35,%36,%37,%38,%39,%40,%41,%42,%43,%44,%45,%46,%47,%48,%49,%50,%51,%52,%53,%54,%55,%56,%57,%58,%59,%60,%61,%62,%63,%64,%65,%66,%67,%68,%69,%70,%71,%72,%73,%74,%75,%76,%77,%78,%79,%80,%81,%82,%83,%84,%85,%86,%87,%88,%89,%90,%91,%92,%93,%94,%95}, %96, %97, p, 1, 1, 0, 1;}\n"
  : "+f"(d[0]),"+f"(d[1]),"+f"(d[2]),"+f"(d[3]),"+f"(d[4]),"+f"(d[5]),"+f"(d[6]),"+f"(d[7]),"+f"(d[8]),"+f"(d[9]),"+f"(d[10]),"+f"(d[11]),"+f"(d[12]),"+f"(d[13]),"+f"(d[14]),"+f"(d[15]),"+f"(d[16]),"+f"(d[17]),"+f"(d[18]),"+f"(d[19]),"+f"(d[20]),"+f"(d[21]),"+f"(d[22]),"+f"(d[23]),"+f"(d[24]),"+f"(d[25]),"+f"(d[26]),"+f"(d[27]),"+f"(d[28]),"+f"(d[29]),"+f"(d[30]),"+f"(d[31]),"+f"(d[32]),"+f"(d[33]),"+f"(d[34]),"+f"(d[35]),"+f"(d[36]),"+f"(d[37]),"+f"(d[38]),"+f"(d[39]),"+f"(d[40]),"+f"(d[41]),"+f"(d[42]),"+f"(d[43]),"+f"(d[44]),"+f"(d[45]),"+f"(d[46]),"+f"(d[47]),"+f"(d[48]),"+f"(d[49]),"+f"(d[50]),"+f"(d[51]),"+f"(d[52]),"+f"(d[53]),"+f"(d[54]),"+f"(d[55]),"+f"(d[56]),"+f"(d[57]),"+f"(d[58]),"+f"(d[59]),"+f"(d[60]),"+f"(d[61]),"+f"(d[62]),"+f"(d[63]),"+f"(d[64]),"+f"(d[65]),"+f"(d[66]),"+f"(d[67]),"+f"(d[68]),"+f"(d[69]),"+f"(d[70]),"+f"(d[71]),"+f"(d[72]),"+f"(d[73]),"+f"(d[74]),"+f"(d[75]),"+f"(d[76]),"+f"(d[77]),"+f"(d[78]),"+f"(d[79]),"+f"(d[80]),"+f"(d[81]),"+f"(d[82]),"+f"(d[83]),"+f"(d[84]),"+f"(d[85]),"+f"(d[86]),"+f"(d[87]),"+f"(d[88]),"+f"(d[89]),"+f"(d[90]),"+f"(d[91]),"+f"(d[92]),"+f"(d[93]),"+f"(d[94]),"+f"(d[95])
  : "l"(da), "l"(db), "r"(sc));
}
template<> __device__ __forceinline__ void wgmma_ss<256>(float* d, uint64_t da, uint64_t db, int sc) {
  asm volatile("{.reg .pred p; setp.ne.b32 p, %130, 0;\n"
  "wgmma.mma_async.sync.aligned.m64n256k16.f32.bf16.bf16 {%0,%1,%2,%3,%4,%5,%6,%7,%8,%9,%10,%11,%12,%13,%14,%15,%16,%17,%18,%19,%20,%21,%22,%23,%24,%25,%26,%27,%28,%29,%30,%31,%32,%33,%34,%35,%36,%37,%38,%39,%40,%41,%42,%43,%44,%45,%46,%47,%48,%49,%50,%51,%52,%53,%54,%55,%56,%57,%58,%59,%60,%61,%62,%63,%64,%65,%66,%67,%68,%69,%70,%71,%72,%73,%74,%75,%76,%77,%78,%79,%80,%81,%82,%83,%84,%85,%86,%87,%88,%89,%90,%91,%92,%93,%94,%95,%96,%97,%98,%99,%100,%101,%102,%103,%104,%105,%106,%107,%108,%109,%110,%111,%112,%113,%114,%115,%116,%117,%118,%119,%120,%121,%122,%123,%124,%125,%126,%127}, %128, %129, p, 1, 1, 0, 1;}\n"
  : "+f"(d[0]),"+f"(d[1]),"+f"(d[2]),"+f"(d[3]),"+f"(d[4]),"+f"(d[5]),"+f"(d[6]),"+f"(d[7]),"+f"(d[8]),"+f"(d[9]),"+f"(d[10]),"+f"(d[11]),"+f"(d[12]),"+f"(d[13]),"+f"(d[14]),"+f"(d[15]),"+f"(d[16]),"+f"(d[17]),"+f"(d[18]),"+f"(d[19]),"+f"(d[20]),"+f"(d[21]),"+f"(d[22]),"+f"(d[23]),"+f"(d[24]),"+f"(d[25]),"+f"(d[26]),"+f"(d[27]),"+f"(d[28]),"+f"(d[29]),"+f"(d[30]),"+f"(d[31]),"+f"(d[32]),"+f"(d[33]),"+f"(d[34]),"+f"(d[35]),"+f"(d[36]),"+f"(d[37]),"+f"(d[38]),"+f"(d[39]),"+f"(d[40]),"+f"(d[41]),"+f"(d[42]),"+f"(d[43]),"+f"(d[44]),"+f"(d[45]),"+f"(d[46]),"+f"(d[47]),"+f"(d[48]),"+f"(d[49]),"+f"(d[50]),"+f"(d[51]),"+f"(d[52]),"+f"(d[53]),"+f"(d[54]),"+f"(d[55]),"+f"(d[56]),"+f"(d[57]),"+f"(d[58]),"+f"(d[59]),"+f"(d[60]),"+f"(d[61]),"+f"(d[62]),"+f"(d[63]),"+f"(d[64]),"+f"(d[65]),"+f"(d[66]),"+f"(d[67]),"+f"(d[68]),"+f"(d[69]),"+f"(d[70]),"+f"(d[71]),"+f"(d[72]),"+f"(d[73]),"+f"(d[74]),"+f"(d[75]),"+f"(d[76]),"+f"(d[77]),"+f"(d[78]),"+f"(d[79]),"+f"(d[80]),"+f"(d[81]),"+f"(d[82]),"+f"(d[83]),"+f"(d[84]),"+f"(d[85]),"+f"(d[86]),"+f"(d[87]),"+f"(d[88]),"+f"(d[89]),"+f"(d[90]),"+f"(d[91]),"+f"(d[92]),"+f"(d[93]),"+f"(d[94]),"+f"(d[95]),"+f"(d[96]),"+f"(d[97]),"+f"(d[98]),"+f"(d[99]),"+f"(d[100]),"+f"(d[101]),"+f"(d[102]),"+f"(d[103]),"+f"(d[104]),"+f"(d[105]),"+f"(d[106]),"+f"(d[107]),"+f"(d[108]),"+f"(d[109]),"+f"(d[110]),"+f"(d[111]),"+f"(d[112]),"+f"(d[113]),"+f"(d[114]),"+f"(d[115]),"+f"(d[116]),"+f"(d[117]),"+f"(d[118]),"+f"(d[119]),"+f"(d[120]),"+f"(d[121]),"+f"(d[122]),"+f"(d[123]),"+f"(d[124]),"+f"(d[125]),"+f"(d[126]),"+f"(d[127])
  : "l"(da), "l"(db), "r"(sc));
}

__device__ __forceinline__ void wg_fence() { asm volatile("wgmma.fence.sync.aligned;" ::: "memory"); }
__device__ __forceinline__ void wg_commit() { asm volatile("wgmma.commit_group.sync.aligned;" ::: "memory"); }
template <int N> __device__ __forceinline__ void wg_wait() { asm volatile("wgmma.wait_group.sync.aligned %0;" ::"n"(N) : "memory"); }
__device__ __forceinline__ uint64_t mkdesc(uint32_t addr, uint32_t lbo, uint32_t sbo, uint32_t swz) {
  return (uint64_t)((addr & 0x3FFFF) >> 4) | ((uint64_t)(lbo >> 4) << 16) | ((uint64_t)(sbo >> 4) << 32) | ((uint64_t)swz << 62);
}
__device__ __forceinline__ void mbar_init(uint32_t a, uint32_t c) { asm volatile("mbarrier.init.shared.b64 [%0], %1;" ::"r"(a), "r"(c) : "memory"); }
__device__ __forceinline__ void mbar_expect_tx(uint32_t a, uint32_t b) { asm volatile("mbarrier.arrive.expect_tx.shared.b64 _, [%0], %1;" ::"r"(a), "r"(b) : "memory"); }
__device__ __forceinline__ void mbar_arrive(uint32_t a) { asm volatile("mbarrier.arrive.shared.b64 _, [%0];" ::"r"(a) : "memory"); }
__device__ __forceinline__ void mbar_arrive_c(uint32_t a, uint32_t n) { asm volatile("mbarrier.arrive.shared::cluster.b64 _, [%0], %1;" ::"r"(a), "r"(n) : "memory"); }
__device__ __forceinline__ void mbar_wait(uint32_t a, uint32_t parity) {
  asm volatile("{.reg .pred p, q; .reg .u32 n; mov.u32 n, 0;\n"
               "W: mbarrier.try_wait.parity.shared.b64 p, [%0], %1;\n"
               "add.u32 n, n, 1; setp.eq.u32 q, n, 0x100000; @q trap; @!p bra.uni W;}" ::"r"(a), "r"(parity) : "memory");
}
__device__ __forceinline__ uint32_t mapa(uint32_t a, uint32_t rank) { uint32_t r; asm("mapa.shared::cluster.u32 %0, %1, %2;" : "=r"(r) : "r"(a), "r"(rank)); return r; }
__device__ __forceinline__ void tma2d(uint32_t dst, const CUtensorMap* m, uint32_t bar, int c0, int c1) {
  asm volatile("cp.async.bulk.tensor.2d.shared::cluster.global.mbarrier::complete_tx::bytes [%0], [%1, {%3,%4}], [%2];"
               ::"r"(dst), "l"(m), "r"(bar), "r"(c0), "r"(c1) : "memory");
}
__device__ __forceinline__ void tma3d(uint32_t dst, const CUtensorMap* m, uint32_t bar, int c0, int c1, int c2) {
  asm volatile("cp.async.bulk.tensor.3d.shared::cluster.global.mbarrier::complete_tx::bytes [%0], [%1, {%3,%4,%5}], [%2];"
               ::"r"(dst), "l"(m), "r"(bar), "r"(c0), "r"(c1), "r"(c2) : "memory");
}
__device__ __forceinline__ void tma3d_mc(uint32_t dst, const CUtensorMap* m, uint32_t bar, int c0, int c1, int c2) {
  asm volatile("cp.async.bulk.tensor.3d.shared::cluster.global.mbarrier::complete_tx::bytes.multicast::cluster [%0], [%1, {%3,%4,%5}], [%2], %6;"
               ::"r"(dst), "l"(m), "r"(bar), "r"(c0), "r"(c1), "r"(c2), "h"((uint16_t)3) : "memory");
}
__device__ __forceinline__ void tma_store(const CUtensorMap* m, uint32_t src, int c0, int c1) {
  asm volatile("cp.async.bulk.tensor.2d.global.shared::cta.bulk_group [%0, {%2,%3}], [%1];" ::"l"(m), "r"(src), "r"(c0), "r"(c1) : "memory");
}
__device__ __forceinline__ void bulk_commit() { asm volatile("cp.async.bulk.commit_group;" ::: "memory"); }
__device__ __forceinline__ void bulk_wait_read() { asm volatile("cp.async.bulk.wait_group.read 0;" ::: "memory"); }
__device__ __forceinline__ void bulk_wait() { asm volatile("cp.async.bulk.wait_group 0;" ::: "memory"); }
__device__ __forceinline__ void bulk_g2s(uint32_t dst, const void* src, uint32_t bytes, uint32_t bar) {
  asm volatile("cp.async.bulk.shared::cluster.global.mbarrier::complete_tx::bytes [%0], [%1], %2, [%3];"
               ::"r"(dst), "l"(src), "r"(bytes), "r"(bar) : "memory");
}
__device__ __forceinline__ void prefetch_l2(const void* src, uint32_t bytes) {
  asm volatile("cp.async.bulk.prefetch.L2.global [%0], %1;" ::"l"(src), "r"(bytes) : "memory");
}
__device__ __forceinline__ void prefetch_tmap(const CUtensorMap* m) { asm volatile("prefetch.tensormap [%0];" ::"l"(m) : "memory"); }
__device__ __forceinline__ void fence_async_smem() { asm volatile("fence.proxy.async.shared::cta;" ::: "memory"); }
__device__ __forceinline__ void fence_async_global() { asm volatile("fence.proxy.async.global;" ::: "memory"); }
__device__ __forceinline__ void bar_sync(int id, int n) { asm volatile("bar.sync %0, %1;" ::"r"(id), "r"(n) : "memory"); }
__device__ __forceinline__ void cluster_wait() { asm volatile("barrier.cluster.wait.aligned;" ::: "memory"); }
__device__ __forceinline__ uint32_t lds32(uint32_t a) { uint32_t v; asm volatile("ld.volatile.shared.b32 %0,[%1];" : "=r"(v) : "r"(a)); return v; }
__device__ __forceinline__ uint4 lds128(uint32_t a) { uint4 v; asm volatile("ld.shared.v4.b32 {%0,%1,%2,%3},[%4];" : "=r"(v.x), "=r"(v.y), "=r"(v.z), "=r"(v.w) : "r"(a) : "memory"); return v; }
__device__ __forceinline__ void sts128(uint32_t a, uint32_t x, uint32_t y, uint32_t z, uint32_t w) { asm volatile("st.shared.v4.b32 [%0],{%1,%2,%3,%4};" ::"r"(a), "r"(x), "r"(y), "r"(z), "r"(w) : "memory"); }
__device__ __forceinline__ void stsm4(uint32_t a, uint32_t x, uint32_t y, uint32_t z, uint32_t w) { asm volatile("stmatrix.sync.aligned.m8n8.x4.shared.b16 [%0],{%1,%2,%3,%4};" ::"r"(a), "r"(x), "r"(y), "r"(z), "r"(w) : "memory"); }
__device__ __forceinline__ void st_async128(uint32_t a, uint32_t bar, uint32_t x, uint32_t y, uint32_t z, uint32_t w) {
  asm volatile("st.async.weak.shared::cluster.mbarrier::complete_tx::bytes.v4.b32 [%0],{%2,%3,%4,%5},[%1];" ::"r"(a), "r"(bar), "r"(x), "r"(y), "r"(z), "r"(w) : "memory");
}
__device__ __forceinline__ uint32_t packbf(float lo, float hi) { uint32_t r; asm("cvt.rn.bf16x2.f32 %0, %1, %2;" : "=r"(r) : "f"(hi), "f"(lo)); return r; }
__device__ __forceinline__ uint32_t packbf_relu(float lo, float hi) { uint32_t r; asm("cvt.rn.relu.bf16x2.f32 %0, %1, %2;" : "=r"(r) : "f"(hi), "f"(lo)); return r; }
__device__ __forceinline__ uint32_t bmul2(uint32_t a, uint32_t b) { uint32_t r; asm("mul.rn.bf16x2 %0, %1, %2;" : "=r"(r) : "r"(a), "r"(b)); return r; }
__device__ __forceinline__ uint32_t bfma2(uint32_t a, uint32_t b, uint32_t c) { uint32_t r; asm("fma.rn.bf16x2 %0, %1, %2, %3;" : "=r"(r) : "r"(a), "r"(b), "r"(c)); return r; }
__device__ __forceinline__ uint32_t badd2(uint32_t a, uint32_t b) { uint32_t r; asm("add.rn.bf16x2 %0, %1, %2;" : "=r"(r) : "r"(a), "r"(b)); return r; }
__device__ __forceinline__ uint32_t bsub2(uint32_t a, uint32_t b) { uint32_t r; asm("sub.rn.bf16x2 %0, %1, %2;" : "=r"(r) : "r"(a), "r"(b)); return r; }
__device__ __forceinline__ float bflo(uint32_t v) { return __uint_as_float(v << 16); }
__device__ __forceinline__ float bfhi(uint32_t v) { return __uint_as_float(v & 0xffff0000u); }
__device__ __forceinline__ uint32_t ldg_relaxed(const uint32_t* p) { uint32_t v; asm volatile("ld.relaxed.gpu.global.b32 %0,[%1];" : "=r"(v) : "l"(p) : "memory"); return v; }
__device__ __forceinline__ uint4 ldg_b128(const void* p) {
  uint4 v;
  asm volatile("{.reg .b128 r; .reg .b64 a, b; ld.relaxed.gpu.global.b128 r, [%4]; mov.b128 {a, b}, r; mov.b64 {%0,%1}, a; mov.b64 {%2,%3}, b;}"
               : "=r"(v.x), "=r"(v.y), "=r"(v.z), "=r"(v.w) : "l"(p) : "memory");
  return v;
}
__device__ __forceinline__ void stg_b128(void* p, uint32_t x, uint32_t y, uint32_t z, uint32_t w) {
  asm volatile("{.reg .b128 r; .reg .b64 a, b; mov.b64 a, {%1,%2}; mov.b64 b, {%3,%4}; mov.b128 r, {a, b}; st.relaxed.gpu.global.b128 [%0], r;}"
               ::"l"(p), "r"(x), "r"(y), "r"(z), "r"(w) : "memory");
}
__device__ __forceinline__ uint4 ldg_nc4(const void* p) { uint4 v; asm volatile("ld.global.nc.L1::no_allocate.v4.b32 {%0,%1,%2,%3},[%4];" : "=r"(v.x), "=r"(v.y), "=r"(v.z), "=r"(v.w) : "l"(p) : "memory"); return v; }
__device__ __forceinline__ void signal(uint32_t* cnt) { asm volatile("red.release.gpu.global.add.u32 [%0], 1;" ::"l"(cnt) : "memory"); }
__device__ __forceinline__ void wait_count(const uint32_t* cnt, uint32_t target) {
  int it = 0;
  while (true) {
    uint32_t v;
    asm volatile("ld.acquire.gpu.global.b32 %0,[%1];" : "=r"(v) : "l"(cnt) : "memory");
    if ((int)(v - target) >= 0) break;
    __nanosleep(32);
    if (++it > (1 << 21)) __trap();
  }
}

template <int LO, int HI> __device__ __forceinline__ void rename(float* d) {
#pragma unroll
  for (int i = LO; i < HI; i++) { float e; asm volatile("mov.b32 %0, %1;" : "=f"(e) : "f"(d[i])); d[i] = e; }
}
template <int M> __device__ __forceinline__ void drain4(const float* d, uint32_t ya, uint32_t ybar, bool lane0) {
  uint32_t r[4];
#pragma unroll
  for (int q = 0; q < 4; q++) {
    const int mu = M + q;
    float v0 = d[4 * mu], v1 = d[4 * mu + 1];
    if (mu > 0) { v0 += d[4 * mu - 2]; v1 += d[4 * mu - 1]; }
    r[q] = packbf(v0, v1);
  }
  asm volatile("stmatrix.sync.aligned.m8n8.x4.trans.shared.b16 [%0],{%1,%2,%3,%4};" ::"r"(ya + M * 128), "r"(r[0]), "r"(r[1]), "r"(r[2]), "r"(r[3]) : "memory");
  if constexpr ((M & 7) == 4) {
    __syncwarp();
    if (lane0) mbar_arrive(ybar + (M >> 3) * 8);
  }
}
__device__ __forceinline__ void lda(uint32_t* a, uint32_t ua) { a[0] = lds32(ua); a[1] = lds32(ua + 128); a[2] = lds32(ua - 16); a[3] = lds32(ua + 112); }
template <int P, bool FIRST> struct Pass {
  static __device__ __forceinline__ void run(float* d, uint32_t (*a)[4], uint32_t ua, uint64_t db, uint32_t ya, uint32_t ubar, uint32_t ybar, bool lane0) {
    if constexpr (P > 0) rename<8 * (P - 1), 128>(d);
    wg_fence();
    wgmma_rs<256 - 16 * P>(d + 8 * P, a[P & 1], db, P != 0);
    wg_commit();
    if constexpr (P < 15) {
      if constexpr (FIRST && (P & 1)) mbar_wait(ubar + 8 * ((P + 1) / 2), 0);
      lda(a[(P + 1) & 1], ua + (P + 1) * 256);
    }
    if constexpr (P >= 3 && (P & 1)) drain4<2 * P - 6>(d, ya, ybar, lane0);
    wg_wait<0>();
    if constexpr (P < 15) Pass<P + 1, FIRST>::run(d, a, ua, db, ya, ubar, ybar, lane0);
    else { rename<120, 128>(d); drain4<28>(d, ya, ybar, lane0); }
  }
};

__device__ __forceinline__ uint32_t off_T(int r) { return r == 0 ? OFF_T0 : r == 1 ? OFF_T1 : r == 2 ? OFF_T2 : OFF_T3; }
__device__ __forceinline__ uint32_t off_Y(int r) { return r == 1 ? OFF_KVA : r == 2 ? OFF_KVB : OFF_X; }
__device__ __forceinline__ uint32_t off_kv(int st) {
  const int sl = st < 5 ? st : st - 5;
  return sl == 0 ? 0 : sl < 3 ? OFF_KVA + (sl - 1) * KV_SLOT : OFF_KVB + (sl - 3) * KV_SLOT;
}
template <bool FIRST>
__device__ __forceinline__ void conv_round(uint32_t sb, int r, int wg, int w, int lane) {
  float d[128];
  uint32_t a[2][4];
  const int g = lane >> 2, t = lane & 3;
  const uint32_t bar = sb + OFF_BAR, tb = sb + off_T(r);
  const uint32_t ua = tb + wg * UT_SIZE + ((g & 1) ? 0 : UT_COPY) + ((g >> 1) + 8 * w + 8 - t) * 4;
  const uint64_t db = mkdesc(tb + 2 * UT_SIZE + wg * KT_SIZE, 16, 128, 0);
  const uint32_t yb = sb + off_Y(r) + wg * YBUF + w * YW;
  mbar_wait(bar + 8 * (FIRST ? B_UFULL : r == 3 ? B_ZDONE : B_UREST), 0);
  lda(a[0], ua);
  if (lane < 2 * w) sts128(yb + lane * 16, 0, 0, 0, 0);
  mbar_wait(bar + 8 * (B_KFULL + 2 * r + wg), 0);
  if (threadIdx.x == 0) TS(1 + r);
  Pass<0, FIRST>::run(d, a, ua, db, yb + (2 * w + lane) * 16, bar + 8 * B_UFULL, bar + 8 * (B_YFULL + 4 * r), lane == 0);
}
__device__ __forceinline__ uint32_t off_act(int tile, int wg, int b) {
  return b < 2 ? OFF_X + wg * 16384 + b * 8192 : tile == 0 ? (2 * wg + b - 2) * 49152 + 40960 : 180224 + wg * 8192;
}

template <int NT>
__device__ __forceinline__ void mainloop(float* acc, uint32_t sb, int wg, bool rel, int nkb) {
  const uint32_t bar = sb + OFF_BAR;
  const uint64_t da0 = mkdesc(sb + wg * 8192, 16, 1024, 1), db0 = mkdesc(sb + 16384, 8192, 1024, 1);
  mbar_wait(bar + 8 * B_FULL, 0);
  wg_fence();
#pragma unroll
  for (int kk = 0; kk < 4; kk++) wgmma_ss<NT>(acc, da0 + kk * 2, db0 + kk * 128, kk != 0);
  wg_commit();
#pragma unroll 1
  for (int kb = 1; kb < nkb; kb++) {
    const int s = kb & 3;
    mbar_wait(bar + 8 * (B_FULL + s), (kb >> 2) & 1);
    const uint64_t da = da0 + s * 3072, db = db0 + s * 3072;
    wg_fence();
#pragma unroll
    for (int kk = 0; kk < 4; kk++) wgmma_ss<NT>(acc, da + kk * 2, db + kk * 128, 1);
    wg_commit();
    wg_wait<1>();
    if (rel) mbar_arrive(bar + 8 * (B_EMPTY + ((kb - 1) & 3)));
  }
}
template <int NT>
__device__ __forceinline__ void gemm1_main(float* out, uint32_t sb, int wg, bool rel, uint32_t hs, bool t3) {
  const uint32_t bar = sb + OFF_BAR;
  float acc[NT / 2];
  mainloop<NT>(acc, sb, wg, rel, 16);
  mbar_wait(bar + 8 * B_CSFULL, NT == 256 ? 0 : 1);
  uint32_t a[4] = {lds32(hs), lds32(hs + 128), 0, 0};
  if (t3) a[0] = a[1] = 0;
  wg_fence();
  wgmma_rs<NT>(acc, a, mkdesc(sb + OFF_X + wg * 16384, 0, 128, 0), 1);
  wg_commit();
  wg_wait<1>();
  if (rel) mbar_arrive(bar + 8 * (B_EMPTY + 3));
  wg_wait<0>();
#pragma unroll
  for (int i = 0; i < NT / 2; i++) asm volatile("mov.b32 %0, %1;" : "=f"(out[i]) : "f"(acc[i]));
}

__global__ void __cluster_dims__(2, 1, 1) __launch_bounds__(NTHREADS, 1) fused_kernel(const __grid_constant__ Params P) {
  extern __shared__ __align__(1024) unsigned char smem[];
  const uint32_t sb = (uint32_t)__cvta_generic_to_shared(smem);
  const uint32_t bar = sb + OFF_BAR;
  const int tid = threadIdx.x, warp = __shfl_sync(0xffffffffu, tid >> 5, 0), lane = tid & 31;
  const int rank = blockIdx.x & 1, cl = blockIdx.x >> 1;
  const int lp = cl < 4 ? 60 + cl : cl < 36 ? 4 * ((cl - 4) & 7) + ((cl - 4) >> 3) : 32 + 4 * ((cl - 36) % 7) + (cl - 36) / 7;
  const int c = 2 * lp + rank;
  const int m = lp >> 2, j = 2 * (lp & 3) + rank;

  if (lane == 0) {
    if (warp == 8) {
      TS(0);
      mbar_init(bar + 8 * B_KVFULL, 1); mbar_init(bar + 8 * B_KFULL, 2); mbar_init(bar + 8 * (B_KFULL + 1), 2);
      mbar_expect_tx(bar + 8 * B_KVFULL, KV_SLOT);
#pragma unroll 1
      for (int i = 0; i < 2; i++) {
        tma3d(sb + i * KV_BOX, &P.tm_k, bar + 8 * B_KVFULL, 8 * (c & ~1), 16 * i - 1, 0);
        tma3d(sb + (2 + i) * KV_BOX, &P.tm_v, bar + 8 * B_KVFULL, 8 * (c & ~1), 16 * i - 1, 0);
      }
#pragma unroll 1
      for (int i = 0; i < 2; i++) {
        mbar_expect_tx(bar + 8 * (B_KFULL + i), 4080);
        bulk_g2s(sb + OFF_T0 + 2 * UT_SIZE + i * KT_SIZE + 32, P.ssm_k + (size_t)(8 * c + i) * S + 8, 4080, bar + 8 * (B_KFULL + i));
      }
    } else if (warp < 8) {
      const uint32_t cnt = (0x18211881u >> (4 * warp)) & 15;
#pragma unroll
      for (int i = 0; i < 8; i++) mbar_init(bar + 8 * (16 + 8 * warp + i), cnt);
      if (warp == 4) mbar_expect_tx(bar + 8 * B_RECV, 32768);
    } else if (warp == 9) {
#pragma unroll
      for (int i = 1; i < 8; i++) { mbar_init(bar + 8 * (B_KVFULL + i), 1); mbar_expect_tx(bar + 8 * (B_KVFULL + i), KV_SLOT); }
    } else if (warp == 10) {
#pragma unroll
      for (int i = 2; i < 8; i++) mbar_init(bar + 8 * (B_KFULL + i), 2);
    }
    asm volatile("fence.mbarrier_init.release.cluster;" ::: "memory");
  }
  if (warp == 11 && lane < 16) sts128(sb + off_T(lane >> 2) + (lane & 3) * UT_COPY, 0, 0, 0, 0);
  __syncthreads();
  asm volatile("barrier.cluster.arrive.relaxed.aligned;" ::: "memory");

  if (warp < 8) {
    if (tid == 32) TS(46);
    if (warp == 0 && lane < 8) {
      const uint4 v = __ldg((const uint4*)(P.ssm_k + (size_t)(8 * c + lane) * S));
      const float k0 = bflo(v.x) + __bfloat162float(P.ssm_D[8 * c + lane]);
      const uint32_t kt = sb + off_T(lane >> 1) + 2 * UT_SIZE + (lane & 1) * KT_SIZE;
      sts128(kt, 0, 0, 0, 0);
      sts128(kt + 16, (v.x & 0xffff0000u) | (packbf(k0, 0.f) & 0xffffu), v.y, v.z, v.w);
      fence_async_smem();
      mbar_arrive(bar + 8 * (B_KFULL + lane));
    }
    __syncwarp();
    cluster_wait();
    const int wg = warp >> 2, w = warp & 3, g = lane >> 2, t = lane & 3;
    conv_round<true>(sb, 0, wg, w, lane);
#pragma unroll 1
    for (int r = 1; r < 4; r++) conv_round<false>(sb, r, wg, w, lane);
    if (tid == 0) TS(5);
    const bool rel = lane == 0 && w == 0;
    const int id = lane >> 3, srow = 16 * w + (lane & 7) + 8 * (id & 1);
    const uint32_t soff = srow * 128, sx = ((id >> 1) ^ (srow & 7)) << 4;
    const uint32_t hs = sb + OFF_HS + (64 * wg + 16 * w + g) * 16;
#pragma unroll 1
    for (int tile = 0; tile < 2; tile++) {
      float acc[128];
      if (tile == 0) {
        gemm1_main<256>(acc, sb, wg, rel, hs + 4 * t, t == 3);
      } else {
        gemm1_main<192>(acc, sb, wg, rel, hs + 4 * t, t == 3);
#pragma unroll
        for (int i = 96; i < 128; i++) asm volatile("mov.b32 %0, 0;" : "=f"(acc[i]));
      }
      if (tid == 0) TS(44 + tile);
#pragma unroll
      for (int b = 0; b < 4; b++) {
        if (b == 3 && tile) break;
        if (b == 2) mbar_wait(bar + 8 * (B_EMPTY + 3), 1);
        const uint32_t dst = sb + off_act(tile, wg, b) + soff;
#pragma unroll
        for (int p = 0; p < 4; p++) {
          uint32_t o[4];
#pragma unroll
          for (int e = 0; e < 4; e++) {
            const uint32_t u = packbf_relu(acc[32 * b + 8 * p + 2 * e], acc[32 * b + 8 * p + 2 * e + 1]);
            o[e] = bmul2(u, u);
          }
          stsm4(dst + (sx ^ (p << 5)), o[0], o[1], o[2], o[3]);
        }
      }
      fence_async_smem();
      __syncwarp();
      if (lane == 0) mbar_arrive(bar + 8 * (B_ADONE + tile));
      if (tid == 0) TS(6 + tile);
    }
    {
      float acc[64], res[64];
      {
        float big[128];
        mainloop<256>(big, sb, wg, rel, 26);
        wg_wait<0>();
#pragma unroll
        for (int i = 0; i < 64; i++) { asm volatile("mov.b32 %0, %1;" : "=f"(acc[i]) : "f"(big[i])); asm volatile("mov.b32 %0, %1;" : "=f"(res[i]) : "f"(big[64 + i])); }
      }
      if (rel) mbar_arrive(bar + 8 * (B_EMPTY + 1));
      if (tid == 0) TS(47);
      const uint64_t da0 = mkdesc(sb + wg * 8192, 16, 1024, 1), db0 = mkdesc(sb + 16384, 8192, 1024, 1);
      const uint32_t ro = (2 + wg) * 49152 + 32768 + (tid & 127) * 16;
      const uint32_t pb = mapa(sb, rank ^ 1);
#pragma unroll
      for (int kb = 26; kb < 30; kb++) {
        const int s = kb & 3;
        mbar_wait(bar + 8 * (B_FULL + s), (kb >> 2) & 1);
        wg_fence();
#pragma unroll
        for (int kk = 0; kk < 4; kk++) wgmma_ss<128>(acc, da0 + s * 3072 + kk * 2, db0 + s * 3072 + kk * 128, 1);
        wg_commit();
        if (kb == 26) mbar_wait(bar + 8 * B_PEER, 0);
        if (kb < 29) {
#pragma unroll
          for (int i = 3 * (kb - 26) - (kb > 26); i < 3 * (kb - 26) + 2; i++)
            st_async128(pb + ro + i * 2048, pb + OFF_BAR + 8 * B_RECV, packbf(res[8 * i], res[8 * i + 1]), packbf(res[8 * i + 2], res[8 * i + 3]),
                        packbf(res[8 * i + 4], res[8 * i + 5]), packbf(res[8 * i + 6], res[8 * i + 7]));
        }
      }
      const float sc0 = __uint_as_float(lds32(hs + 12)), sc1 = __uint_as_float(lds32(hs + 140));
      mbar_wait(bar + 8 * B_HRES, 0);
#pragma unroll
      for (int cc = 0; cc < 4; cc++) {
        const uint4 b = lds128(sb + OFF_RED + t * 64 + cc * 16);
#pragma unroll
        for (int h = 0; h < 2; h++) {
          const int row = 64 * wg + 16 * w + 8 * h + g;
          const uint4 v = lds128(sb + OFF_X + row * 256 + t * 64 + ((cc ^ ((2 * row + (t >> 1)) & 3)) << 4));
          const uint32_t hb[4] = {badd2(v.x, b.x), badd2(v.y, b.y), badd2(v.z, b.z), badd2(v.w, b.w)};
#pragma unroll
          for (int q = 0; q < 4; q++) { res[16 * cc + 4 * q + 2 * h] = bflo(hb[q]); res[16 * cc + 4 * q + 2 * h + 1] = bfhi(hb[q]); }
        }
      }
      mbar_wait(bar + 8 * B_RECV, 0);
      if (tid == 0) TS(10);
#pragma unroll
      for (int i = 0; i < 8; i++) {
        const uint4 v = lds128(sb + ro + i * 2048);
        const uint32_t vv[4] = {v.x, v.y, v.z, v.w};
#pragma unroll
        for (int e = 0; e < 4; e++) {
          const float sc = (e & 1) ? sc1 : sc0;
          res[8 * i + 2 * e] = fmaf(bflo(vv[e]), sc, res[8 * i + 2 * e]);
          res[8 * i + 2 * e + 1] = fmaf(bfhi(vv[e]), sc, res[8 * i + 2 * e + 1]);
        }
      }
      bar_sync(3 + wg, 128);
      wg_wait<0>();
      rename<0, 64>(acc);
      if (tid == 0) TS(8);
      const uint32_t ob = sb + OFF_X + wg * 16384;
#pragma unroll
      for (int mu = 0; mu < 16; mu += 2) {
        const float* a = acc + 4 * mu;
        const float* q = res + 4 * mu;
        stsm4(ob + (mu >> 3) * 8192 + soff + (sx ^ ((mu & 6) << 4)),
              packbf(fmaf(a[0], sc0, q[0]), fmaf(a[1], sc0, q[1])), packbf(fmaf(a[2], sc1, q[2]), fmaf(a[3], sc1, q[3])),
              packbf(fmaf(a[4], sc0, q[4]), fmaf(a[5], sc0, q[5])), packbf(fmaf(a[6], sc1, q[6]), fmaf(a[7], sc1, q[7])));
      }
      fence_async_smem();
      bar_sync(3 + wg, 128);
      if (w == 0 && lane == 0) {
        tma_store(&P.tm_out, ob, 128 * j, 128 * m + 64 * wg);
        tma_store(&P.tm_out, ob + 8192, 128 * j + 64, 128 * m + 64 * wg);
        bulk_commit();
        bulk_wait_read();
        if (tid == 0) TS(9);
      }
    }
  } else if (warp == 8) {
    cluster_wait();
    if (lane == 0) {
#pragma unroll 1
      for (int i = 1; i < 8; i++) {
        if (i >= 5) mbar_wait(bar + 8 * (B_KVFREE + i - 5), 0);
        const uint32_t dst = sb + off_kv(i) + rank * KV_BOX;
        tma3d_mc(dst, &P.tm_k, bar + 8 * (B_KVFULL + i), 8 * (c & ~1), 32 * i + 16 * rank - 1, 0);
        tma3d_mc(dst + 2 * KV_BOX, &P.tm_v, bar + 8 * (B_KVFULL + i), 8 * (c & ~1), 32 * i + 16 * rank - 1, 0);
      }
      const uint32_t epoch = ldg_relaxed(g_epoch + c) + 1;
      mbar_wait(bar + 8 * (B_KVFULL + KV_GATE), 0);
#pragma unroll 1
      for (int ch = 2; ch < 8; ch++) {
        if (ch == 4) prefetch_l2(P.x + (size_t)(128 * m + 16 * j) * D, 16 * D * 2);
        mbar_expect_tx(bar + 8 * (B_KFULL + ch), 4080);
        bulk_g2s(sb + off_T(ch >> 1) + 2 * UT_SIZE + (ch & 1) * KT_SIZE + 32, P.ssm_k + (size_t)(8 * c + ch) * S + 8, 4080, bar + 8 * (B_KFULL + ch));
      }
      prefetch_tmap(&P.tm_h); prefetch_tmap(&P.tm_w1); prefetch_tmap(&P.tm_act); prefetch_tmap(&P.tm_w2);
      prefetch_tmap(&P.tm_actst); prefetch_tmap(&P.tm_hres); prefetch_tmap(&P.tm_out);
      mbar_wait(bar + 8 * (B_KFULL + 7), 0);
      TS(31);
      prefetch_l2(P.w1 + (size_t)c * 8 * F, 8 * F * 2);
#pragma unroll 1
      for (int it = 0; it < 32; it++) {
        const int s = it & 3, kb = it & 15, tile = it >> 4;
        mbar_wait(bar + 8 * (it < 2 ? B_ZDONE + 1 : it == 2 ? B_ZDONE + 2 : it == 3 ? B_YFULL + 15 : B_EMPTY + s), it < 4 ? 0 : ((it >> 2) - 1) & 1);
        if (it < 4) fence_async_smem();
        const uint32_t sa = sb + s * 49152, fb = bar + 8 * (B_FULL + s);
        const int nb = tile ? 3 : 4, n0 = 448 * j + 256 * tile;
        mbar_expect_tx(fb, 16384 + nb * 8192);
#pragma unroll 1
        for (int i = 0; i < nb; i++) tma3d(sa + 16384 + i * 8192, &P.tm_w1, fb, n0 + 64 * i, 2 * (kb >> 2), 32 * (kb & 3));
        if (it < 16 && (it & 3) == 0) { wait_count(g_hcnt + ((it >> 2) * 16 + m) * 32, epoch * 8); fence_async_global(); TS(11 + (it >> 2)); }
        tma2d(sa, &P.tm_h, fb, 64 * kb, 128 * m);
        if (it == 8) prefetch_l2(P.w2 + (size_t)c * 28 * D, 28 * D * 2);
      }
      mbar_wait(bar + 8 * B_XFREE, 0);
#pragma unroll 1
      for (int kb = 0; kb < 30; kb++) {
        const int s = kb & 3;
        mbar_wait(bar + 8 * (B_EMPTY + s), ((kb >> 2) + 1) & 1);
        if (kb == 3) mbar_wait(bar + 8 * B_SFREE, 0);
        if (kb == 27) mbar_arrive_c(mapa(bar + 8 * B_PEER, rank ^ 1), 1);
        const int t1 = kb < 26 ? 10 * rank + kb - 16 : kb - 6;
        const int col = kb < 16 ? 448 * (4 * rank + (kb >> 2)) + 64 * (kb & 3) : 448 * (t1 / 3) + 256 + 64 * (t1 % 3);
        const uint32_t sa = sb + s * 49152, fb = bar + 8 * (B_FULL + s);
        const int nb = kb < 26 ? 4 : 2;
        mbar_expect_tx(fb, 16384 + nb * 8192);
#pragma unroll 1
        for (int i = 0; i < nb; i++) tma2d(sa + 16384 + i * 8192, &P.tm_w2, fb, 128 * (j ^ (i >> 1)) + 64 * (i & 1), col);
        if ((kb & 15) == 0) { wait_count(g_acnt + ((kb >> 4) * 16 + m) * 32, epoch * 8); fence_async_global(); TS(15 + (kb >> 4)); }
        tma2d(sa, &P.tm_act, fb, col, 128 * m);
      }
    }
  } else {
    const int zw = warp - 9;
    {
      uint32_t W[4][4];
      const uint4* wp = (const uint4*)(P.shift_k + (size_t)32 * c);
#pragma unroll
      for (int p = 0; p < 4; p++) {
        const uint4 v = __ldg(wp + p);
        W[0][p] = __byte_perm(v.x, v.z, 0x5410); W[1][p] = __byte_perm(v.x, v.z, 0x7632);
        W[2][p] = __byte_perm(v.y, v.w, 0x5410); W[3][p] = __byte_perm(v.y, v.w, 0x7632);
      }
      cluster_wait();
#pragma unroll 1
      for (int st = zw; st < 8; st = st < 3 ? st + 3 : st == 3 ? 8 : st + 2) {
        mbar_wait(bar + 8 * (B_KVFULL + st), 0);
        if (lane == 0) TS(48 + st);
        const uint32_t ka = sb + off_kv(st) + (lane >> 4) * KV_BOX + (lane & 15) * 32 + rank * 16;
        uint32_t k[12][4], v[9][4];
#pragma unroll
        for (int i = 0; i < 12; i++) {
          const uint32_t o = i < 4 ? (4 + i) * 544 : (i - 4) * 544 + 32;
          const uint4 a = lds128(ka + o);
          k[i][0] = a.x; k[i][1] = a.y; k[i][2] = a.z; k[i][3] = a.w;
          if (i >= 3) {
            const uint4 b = lds128(ka + 2 * KV_BOX + o);
            v[i - 3][0] = b.x; v[i - 3][1] = b.y; v[i - 3][2] = b.z; v[i - 3][3] = b.w;
          }
        }
#pragma unroll
        for (int p = 0; p < 4; p++) {
          uint32_t u[9];
#pragma unroll
          for (int i = 0; i < 9; i++)
            u[i] = bmul2(bfma2(k[i + 3][p], W[0][p], bfma2(k[i + 2][p], W[1][p], bfma2(k[i + 1][p], W[2][p], bmul2(k[i][p], W[3][p])))), v[i][p]);
          const uint32_t ta = sb + off_T(p) + 16 + (32 * st + lane) * 16;
#pragma unroll
          for (int e = 0; e < 2; e++) {
            const uint32_t sel = e ? 0x7632 : 0x5410;
            sts128(ta + e * UT_SIZE, __byte_perm(u[2], u[1], sel), __byte_perm(u[4], u[3], sel), __byte_perm(u[6], u[5], sel), __byte_perm(u[8], u[7], sel));
            sts128(ta + e * UT_SIZE + UT_COPY, __byte_perm(u[1], u[0], sel), __byte_perm(u[3], u[2], sel), __byte_perm(u[5], u[4], sel), __byte_perm(u[7], u[6], sel));
          }
          if (p == 0) {
            __syncwarp();
            if (lane == 0) mbar_arrive(bar + 8 * (B_UFULL + st));
            if (st < 3 && lane < 2) mbar_arrive_c(mapa(bar + 8 * (B_KVFREE + st), lane), 1);
          }
        }
        __syncwarp();
        if (lane == 0) { mbar_arrive(bar + 8 * B_UREST); TS(56 + st); }
      }
    }
    const uint32_t epoch = ldg_relaxed(g_epoch + c) + 1;
    const uint32_t par = epoch & 1;
    if (zw == 0) {
      {
        uint4 p[2][8];
        mbar_wait(bar + 8 * B_YFULL, 0);
#pragma unroll
        for (int i = 0; i < 8; i++) p[0][i] = lds128(sb + OFF_X + lane * 16 + i * YW);
#pragma unroll 1
        for (int qt = 0; qt < 16; qt++) {
          uint32_t* zp = g_z + (size_t)((qt >> 2) * NCTA + c) * S + (qt & 3) * 512 + (lane >> 2) * 32 + (lane & 3) * 4;
#pragma unroll
          for (int k = 0; k < 2; k++) {
            const int nq = min(qt + k, 15);
            const uint32_t yb = sb + off_Y(nq >> 2) + (nq & 3) * 1024 + (k ^ 1) * 512 + lane * 16;
            if (k == 0) {
#pragma unroll
              for (int i = 0; i < 8; i++) p[1][i] = lds128(yb + i * YW);
            }
            uint32_t a[4], b[4];
            const uint4* pp = p[k];
            a[0] = badd2(badd2(pp[0].x, pp[1].x), badd2(pp[2].x, pp[3].x)); b[0] = badd2(badd2(pp[4].x, pp[5].x), badd2(pp[6].x, pp[7].x));
            a[1] = badd2(badd2(pp[0].y, pp[1].y), badd2(pp[2].y, pp[3].y)); b[1] = badd2(badd2(pp[4].y, pp[5].y), badd2(pp[6].y, pp[7].y));
            a[2] = badd2(badd2(pp[0].z, pp[1].z), badd2(pp[2].z, pp[3].z)); b[2] = badd2(badd2(pp[4].z, pp[5].z), badd2(pp[6].z, pp[7].z));
            a[3] = badd2(badd2(pp[0].w, pp[1].w), badd2(pp[2].w, pp[3].w)); b[3] = badd2(badd2(pp[4].w, pp[5].w), badd2(pp[6].w, pp[7].w));
#pragma unroll
            for (int hf = 0; hf < 2; hf++)
              stg_b128(zp + k * 256 + hf * 16, (__byte_perm(a[2 * hf], b[2 * hf], 0x5410) & ~1u) | par, __byte_perm(a[2 * hf], b[2 * hf], 0x7632),
                       __byte_perm(a[2 * hf + 1], b[2 * hf + 1], 0x5410), __byte_perm(a[2 * hf + 1], b[2 * hf + 1], 0x7632));
            if (k == 1) {
              if ((qt & 3) == 3) {
                __syncwarp();
                if (lane == 0) { mbar_arrive(bar + 8 * (B_ZDONE + (qt >> 2))); TS(17 + (qt >> 2)); }
              }
              mbar_wait(bar + 8 * (B_YFULL + nq), 0);
#pragma unroll
              for (int i = 0; i < 8; i++) p[0][i] = lds128(yb + i * YW);
            }
          }
        }
      }
#pragma unroll 1
      for (int tile = 0; tile < 2; tile++) {
        const int n0 = 448 * j + 256 * tile;
        if (tile == 0 || m < 12) {
          float cs[8];
#pragma unroll
          for (int i = 0; i < 8; i++) cs[i] = 0.f;
          const __nv_bfloat16* wp = P.w1 + (size_t)(lane >> 1) * F + n0 + 16 * m + 8 * (lane & 1);
          const uint32_t bv = __ldg((const unsigned short*)P.b1 + n0 + 16 * m + 8 * (lane & 1) + ((lane >> 1) & 7));
#pragma unroll 1
          for (int b = 0; b < 2; b++) {
            uint4 v[32];
#pragma unroll
            for (int i = 0; i < 32; i++) v[i] = __ldg((const uint4*)(wp + (size_t)(32 * b + i) * 16 * F));
#pragma unroll
            for (int i = 0; i < 32; i += 4) {
              const uint32_t a0 = badd2(badd2(v[i].x, v[i + 1].x), badd2(v[i + 2].x, v[i + 3].x)), a1 = badd2(badd2(v[i].y, v[i + 1].y), badd2(v[i + 2].y, v[i + 3].y));
              const uint32_t a2 = badd2(badd2(v[i].z, v[i + 1].z), badd2(v[i + 2].z, v[i + 3].z)), a3 = badd2(badd2(v[i].w, v[i + 1].w), badd2(v[i + 2].w, v[i + 3].w));
              cs[0] += bflo(a0); cs[1] += bfhi(a0); cs[2] += bflo(a1); cs[3] += bfhi(a1);
              cs[4] += bflo(a2); cs[5] += bfhi(a2); cs[6] += bflo(a3); cs[7] += bfhi(a3);
            }
          }
#pragma unroll 1
          for (int o = 2; o < 32; o <<= 1) {
#pragma unroll
            for (int i = 0; i < 8; i++) cs[i] += __shfl_xor_sync(0xffffffffu, cs[i], o);
          }
          float cv = cs[0];
#pragma unroll
          for (int i = 1; i < 8; i++) cv = ((lane >> 1) & 7) == i ? cs[i] : cv;
          const uint32_t hi = packbf(cv, 0.f), lo = packbf(cv - bflo(hi), 0.f);
          if (lane < 16) stg_b128(g_baug + n0 + 16 * m + 8 * (lane & 1) + (lane >> 1), hi | (lo << 16), hi | (bv << 16), bv, epoch);
        }
        uint4 v[8], hv[4];
        int it = 0;
        while (true) {
          bool ok = true;
#pragma unroll
          for (int i = 0; i < 8; i++) v[i] = ldg_b128(g_baug + n0 + min(lane + 32 * i, tile ? 191 : 255));
#pragma unroll
          for (int i = 0; i < 4; i++) hv[i] = ldg_b128(g_hstat + 128 * m + lane + 32 * i);
#pragma unroll
          for (int i = 0; i < 8; i++) ok = ok && v[i].w == epoch;
#pragma unroll
          for (int i = 0; i < 4; i++) ok = ok && (hv[i].z >> 16) == (epoch & 0xffffu);
          if (__all_sync(0xffffffffu, ok)) break;
          __nanosleep(200);
          if (++it > (1 << 20)) __trap();
        }
        if (tile) mbar_wait(bar + 8 * B_XFREE, 0);
#pragma unroll
        for (int i = 0; i < 8; i++) {
          sts128(sb + OFF_X + (lane + 32 * i) * 16, v[i].x, v[i].y, v[i].z, 0);
          sts128(sb + OFF_X + 16384 + (lane + 32 * i) * 16, v[i].x, v[i].y, v[i].z, 0);
        }
        if (tile == 0) {
#pragma unroll
          for (int i = 0; i < 4; i++) sts128(sb + OFF_HS + (lane + 32 * i) * 16, hv[i].x, hv[i].y, hv[i].z & 0xffffu, hv[i].w);
        } else {
          const uint32_t* b2p = (const uint32_t*)(P.b2 + 128 * j);
          ((uint32_t*)(smem + OFF_RED))[(lane & 3) * 16 + (lane >> 2)] = __ldg(b2p + lane);
          ((uint32_t*)(smem + OFF_RED))[(lane & 3) * 16 + 8 + (lane >> 2)] = __ldg(b2p + 32 + lane);
        }
        fence_async_smem();
        __syncwarp();
        if (lane == 0) { mbar_arrive(bar + 8 * B_CSFULL); TS(21 + 19 * tile); }
      }
    } else {
      const int hw = zw - 1, rowb = 128 * m + 16 * j;
      const int q = lane & 3, i0 = 64 * hw + (lane >> 2), row0 = rowb + 4 * q;
      const uint4* xp = (const uint4*)(P.x + (size_t)row0 * D) + i0;
      const uint32_t* zp0 = g_z + (size_t)i0 * S + (rowb & ~31) + (q & 1) * 16 + (((rowb >> 3) & 2) + (q >> 1)) * 4;
      uint32_t* hp = (uint32_t*)(g_h + (size_t)row0 * D) + i0;
      float2* red = (float2*)(smem + OFF_RED);
      uint32_t xr[4][8][2];
      uint4 zv[8];
      float t1[4], t2[4];
      auto chain8 = [](const uint32_t* v, uint32_t pv, float& s1, float& s2) {
        uint32_t c1 = 0, c2 = 0;
#pragma unroll
        for (int i = 0; i < 8; i++) {
          const uint32_t dd = bsub2(v[i], pv);
          c1 = i ? badd2(c1, dd) : dd;
          c2 = i ? bfma2(dd, dd, c2) : bmul2(dd, dd);
        }
        s1 += bflo(c1) + bfhi(c1);
        s2 += bflo(c2) + bfhi(c2);
      };
      auto reduce_rows = [&](const uint32_t* pv) {
#pragma unroll
        for (int a = 0; a < 4; a++) {
          const float pf = bflo(pv[a]);
          t2[a] = fmaf(pf, fmaf(pf, 64.f, 2.f * t1[a]), t2[a]);
          t1[a] = fmaf(pf, 64.f, t1[a]);
        }
#pragma unroll
        for (int o = 4; o < 32; o <<= 1) {
#pragma unroll
          for (int a = 0; a < 4; a++) { t1[a] += __shfl_xor_sync(0xffffffffu, t1[a], o); t2[a] += __shfl_xor_sync(0xffffffffu, t2[a], o); }
        }
        if (lane < 4) {
          ((float4*)red)[hw * 8 + 2 * q] = make_float4(t1[0], t2[0], t1[1], t2[1]);
          ((float4*)red)[hw * 8 + 2 * q + 1] = make_float4(t1[2], t2[2], t1[3], t2[3]);
        }
        bar_sync(1, 64);
      };
      uint32_t pv[4];
      mbar_wait(bar + 8 * (B_KFULL + 5), 0);
      {
        uint4 v[4][8];
#pragma unroll
        for (int a = 0; a < 3; a++)
#pragma unroll
          for (int i = 0; i < 8; i++) v[a][i] = ldg_nc4(xp + a * (D / 8) + 8 * i);
#pragma unroll
        for (int a = 0; a < 4; a++) {
          pv[a] = __byte_perm(v[a][0].x, 0, 0x1010);
          t1[a] = 0.f; t2[a] = 0.f;
#pragma unroll
          for (int i = 0; i < 8; i += 2) {
            const uint32_t w8[8] = {v[a][i].x, v[a][i].y, v[a][i].z, v[a][i].w, v[a][i + 1].x, v[a][i + 1].y, v[a][i + 1].z, v[a][i + 1].w};
            chain8(w8, pv[a], t1[a], t2[a]);
          }
#pragma unroll
          for (int i = 0; i < 8; i++) { xr[a][i][0] = v[a][i].x; xr[a][i][1] = v[a][i].y; }
          if (a == 0) {
#pragma unroll
            for (int i = 0; i < 8; i++) v[3][i] = ldg_nc4(xp + 3 * (D / 8) + 8 * i);
          }
          if (a == 2) {
#pragma unroll
            for (int i = 0; i < 8; i++) zv[i] = ldg_b128(zp0 + (size_t)8 * i * S);
          }
        }
      }
      reduce_rows(pv);
      uint32_t rs2[4], nm2[4];
#pragma unroll
      for (int a = 0; a < 4; a++) {
        const float2 r0 = red[4 * q + a], r1 = red[16 + 4 * q + a];
        const float mu = (r0.x + r1.x) * (1.f / D);
        const float rs = rsqrtf(fmaxf(fmaf(-mu, mu, (r0.y + r1.y) * (1.f / D)), 0.f) + 1e-5f);
        rs2[a] = packbf(rs, rs);
        nm2[a] = packbf(-mu * bflo(rs2[a]), -mu * bflo(rs2[a]));
        t1[a] = 0.f; t2[a] = 0.f;
      }
      if (tid == 320) TS(22);
#pragma unroll 1
      for (int rr = 0; rr < 4; rr += 2) {
#pragma unroll
        for (int e = 0; e < 2; e++) {
          const int r = rr + e;
          const uint32_t* zp = zp0 + (size_t)r * NCTA * S;
          int it = 0;
          while (true) {
            uint32_t bad = 0;
#pragma unroll
            for (int i = 0; i < 8; i++) bad |= zv[i].x ^ par;
            if (__all_sync(0xffffffffu, (bad & 1) == 0)) break;
            mbar_wait(bar + 8 * (B_YFULL + 4 * r + (m >> 2)), 0);
            __nanosleep(100);
#pragma unroll
            for (int i = 0; i < 8; i++) zv[i] = ldg_b128(zp + (size_t)8 * i * S);
            if (++it > (1 << 20)) __trap();
          }
          if (tid == 320) TS(27 + r);
#pragma unroll
          for (int i = 0; i < 8; i++) {
            const uint32_t zz[4] = {zv[i].x, zv[i].y, zv[i].z, zv[i].w};
#pragma unroll
            for (int a = 0; a < 4; a++) {
              xr[a][i][e] = bfma2(bfma2(xr[a][i][e], rs2[a], nm2[a]), zz[a], xr[a][i][e]);
              hp[a * (D / 2) + 128 * r + 8 * i] = xr[a][i][e];
            }
          }
          if (r < 3) {
#pragma unroll
            for (int i = 0; i < 8; i++) zv[i] = ldg_b128(zp + (size_t)(NCTA + 8 * i) * S);
          }
          fence_async_global();
          if (tid == 320) TS(23 + r);
          if (hw == e) {
            bar_sync(5 + r, 64);
            if (lane == 0) { signal(g_hcnt + (r * 16 + m) * 32); TS(32 + r); }
            __syncwarp();
          } else {
            asm volatile("bar.arrive %0, 64;" ::"r"(5 + r) : "memory");
          }
#pragma unroll
          for (int a = 0; a < 4; a++) {
            if (r == 0) pv[a] = __byte_perm(xr[a][0][0], 0, 0x1010);
            const uint32_t w8[8] = {xr[a][0][e], xr[a][1][e], xr[a][2][e], xr[a][3][e], xr[a][4][e], xr[a][5][e], xr[a][6][e], xr[a][7][e]};
            chain8(w8, pv[a], t1[a], t2[a]);
            if (e == 1 && rr == 0) {
#pragma unroll
              for (int i = 0; i < 8; i++) {
                const uint2 v = __ldg((const uint2*)(xp + a * (D / 8) + 8 * i) + 1);
                xr[a][i][0] = v.x; xr[a][i][1] = v.y;
              }
            }
          }
        }
      }
      reduce_rows(pv);
      if (hw == 0 && lane < 16) {
        const float2 r0 = red[lane], r1 = red[16 + lane];
        const float mu = (r0.x + r1.x) * (1.f / D);
        const float var = fmaxf(fmaf(-mu, mu, (r0.y + r1.y) * (1.f / D)), 0.f) + 1e-5f;
        const float sd = sqrtf(var);
        const uint32_t hi = packbf(-mu, sd), lo = packbf(-mu - bflo(hi), sd - bfhi(hi));
        stg_b128(g_hstat + rowb + lane, __byte_perm(hi, 0, 0x1010), __byte_perm(lo, hi, 0x7610), __byte_perm(lo, epoch, 0x5432), __float_as_uint(1.f / var));
        if (lane == 0) TS(43);
      }
      if (hw == 0 && lane == 0) {
#pragma unroll 1
        for (int tile = 0; tile < 2; tile++) {
          mbar_wait(bar + 8 * (B_ADONE + tile), 0);
          const int nb = tile ? 6 : 8;
#pragma unroll 1
          for (int i = nb - 1; i >= 0; i--) {
            if (!(EXP & 1) || tile == 0) tma_store(&P.tm_actst, sb + off_act(tile, i & 1, i >> 1), 448 * j + 256 * tile + 64 * (i >> 1), 128 * m + 64 * (i & 1));
            bulk_commit();
            bulk_wait_read();
            if (tile == 1 && i == 4) mbar_arrive(bar + 8 * B_SFREE);
            if (tile == 0 || i <= 4) __nanosleep(ST_SLEEP);
          }
          if (tile == 0) {
            mbar_arrive(bar + 8 * B_XFREE);
          } else {
            mbar_expect_tx(bar + 8 * B_HRES, 32768);
            tma3d(sb + OFF_X, &P.tm_hres, bar + 8 * B_HRES, 32 * j, 0, 128 * m);
          }
          bulk_wait();
          fence_async_global();
          signal(g_acnt + (tile * 16 + m) * 32);
          TS(41 + tile);
        }
        g_epoch[c] = epoch;
      }
    }
  }
}

typedef CUresult (*PFN_encode)(CUtensorMap*, CUtensorMapDataType, cuuint32_t, void*, const cuuint64_t*, const cuuint64_t*, const cuuint32_t*,
                               const cuuint32_t*, CUtensorMapInterleave, CUtensorMapSwizzle, CUtensorMapL2promotion, CUtensorMapFloatOOBfill);

void encode(PFN_encode enc, CUtensorMap* m, const void* ptr, int rank, const cuuint64_t* dims, const cuuint64_t* strides, const cuuint32_t* box,
            CUtensorMapSwizzle swz) {
  const cuuint32_t es[5] = {1, 1, 1, 1, 1};
  enc(m, CU_TENSOR_MAP_DATA_TYPE_BFLOAT16, rank, (void*)ptr, dims, strides, box, es, CU_TENSOR_MAP_INTERLEAVE_NONE, swz,
      CU_TENSOR_MAP_L2_PROMOTION_L2_128B, CU_TENSOR_MAP_FLOAT_OOB_FILL_NONE);
}

}

extern "C" void kernel_launch(void* const* d_in, const int* in_sizes, int n_in, void* d_out, int out_size) {
  static PFN_encode enc = nullptr;
  static void *p_h = nullptr, *p_act = nullptr;
  if (!enc) {
    cudaDriverEntryPointQueryResult qr;
    cudaGetDriverEntryPoint("cuTensorMapEncodeTiled", (void**)&enc, cudaEnableDefault, &qr);
    cudaGetSymbolAddress(&p_h, g_h);
    cudaGetSymbolAddress(&p_act, g_act);
    cudaFuncSetAttribute(fused_kernel, cudaFuncAttributeMaxDynamicSharedMemorySize, SMEM_BYTES);
  }
  Params P;
  P.x = (const __nv_bfloat16*)d_in[0];
  P.shift_k = (const __nv_bfloat16*)d_in[3];
  P.ssm_k = (const __nv_bfloat16*)d_in[4];
  P.ssm_D = (const __nv_bfloat16*)d_in[5];
  P.w1 = (const __nv_bfloat16*)d_in[7];
  P.b1 = (const __nv_bfloat16*)d_in[8];
  P.w2 = (const __nv_bfloat16*)d_in[9];
  P.b2 = (const __nv_bfloat16*)d_in[10];
  {
    const cuuint64_t dims[3] = {D, S / 8, 8}, str[2] = {8 * D * 2, D * 2};
    const cuuint32_t box[3] = {16, 17, 8};
    encode(enc, &P.tm_k, d_in[1], 3, dims, str, box, CU_TENSOR_MAP_SWIZZLE_NONE);
    encode(enc, &P.tm_v, d_in[2], 3, dims, str, box, CU_TENSOR_MAP_SWIZZLE_NONE);
  }
  {
    const cuuint64_t dims[2] = {D, S}, str[1] = {D * 2};
    const cuuint32_t box[2] = {64, 128}, boxo[2] = {64, 64};
    encode(enc, &P.tm_h, p_h, 2, dims, str, box, CU_TENSOR_MAP_SWIZZLE_128B);
    encode(enc, &P.tm_out, d_out, 2, dims, str, boxo, CU_TENSOR_MAP_SWIZZLE_128B);
  }
  {
    const cuuint64_t dims[3] = {F, 8, D / 8}, str[2] = {F * 2, 8 * F * 2};
    const cuuint32_t box[3] = {64, 2, 32};
    encode(enc, &P.tm_w1, P.w1, 3, dims, str, box, CU_TENSOR_MAP_SWIZZLE_128B);
  }
  {
    const cuuint64_t dims[2] = {F, S}, str[1] = {F * 2};
    const cuuint32_t box[2] = {64, 128}, boxs[2] = {64, 64};
    encode(enc, &P.tm_act, p_act, 2, dims, str, box, CU_TENSOR_MAP_SWIZZLE_128B);
    encode(enc, &P.tm_actst, p_act, 2, dims, str, boxs, CU_TENSOR_MAP_SWIZZLE_128B);
  }
  {
    const cuuint64_t dims[2] = {D, F}, str[1] = {D * 2};
    const cuuint32_t box[2] = {64, 64};
    encode(enc, &P.tm_w2, P.w2, 2, dims, str, box, CU_TENSOR_MAP_SWIZZLE_128B);
  }
  {
    const cuuint64_t dims[3] = {256, 4, S}, str[2] = {512, D * 2};
    const cuuint32_t box[3] = {32, 4, 128};
    encode(enc, &P.tm_hres, p_h, 3, dims, str, box, CU_TENSOR_MAP_SWIZZLE_64B);
  }
  fused_kernel<<<NCTA, NTHREADS, SMEM_BYTES>>>(P);
}
```

```cpp
#include <cuda_runtime.h>
#include <cuda_bf16.h>
#include <cuda.h>
#include <stdint.h>

#define DBG_TS 0
#define KV_GATE 3
#define JGROUP 4
#define NU_MMA 0
#define POLL_SLEEP 60
#define CS_LATE 0
#define ZFENCE 0
#define X_GATE 6
#define START_GATE 0
#define TW 0
#define ORD 1
#define AUG_LAST 0
#define NSMALL 4
#define ZP0 1
#define HINT_DELAY 0
#define ZHINT_DELAY 0
#define PF_EARLY 3
#define EXP 0
#define ST_SLEEP 200

#define STR2(x) #x
#define STR(x) STR2(x)

namespace {

constexpr int S = 2048, D = 1024, F = 3584;
constexpr int NCTA = 128, NTHREADS = 384;
constexpr int NBIG = 28 - NSMALL / 2;

constexpr int UT_COPY = 1040 * 4;
constexpr int UT_SIZE = 2 * UT_COPY;
constexpr int KT_SIZE = 16 + 4096;
constexpr int T_SIZE = 2 * (UT_SIZE + KT_SIZE);
constexpr int KV_BOX = 17 * 8 * 32;
constexpr int KV_SLOT = 4 * KV_BOX;
constexpr int KV_SIZE = 2 * KV_SLOT;
constexpr int YW = 4096 + 96;
constexpr int YBUF = 4 * YW;
constexpr int OFF_T3 = 196608 - T_SIZE;
constexpr int HB_WARP = 4096;
constexpr int OFF_HB = (OFF_T3 - 2 * HB_WARP) & ~1023;
constexpr int OFF_KVB = (OFF_HB - 2 * YBUF) & ~255;
constexpr int OFF_T2 = OFF_KVB - T_SIZE;
constexpr int OFF_KVA = (OFF_T2 - KV_SIZE) & ~255;
constexpr int OFF_T1 = OFF_KVA - T_SIZE;
constexpr int OFF_T0 = OFF_T1 - T_SIZE;
constexpr int OFF_X = 196608;
constexpr int OFF_HS = OFF_X + 32768;
constexpr int OFF_XS = OFF_X + 34304;
constexpr int OFF_RED = OFF_X + 34816;
constexpr int OFF_BAR = OFF_X + 35072;
constexpr int SMEM_BYTES = 232448;
static_assert(OFF_T0 >= KV_SLOT && 2 * YBUF <= KV_SIZE && OFF_X + 2 * YBUF <= OFF_RED && OFF_BAR + 640 <= SMEM_BYTES, "smem map");
static_assert(OFF_KVB + KV_SIZE <= OFF_T3 && OFF_HB >= 147456, "smem map");
static_assert(OFF_KVB + 32864 <= OFF_HB, "x rows");
static_assert(OFF_T2 >= 98304, "stage 1 must only overlap T0,T1,KVA");
static_assert(OFF_T3 >= 147456, "stage 2 must not overlap T3");

enum {
  B_KVFULL = 0, B_KFULL = 8, B_UFULL = 16, B_YFULL = 24  , B_ZFULL = 32  ,
  B_FULL = 40, B_ZDONE = 44  , B_PEER = 16  ,
  B_CSFULL = 48, B_HRES = 49, B_XFREE = 50, B_SFREE = 51, B_RECV = 52  , B_XFULL = 54,
  B_EMPTY = 56, B_KVFREE = 60  , B_XREAD = 63, B_ADONE = 64, B_UREST = 66  , B_XDONE = 68, B_GOT = 69, B_SEND = 70  ,
  B_ZIN = 72  , B_WFULL = 74  , B_HOUT = 76
};

struct Params {
  CUtensorMap tm_k, tm_v, tm_z, tm_hst, tm_h, tm_w1, tm_w1c, tm_act, tm_actst, tm_w2, tm_hres, tm_out;
  const __nv_bfloat16 *x, *shift_k, *ssm_k, *ssm_D, *w1, *b1, *w2, *b2;
};

__device__ __align__(1024) uint32_t g_z[4 * NCTA * S];
__device__ __align__(1024) __nv_bfloat16 g_h[2 * S * D];
__device__ __align__(1024) __nv_bfloat16 g_act[S * F];
__device__ __align__(128) uint4 g_hstat[S];
__device__ __align__(128) uint4 g_baug[F];
enum { C_Z = 0, C_H = 4, C_ACT = 8 };
__device__ __align__(128) uint32_t g_cnt[16 * 32];
#define CNT(i)
#define TSM(idx) do {} while (0)
#define TSDUMP() do {} while (0)
#define TS(slot) do {} while (0)

template<int N> __device__ __forceinline__ void wgmma_rs(float* d, const uint32_t* a, uint64_t db, int sc);
template<int N> __device__ __forceinline__ void wgmma_ss(float* d, uint64_t da, uint64_t db, int sc);
template<> __device__ __forceinline__ void wgmma_rs<16>(float* d, const uint32_t* a, uint64_t db, int sc) {
  asm volatile("{.reg .pred p; setp.ne.b32 p, %13, 0;\n"
  "wgmma.mma_async.sync.aligned.m64n16k16.f32.bf16.bf16 {%0,%1,%2,%3,%4,%5,%6,%7}, {%8,%9,%10,%11}, %12, p, 1, 1, 0;}\n"
  : "+f"(d[0]),"+f"(d[1]),"+f"(d[2]),"+f"(d[3]),"+f"(d[4]),"+f"(d[5]),"+f"(d[6]),"+f"(d[7])
  : "r"(a[0]), "r"(a[1]), "r"(a[2]), "r"(a[3]), "l"(db), "r"(sc));
}
template<> __device__ __forceinline__ void wgmma_rs<32>(float* d, const uint32_t* a, uint64_t db, int sc) {
  asm volatile("{.reg .pred p; setp.ne.b32 p, %21, 0;\n"
  "wgmma.mma_async.sync.aligned.m64n32k16.f32.bf16.bf16 {%0,%1,%2,%3,%4,%5,%6,%7,%8,%9,%10,%11,%12,%13,%14,%15}, {%16,%17,%18,%19}, %20, p, 1, 1, 0;}\n"
  : "+f"(d[0]),"+f"(d[1]),"+f"(d[2]),"+f"(d[3]),"+f"(d[4]),"+f"(d[5]),"+f"(d[6]),"+f"(d[7]),"+f"(d[8]),"+f"(d[9]),"+f"(d[10]),"+f"(d[11]),"+f"(d[12]),"+f"(d[13]),"+f"(d[14]),"+f"(d[15])
  : "r"(a[0]), "r"(a[1]), "r"(a[2]), "r"(a[3]), "l"(db), "r"(sc));
}
template<> __device__ __forceinline__ void wgmma_rs<48>(float* d, const uint32_t* a, uint64_t db, int sc) {
  asm volatile("{.reg .pred p; setp.ne.b32 p, %29, 0;\n"
  "wgmma.mma_async.sync.aligned.m64n48k16.f32.bf16.bf16 {%0,%1,%2,%3,%4,%5,%6,%7,%8,%9,%10,%11,%12,%13,%14,%15,%16,%17,%18,%19,%20,%21,%22,%23}, {%24,%25,%26,%27}, %28, p, 1, 1, 0;}\n"
  : "+f"(d[0]),"+f"(d[1]),"+f"(d[2]),"+f"(d[3]),"+f"(d[4]),"+f"(d[5]),"+f"(d[6]),"+f"(d[7]),"+f"(d[8]),"+f"(d[9]),"+f"(d[10]),"+f"(d[11]),"+f"(d[12]),"+f"(d[13]),"+f"(d[14]),"+f"(d[15]),"+f"(d[16]),"+f"(d[17]),"+f"(d[18]),"+f"(d[19]),"+f"(d[20]),"+f"(d[21]),"+f"(d[22]),"+f"(d[23])
  : "r"(a[0]), "r"(a[1]), "r"(a[2]), "r"(a[3]), "l"(db), "r"(sc));
}
template<> __device__ __forceinline__ void wgmma_rs<64>(float* d, const uint32_t* a, uint64_t db, int sc) {
  asm volatile("{.reg .pred p; setp.ne.b32 p, %37, 0;\n"
  "wgmma.mma_async.sync.aligned.m64n64k16.f32.bf16.bf16 {%0,%1,%2,%3,%4,%5,%6,%7,%8,%9,%10,%11,%12,%13,%14,%15,%16,%17,%18,%19,%20,%21,%22,%23,%24,%25,%26,%27,%28,%29,%30,%31}, {%32,%33,%34,%35}, %36, p, 1, 1, 0;}\n"
  : "+f"(d[0]),"+f"(d[1]),"+f"(d[2]),"+f"(d[3]),"+f"(d[4]),"+f"(d[5]),"+f"(d[6]),"+f"(d[7]),"+f"(d[8]),"+f"(d[9]),"+f"(d[10]),"+f"(d[11]),"+f"(d[12]),"+f"(d[13]),"+f"(d[14]),"+f"(d[15]),"+f"(d[16]),"+f"(d[17]),"+f"(d[18]),"+f"(d[19]),"+f"(d[20]),"+f"(d[21]),"+f"(d[22]),"+f"(d[23]),"+f"(d[24]),"+f"(d[25]),"+f"(d[26]),"+f"(d[27]),"+f"(d[28]),"+f"(d[29]),"+f"(d[30]),"+f"(d[31])
  : "r"(a[0]), "r"(a[1]), "r"(a[2]), "r"(a[3]), "l"(db), "r"(sc));
}
template<> __device__ __forceinline__ void wgmma_rs<80>(float* d, const uint32_t* a, uint64_t db, int sc) {
  asm volatile("{.reg .pred p; setp.ne.b32 p, %45, 0;\n"
  "wgmma.mma_async.sync.aligned.m64n80k16.f32.bf16.bf16 {%0,%1,%2,%3,%4,%5,%6,%7,%8,%9,%10,%11,%12,%13,%14,%15,%16,%17,%18,%19,%20,%21,%22,%23,%24,%25,%26,%27,%28,%29,%30,%31,%32,%33,%34,%35,%36,%37,%38,%39}, {%40,%41,%42,%43}, %44, p, 1, 1, 0;}\n"
  : "+f"(d[0]),"+f"(d[1]),"+f"(d[2]),"+f"(d[3]),"+f"(d[4]),"+f"(d[5]),"+f"(d[6]),"+f"(d[7]),"+f"(d[8]),"+f"(d[9]),"+f"(d[10]),"+f"(d[11]),"+f"(d[12]),"+f"(d[13]),"+f"(d[14]),"+f"(d[15]),"+f"(d[16]),"+f"(d[17]),"+f"(d[18]),"+f"(d[19]),"+f"(d[20]),"+f"(d[21]),"+f"(d[22]),"+f"(d[23]),"+f"(d[24]),"+f"(d[25]),"+f"(d[26]),"+f"(d[27]),"+f"(d[28]),"+f"(d[29]),"+f"(d[30]),"+f"(d[31]),"+f"(d[32]),"+f"(d[33]),"+f"(d[34]),"+f"(d[35]),"+f"(d[36]),"+f"(d[37]),"+f"(d[38]),"+f"(d[39])
  : "r"(a[0]), "r"(a[1]), "r"(a[2]), "r"(a[3]), "l"(db), "r"(sc));
}
template<> __device__ __forceinline__ void wgmma_rs<96>(float* d, const uint32_t* a, uint64_t db, int sc) {
  asm volatile("{.reg .pred p; setp.ne.b32 p, %53, 0;\n"
  "wgmma.mma_async.sync.aligned.m64n96k16.f32.bf16.bf16 {%0,%1,%2,%3,%4,%5,%6,%7,%8,%9,%10,%11,%12,%13,%14,%15,%16,%17,%18,%19,%20,%21,%22,%23,%24,%25,%26,%27,%28,%29,%30,%31,%32,%33,%34,%35,%36,%37,%38,%39,%40,%41,%42,%43,%44,%45,%46,%47}, {%48,%49,%50,%51}, %52, p, 1, 1, 0;}\n"
  : "+f"(d[0]),"+f"(d[1]),"+f"(d[2]),"+f"(d[3]),"+f"(d[4]),"+f"(d[5]),"+f"(d[6]),"+f"(d[7]),"+f"(d[8]),"+f"(d[9]),"+f"(d[10]),"+f"(d[11]),"+f"(d[12]),"+f"(d[13]),"+f"(d[14]),"+f"(d[15]),"+f"(d[16]),"+f"(d[17]),"+f"(d[18]),"+f"(d[19]),"+f"(d[20]),"+f"(d[21]),"+f"(d[22]),"+f"(d[23]),"+f"(d[24]),"+f"(d[25]),"+f"(d[26]),"+f"(d[27]),"+f"(d[28]),"+f"(d[29]),"+f"(d[30]),"+f"(d[31]),"+f"(d[32]),"+f"(d[33]),"+f"(d[34]),"+f"(d[35]),"+f"(d[36]),"+f"(d[37]),"+f"(d[38]),"+f"(d[39]),"+f"(d[40]),"+f"(d[41]),"+f"(d[42]),"+f"(d[43]),"+f"(d[44]),"+f"(d[45]),"+f"(d[46]),"+f"(d[47])
  : "r"(a[0]), "r"(a[1]), "r"(a[2]), "r"(a[3]), "l"(db), "r"(sc));
}
template<> __device__ __forceinline__ void wgmma_rs<112>(float* d, const uint32_t* a, uint64_t db, int sc) {
  asm volatile("{.reg .pred p; setp.ne.b32 p, %61, 0;\n"
  "wgmma.mma_async.sync.aligned.m64n112k16.f32.bf16.bf16 {%0,%1,%2,%3,%4,%5,%6,%7,%8,%9,%10,%11,%12,%13,%14,%15,%16,%17,%18,%19,%20,%21,%22,%23,%24,%25,%26,%27,%28,%29,%30,%31,%32,%33,%34,%35,%36,%37,%38,%39,%40,%41,%42,%43,%44,%45,%46,%47,%48,%49,%50,%51,%52,%53,%54,%55}, {%56,%57,%58,%59}, %60, p, 1, 1, 0;}\n"
  : "+f"(d[0]),"+f"(d[1]),"+f"(d[2]),"+f"(d[3]),"+f"(d[4]),"+f"(d[5]),"+f"(d[6]),"+f"(d[7]),"+f"(d[8]),"+f"(d[9]),"+f"(d[10]),"+f"(d[11]),"+f"(d[12]),"+f"(d[13]),"+f"(d[14]),"+f"(d[15]),"+f"(d[16]),"+f"(d[17]),"+f"(d[18]),"+f"(d[19]),"+f"(d[20]),"+f"(d[21]),"+f"(d[22]),"+f"(d[23]),"+f"(d[24]),"+f"(d[25]),"+f"(d[26]),"+f"(d[27]),"+f"(d[28]),"+f"(d[29]),"+f"(d[30]),"+f"(d[31]),"+f"(d[32]),"+f"(d[33]),"+f"(d[34]),"+f"(d[35]),"+f"(d[36]),"+f"(d[37]),"+f"(d[38]),"+f"(d[39]),"+f"(d[40]),"+f"(d[41]),"+f"(d[42]),"+f"(d[43]),"+f"(d[44]),"+f"(d[45]),"+f"(d[46]),"+f"(d[47]),"+f"(d[48]),"+f"(d[49]),"+f"(d[50]),"+f"(d[51]),"+f"(d[52]),"+f"(d[53]),"+f"(d[54]),"+f"(d[55])
  : "r"(a[0]), "r"(a[1]), "r"(a[2]), "r"(a[3]), "l"(db), "r"(sc));
}
template<> __device__ __forceinline__ void wgmma_rs<128>(float* d, const uint32_t* a, uint64_t db, int sc) {
  asm volatile("{.reg .pred p; setp.ne.b32 p, %69, 0;\n"
  "wgmma.mma_async.sync.aligned.m64n128k16.f32.bf16.bf16 {%0,%1,%2,%3,%4,%5,%6,%7,%8,%9,%10,%11,%12,%13,%14,%15,%16,%17,%18,%19,%20,%21,%22,%23,%24,%25,%26,%27,%28,%29,%30,%31,%32,%33,%34,%35,%36,%37,%38,%39,%40,%41,%42,%43,%44,%45,%46,%47,%48,%49,%50,%51,%52,%53,%54,%55,%56,%57,%58,%59,%60,%61,%62,%63}, {%64,%65,%66,%67}, %68, p, 1, 1, 0;}\n"
  : "+f"(d[0]),"+f"(d[1]),"+f"(d[2]),"+f"(d[3]),"+f"(d[4]),"+f"(d[5]),"+f"(d[6]),"+f"(d[7]),"+f"(d[8]),"+f"(d[9]),"+f"(d[10]),"+f"(d[11]),"+f"(d[12]),"+f"(d[13]),"+f"(d[14]),"+f"(d[15]),"+f"(d[16]),"+f"(d[17]),"+f"(d[18]),"+f"(d[19]),"+f"(d[20]),"+f"(d[21]),"+f"(d[22]),"+f"(d[23]),"+f"(d[24]),"+f"(d[25]),"+f"(d[26]),"+f"(d[27]),"+f"(d[28]),"+f"(d[29]),"+f"(d[30]),"+f"(d[31]),"+f"(d[32]),"+f"(d[33]),"+f"(d[34]),"+f"(d[35]),"+f"(d[36]),"+f"(d[37]),"+f"(d[38]),"+f"(d[39]),"+f"(d[40]),"+f"(d[41]),"+f"(d[42]),"+f"(d[43]),"+f"(d[44]),"+f"(d[45]),"+f"(d[46]),"+f"(d[47]),"+f"(d[48]),"+f"(d[49]),"+f"(d[50]),"+f"(d[51]),"+f"(d[52]),"+f"(d[53]),"+f"(d[54]),"+f"(d[55]),"+f"(d[56]),"+f"(d[57]),"+f"(d[58]),"+f"(d[59]),"+f"(d[60]),"+f"(d[61]),"+f"(d[62]),"+f"(d[63])
  : "r"(a[0]), "r"(a[1]), "r"(a[2]), "r"(a[3]), "l"(db), "r"(sc));
}
template<> __device__ __forceinline__ void wgmma_rs<144>(float* d, const uint32_t* a, uint64_t db, int sc) {
  asm volatile("{.reg .pred p; setp.ne.b32 p, %77, 0;\n"
  "wgmma.mma_async.sync.aligned.m64n144k16.f32.bf16.bf16 {%0,%1,%2,%3,%4,%5,%6,%7,%8,%9,%10,%11,%12,%13,%14,%15,%16,%17,%18,%19,%20,%21,%22,%23,%24,%25,%26,%27,%28,%29,%30,%31,%32,%33,%34,%35,%36,%37,%38,%39,%40,%41,%42,%43,%44,%45,%46,%47,%48,%49,%50,%51,%52,%53,%54,%55,%56,%57,%58,%59,%60,%61,%62,%63,%64,%65,%66,%67,%68,%69,%70,%71}, {%72,%73,%74,%75}, %76, p, 1, 1, 0;}\n"
  : "+f"(d[0]),"+f"(d[1]),"+f"(d[2]),"+f"(d[3]),"+f"(d[4]),"+f"(d[5]),"+f"(d[6]),"+f"(d[7]),"+f"(d[8]),"+f"(d[9]),"+f"(d[10]),"+f"(d[11]),"+f"(d[12]),"+f"(d[13]),"+f"(d[14]),"+f"(d[15]),"+f"(d[16]),"+f"(d[17]),"+f"(d[18]),"+f"(d[19]),"+f"(d[20]),"+f"(d[21]),"+f"(d[22]),"+f"(d[23]),"+f"(d[24]),"+f"(d[25]),"+f"(d[26]),"+f"(d[27]),"+f"(d[28]),"+f"(d[29]),"+f"(d[30]),"+f"(d[31]),"+f"(d[32]),"+f"(d[33]),"+f"(d[34]),"+f"(d[35]),"+f"(d[36]),"+f"(d[37]),"+f"(d[38]),"+f"(d[39]),"+f"(d[40]),"+f"(d[41]),"+f"(d[42]),"+f"(d[43]),"+f"(d[44]),"+f"(d[45]),"+f"(d[46]),"+f"(d[47]),"+f"(d[48]),"+f"(d[49]),"+f"(d[50]),"+f"(d[51]),"+f"(d[52]),"+f"(d[53]),"+f"(d[54]),"+f"(d[55]),"+f"(d[56]),"+f"(d[57]),"+f"(d[58]),"+f"(d[59]),"+f"(d[60]),"+f"(d[61]),"+f"(d[62]),"+f"(d[63]),"+f"(d[64]),"+f"(d[65]),"+f"(d[66]),"+f"(d[67]),"+f"(d[68]),"+f"(d[69]),"+f"(d[70]),"+f"(d[71])
  : "r"(a[0]), "r"(a[1]), "r"(a[2]), "r"(a[3]), "l"(db), "r"(sc));
}
template<> __device__ __forceinline__ void wgmma_rs<160>(float* d, const uint32_t* a, uint64_t db, int sc) {
  asm volatile("{.reg .pred p; setp.ne.b32 p, %85, 0;\n"
  "wgmma.mma_async.sync.aligned.m64n160k16.f32.bf16.bf16 {%0,%1,%2,%3,%4,%5,%6,%7,%8,%9,%10,%11,%12,%13,%14,%15,%16,%17,%18,%19,%20,%21,%22,%23,%24,%25,%26,%27,%28,%29,%30,%31,%32,%33,%34,%35,%36,%37,%38,%39,%40,%41,%42,%43,%44,%45,%46,%47,%48,%49,%50,%51,%52,%53,%54,%55,%56,%57,%58,%59,%60,%61,%62,%63,%64,%65,%66,%67,%68,%69,%70,%71,%72,%73,%74,%75,%76,%77,%78,%79}, {%80,%81,%82,%83}, %84, p, 1, 1, 0;}\n"
  : "+f"(d[0]),"+f"(d[1]),"+f"(d[2]),"+f"(d[3]),"+f"(d[4]),"+f"(d[5]),"+f"(d[6]),"+f"(d[7]),"+f"(d[8]),"+f"(d[9]),"+f"(d[10]),"+f"(d[11]),"+f"(d[12]),"+f"(d[13]),"+f"(d[14]),"+f"(d[15]),"+f"(d[16]),"+f"(d[17]),"+f"(d[18]),"+f"(d[19]),"+f"(d[20]),"+f"(d[21]),"+f"(d[22]),"+f"(d[23]),"+f"(d[24]),"+f"(d[25]),"+f"(d[26]),"+f"(d[27]),"+f"(d[28]),"+f"(d[29]),"+f"(d[30]),"+f"(d[31]),"+f"(d[32]),"+f"(d[33]),"+f"(d[34]),"+f"(d[35]),"+f"(d[36]),"+f"(d[37]),"+f"(d[38]),"+f"(d[39]),"+f"(d[40]),"+f"(d[41]),"+f"(d[42]),"+f"(d[43]),"+f"(d[44]),"+f"(d[45]),"+f"(d[46]),"+f"(d[47]),"+f"(d[48]),"+f"(d[49]),"+f"(d[50]),"+f"(d[51]),"+f"(d[52]),"+f"(d[53]),"+f"(d[54]),"+f"(d[55]),"+f"(d[56]),"+f"(d[57]),"+f"(d[58]),"+f"(d[59]),"+f"(d[60]),"+f"(d[61]),"+f"(d[62]),"+f"(d[63]),"+f"(d[64]),"+f"(d[65]),"+f"(d[66]),"+f"(d[67]),"+f"(d[68]),"+f"(d[69]),"+f"(d[70]),"+f"(d[71]),"+f"(d[72]),"+f"(d[73]),"+f"(d[74]),"+f"(d[75]),"+f"(d[76]),"+f"(d[77]),"+f"(d[78]),"+f"(d[79])
  : "r"(a[0]), "r"(a[1]), "r"(a[2]), "r"(a[3]), "l"(db), "r"(sc));
}
template<> __device__ __forceinline__ void wgmma_rs<176>(float* d, const uint32_t* a, uint64_t db, int sc) {
  asm volatile("{.reg .pred p; setp.ne.b32 p, %93, 0;\n"
  "wgmma.mma_async.sync.aligned.m64n176k16.f32.bf16.bf16 {%0,%1,%2,%3,%4,%5,%6,%7,%8,%9,%10,%11,%12,%13,%14,%15,%16,%17,%18,%19,%20,%21,%22,%23,%24,%25,%26,%27,%28,%29,%30,%31,%32,%33,%34,%35,%36,%37,%38,%39,%40,%41,%42,%43,%44,%45,%46,%47,%48,%49,%50,%51,%52,%53,%54,%55,%56,%57,%58,%59,%60,%61,%62,%63,%64,%65,%66,%67,%68,%69,%70,%71,%72,%73,%74,%75,%76,%77,%78,%79,%80,%81,%82,%83,%84,%85,%86,%87}, {%88,%89,%90,%91}, %92, p, 1, 1, 0;}\n"
  : "+f"(d[0]),"+f"(d[1]),"+f"(d[2]),"+f"(d[3]),"+f"(d[4]),"+f"(d[5]),"+f"(d[6]),"+f"(d[7]),"+f"(d[8]),"+f"(d[9]),"+f"(d[10]),"+f"(d[11]),"+f"(d[12]),"+f"(d[13]),"+f"(d[14]),"+f"(d[15]),"+f"(d[16]),"+f"(d[17]),"+f"(d[18]),"+f"(d[19]),"+f"(d[20]),"+f"(d[21]),"+f"(d[22]),"+f"(d[23]),"+f"(d[24]),"+f"(d[25]),"+f"(d[26]),"+f"(d[27]),"+f"(d[28]),"+f"(d[29]),"+f"(d[30]),"+f"(d[31]),"+f"(d[32]),"+f"(d[33]),"+f"(d[34]),"+f"(d[35]),"+f"(d[36]),"+f"(d[37]),"+f"(d[38]),"+f"(d[39]),"+f"(d[40]),"+f"(d[41]),"+f"(d[42]),"+f"(d[43]),"+f"(d[44]),"+f"(d[45]),"+f"(d[46]),"+f"(d[47]),"+f"(d[48]),"+f"(d[49]),"+f"(d[50]),"+f"(d[51]),"+f"(d[52]),"+f"(d[53]),"+f"(d[54]),"+f"(d[55]),"+f"(d[56]),"+f"(d[57]),"+f"(d[58]),"+f"(d[59]),"+f"(d[60]),"+f"(d[61]),"+f"(d[62]),"+f"(d[63]),"+f"(d[64]),"+f"(d[65]),"+f"(d[66]),"+f"(d[67]),"+f"(d[68]),"+f"(d[69]),"+f"(d[70]),"+f"(d[71]),"+f"(d[72]),"+f"(d[73]),"+f"(d[74]),"+f"(d[75]),"+f"(d[76]),"+f"(d[77]),"+f"(d[78]),"+f"(d[79]),"+f"(d[80]),"+f"(d[81]),"+f"(d[82]),"+f"(d[83]),"+f"(d[84]),"+f"(d[85]),"+f"(d[86]),"+f"(d[87])
  : "r"(a[0]), "r"(a[1]), "r"(a[2]), "r"(a[3]), "l"(db), "r"(sc));
}
template<> __device__ __forceinline__ void wgmma_rs<192>(float* d, const uint32_t* a, uint64_t db, int sc) {
  asm volatile("{.reg .pred p; setp.ne.b32 p, %101, 0;\n"
  "wgmma.mma_async.sync.aligned.m64n192k16.f32.bf16.bf16 {%0,%1,%2,%3,%4,%5,%6,%7,%8,%9,%10,%11,%12,%13,%14,%15,%16,%17,%18,%19,%20,%21,%22,%23,%24,%25,%26,%27,%28,%29,%30,%31,%32,%33,%34,%35,%36,%37,%38,%39,%40,%41,%42,%43,%44,%45,%46,%47,%48,%49,%50,%51,%52,%53,%54,%55,%56,%57,%58,%59,%60,%61,%62,%63,%64,%65,%66,%67,%68,%69,%70,%71,%72,%73,%74,%75,%76,%77,%78,%79,%80,%81,%82,%83,%84,%85,%86,%87,%88,%89,%90,%91,%92,%93,%94,%95}, {%96,%97,%98,%99}, %100, p, 1, 1, 0;}\n"
  : "+f"(d[0]),"+f"(d[1]),"+f"(d[2]),"+f"(d[3]),"+f"(d[4]),"+f"(d[5]),"+f"(d[6]),"+f"(d[7]),"+f"(d[8]),"+f"(d[9]),"+f"(d[10]),"+f"(d[11]),"+f"(d[12]),"+f"(d[13]),"+f"(d[14]),"+f"(d[15]),"+f"(d[16]),"+f"(d[17]),"+f"(d[18]),"+f"(d[19]),"+f"(d[20]),"+f"(d[21]),"+f"(d[22]),"+f"(d[23]),"+f"(d[24]),"+f"(d[25]),"+f"(d[26]),"+f"(d[27]),"+f"(d[28]),"+f"(d[29]),"+f"(d[30]),"+f"(d[31]),"+f"(d[32]),"+f"(d[33]),"+f"(d[34]),"+f"(d[35]),"+f"(d[36]),"+f"(d[37]),"+f"(d[38]),"+f"(d[39]),"+f"(d[40]),"+f"(d[41]),"+f"(d[42]),"+f"(d[43]),"+f"(d[44]),"+f"(d[45]),"+f"(d[46]),"+f"(d[47]),"+f"(d[48]),"+f"(d[49]),"+f"(d[50]),"+f"(d[51]),"+f"(d[52]),"+f"(d[53]),"+f"(d[54]),"+f"(d[55]),"+f"(d[56]),"+f"(d[57]),"+f"(d[58]),"+f"(d[59]),"+f"(d[60]),"+f"(d[61]),"+f"(d[62]),"+f"(d[63]),"+f"(d[64]),"+f"(d[65]),"+f"(d[66]),"+f"(d[67]),"+f"(d[68]),"+f"(d[69]),"+f"(d[70]),"+f"(d[71]),"+f"(d[72]),"+f"(d[73]),"+f"(d[74]),"+f"(d[75]),"+f"(d[76]),"+f"(d[77]),"+f"(d[78]),"+f"(d[79]),"+f"(d[80]),"+f"(d[81]),"+f"(d[82]),"+f"(d[83]),"+f"(d[84]),"+f"(d[85]),"+f"(d[86]),"+f"(d[87]),"+f"(d[88]),"+f"(d[89]),"+f"(d[90]),"+f"(d[91]),"+f"(d[92]),"+f"(d[93]),"+f"(d[94]),"+f"(d[95])
  : "r"(a[0]), "r"(a[1]), "r"(a[2]), "r"(a[3]), "l"(db), "r"(sc));
}
template<> __device__ __forceinline__ void wgmma_rs<208>(float* d, const uint32_t* a, uint64_t db, int sc) {
  asm volatile("{.reg .pred p; setp.ne.b32 p, %109, 0;\n"
  "wgmma.mma_async.sync.aligned.m64n208k16.f32.bf16.bf16 {%0,%1,%2,%3,%4,%5,%6,%7,%8,%9,%10,%11,%12,%13,%14,%15,%16,%17,%18,%19,%20,%21,%22,%23,%24,%25,%26,%27,%28,%29,%30,%31,%32,%33,%34,%35,%36,%37,%38,%39,%40,%41,%42,%43,%44,%45,%46,%47,%48,%49,%50,%51,%52,%53,%54,%55,%56,%57,%58,%59,%60,%61,%62,%63,%64,%65,%66,%67,%68,%69,%70,%71,%72,%73,%74,%75,%76,%77,%78,%79,%80,%81,%82,%83,%84,%85,%86,%87,%88,%89,%90,%91,%92,%93,%94,%95,%96,%97,%98,%99,%100,%101,%102,%103}, {%104,%105,%106,%107}, %108, p, 1, 1, 0;}\n"
  : "+f"(d[0]),"+f"(d[1]),"+f"(d[2]),"+f"(d[3]),"+f"(d[4]),"+f"(d[5]),"+f"(d[6]),"+f"(d[7]),"+f"(d[8]),"+f"(d[9]),"+f"(d[10]),"+f"(d[11]),"+f"(d[12]),"+f"(d[13]),"+f"(d[14]),"+f"(d[15]),"+f"(d[16]),"+f"(d[17]),"+f"(d[18]),"+f"(d[19]),"+f"(d[20]),"+f"(d[21]),"+f"(d[22]),"+f"(d[23]),"+f"(d[24]),"+f"(d[25]),"+f"(d[26]),"+f"(d[27]),"+f"(d[28]),"+f"(d[29]),"+f"(d[30]),"+f"(d[31]),"+f"(d[32]),"+f"(d[33]),"+f"(d[34]),"+f"(d[35]),"+f"(d[36]),"+f"(d[37]),"+f"(d[38]),"+f"(d[39]),"+f"(d[40]),"+f"(d[41]),"+f"(d[42]),"+f"(d[43]),"+f"(d[44]),"+f"(d[45]),"+f"(d[46]),"+f"(d[47]),"+f"(d[48]),"+f"(d[49]),"+f"(d[50]),"+f"(d[51]),"+f"(d[52]),"+f"(d[53]),"+f"(d[54]),"+f"(d[55]),"+f"(d[56]),"+f"(d[57]),"+f"(d[58]),"+f"(d[59]),"+f"(d[60]),"+f"(d[61]),"+f"(d[62]),"+f"(d[63]),"+f"(d[64]),"+f"(d[65]),"+f"(d[66]),"+f"(d[67]),"+f"(d[68]),"+f"(d[69]),"+f"(d[70]),"+f"(d[71]),"+f"(d[72]),"+f"(d[73]),"+f"(d[74]),"+f"(d[75]),"+f"(d[76]),"+f"(d[77]),"+f"(d[78]),"+f"(d[79]),"+f"(d[80]),"+f"(d[81]),"+f"(d[82]),"+f"(d[83]),"+f"(d[84]),"+f"(d[85]),"+f"(d[86]),"+f"(d[87]),"+f"(d[88]),"+f"(d[89]),"+f"(d[90]),"+f"(d[91]),"+f"(d[92]),"+f"(d[93]),"+f"(d[94]),"+f"(d[95]),"+f"(d[96]),"+f"(d[97]),"+f"(d[98]),"+f"(d[99]),"+f"(d[100]),"+f"(d[101]),"+f"(d[102]),"+f"(d[103])
  : "r"(a[0]), "r"(a[1]), "r"(a[2]), "r"(a[3]), "l"(db), "r"(sc));
}
template<> __device__ __forceinline__ void wgmma_rs<224>(float* d, const uint32_t* a, uint64_t db, int sc) {
  asm volatile("{.reg .pred p; setp.ne.b32 p, %117, 0;\n"
  "wgmma.mma_async.sync.aligned.m64n224k16.f32.bf16.bf16 {%0,%1,%2,%3,%4,%5,%6,%7,%8,%9,%10,%11,%12,%13,%14,%15,%16,%17,%18,%19,%20,%21,%22,%23,%24,%25,%26,%27,%28,%29,%30,%31,%32,%33,%34,%35,%36,%37,%38,%39,%40,%41,%42,%43,%44,%45,%46,%47,%48,%49,%50,%51,%52,%53,%54,%55,%56,%57,%58,%59,%60,%61,%62,%63,%64,%65,%66,%67,%68,%69,%70,%71,%72,%73,%74,%75,%76,%77,%78,%79,%80,%81,%82,%83,%84,%85,%86,%87,%88,%89,%90,%91,%92,%93,%94,%95,%96,%97,%98,%99,%100,%101,%102,%103,%104,%105,%106,%107,%108,%109,%110,%111}, {%112,%113,%114,%115}, %116, p, 1, 1, 0;}\n"
  : "+f"(d[0]),"+f"(d[1]),"+f"(d[2]),"+f"(d[3]),"+f"(d[4]),"+f"(d[5]),"+f"(d[6]),"+f"(d[7]),"+f"(d[8]),"+f"(d[9]),"+f"(d[10]),"+f"(d[11]),"+f"(d[12]),"+f"(d[13]),"+f"(d[14]),"+f"(d[15]),"+f"(d[16]),"+f"(d[17]),"+f"(d[18]),"+f"(d[19]),"+f"(d[20]),"+f"(d[21]),"+f"(d[22]),"+f"(d[23]),"+f"(d[24]),"+f"(d[25]),"+f"(d[26]),"+f"(d[27]),"+f"(d[28]),"+f"(d[29]),"+f"(d[30]),"+f"(d[31]),"+f"(d[32]),"+f"(d[33]),"+f"(d[34]),"+f"(d[35]),"+f"(d[36]),"+f"(d[37]),"+f"(d[38]),"+f"(d[39]),"+f"(d[40]),"+f"(d[41]),"+f"(d[42]),"+f"(d[43]),"+f"(d[44]),"+f"(d[45]),"+f"(d[46]),"+f"(d[47]),"+f"(d[48]),"+f"(d[49]),"+f"(d[50]),"+f"(d[51]),"+f"(d[52]),"+f"(d[53]),"+f"(d[54]),"+f"(d[55]),"+f"(d[56]),"+f"(d[57]),"+f"(d[58]),"+f"(d[59]),"+f"(d[60]),"+f"(d[61]),"+f"(d[62]),"+f"(d[63]),"+f"(d[64]),"+f"(d[65]),"+f"(d[66]),"+f"(d[67]),"+f"(d[68]),"+f"(d[69]),"+f"(d[70]),"+f"(d[71]),"+f"(d[72]),"+f"(d[73]),"+f"(d[74]),"+f"(d[75]),"+f"(d[76]),"+f"(d[77]),"+f"(d[78]),"+f"(d[79]),"+f"(d[80]),"+f"(d[81]),"+f"(d[82]),"+f"(d[83]),"+f"(d[84]),"+f"(d[85]),"+f"(d[86]),"+f"(d[87]),"+f"(d[88]),"+f"(d[89]),"+f"(d[90]),"+f"(d[91]),"+f"(d[92]),"+f"(d[93]),"+f"(d[94]),"+f"(d[95]),"+f"(d[96]),"+f"(d[97]),"+f"(d[98]),"+f"(d[99]),"+f"(d[100]),"+f"(d[101]),"+f"(d[102]),"+f"(d[103]),"+f"(d[104]),"+f"(d[105]),"+f"(d[106]),"+f"(d[107]),"+f"(d[108]),"+f"(d[109]),"+f"(d[110]),"+f"(d[111])
  : "r"(a[0]), "r"(a[1]), "r"(a[2]), "r"(a[3]), "l"(db), "r"(sc));
}
template<> __device__ __forceinline__ void wgmma_rs<240>(float* d, const uint32_t* a, uint64_t db, int sc) {
  asm volatile("{.reg .pred p; setp.ne.b32 p, %125, 0;\n"
  "wgmma.mma_async.sync.aligned.m64n240k16.f32.bf16.bf16 {%0,%1,%2,%3,%4,%5,%6,%7,%8,%9,%10,%11,%12,%13,%14,%15,%16,%17,%18,%19,%20,%21,%22,%23,%24,%25,%26,%27,%28,%29,%30,%31,%32,%33,%34,%35,%36,%37,%38,%39,%40,%41,%42,%43,%44,%45,%46,%47,%48,%49,%50,%51,%52,%53,%54,%55,%56,%57,%58,%59,%60,%61,%62,%63,%64,%65,%66,%67,%68,%69,%70,%71,%72,%73,%74,%75,%76,%77,%78,%79,%80,%81,%82,%83,%84,%85,%86,%87,%88,%89,%90,%91,%92,%93,%94,%95,%96,%97,%98,%99,%100,%101,%102,%103,%104,%105,%106,%107,%108,%109,%110,%111,%112,%113,%114,%115,%116,%117,%118,%119}, {%120,%121,%122,%123}, %124, p, 1, 1, 0;}\n"
  : "+f"(d[0]),"+f"(d[1]),"+f"(d[2]),"+f"(d[3]),"+f"(d[4]),"+f"(d[5]),"+f"(d[6]),"+f"(d[7]),"+f"(d[8]),"+f"(d[9]),"+f"(d[10]),"+f"(d[11]),"+f"(d[12]),"+f"(d[13]),"+f"(d[14]),"+f"(d[15]),"+f"(d[16]),"+f"(d[17]),"+f"(d[18]),"+f"(d[19]),"+f"(d[20]),"+f"(d[21]),"+f"(d[22]),"+f"(d[23]),"+f"(d[24]),"+f"(d[25]),"+f"(d[26]),"+f"(d[27]),"+f"(d[28]),"+f"(d[29]),"+f"(d[30]),"+f"(d[31]),"+f"(d[32]),"+f"(d[33]),"+f"(d[34]),"+f"(d[35]),"+f"(d[36]),"+f"(d[37]),"+f"(d[38]),"+f"(d[39]),"+f"(d[40]),"+f"(d[41]),"+f"(d[42]),"+f"(d[43]),"+f"(d[44]),"+f"(d[45]),"+f"(d[46]),"+f"(d[47]),"+f"(d[48]),"+f"(d[49]),"+f"(d[50]),"+f"(d[51]),"+f"(d[52]),"+f"(d[53]),"+f"(d[54]),"+f"(d[55]),"+f"(d[56]),"+f"(d[57]),"+f"(d[58]),"+f"(d[59]),"+f"(d[60]),"+f"(d[61]),"+f"(d[62]),"+f"(d[63]),"+f"(d[64]),"+f"(d[65]),"+f"(d[66]),"+f"(d[67]),"+f"(d[68]),"+f"(d[69]),"+f"(d[70]),"+f"(d[71]),"+f"(d[72]),"+f"(d[73]),"+f"(d[74]),"+f"(d[75]),"+f"(d[76]),"+f"(d[77]),"+f"(d[78]),"+f"(d[79]),"+f"(d[80]),"+f"(d[81]),"+f"(d[82]),"+f"(d[83]),"+f"(d[84]),"+f"(d[85]),"+f"(d[86]),"+f"(d[87]),"+f"(d[88]),"+f"(d[89]),"+f"(d[90]),"+f"(d[91]),"+f"(d[92]),"+f"(d[93]),"+f"(d[94]),"+f"(d[95]),"+f"(d[96]),"+f"(d[97]),"+f"(d[98]),"+f"(d[99]),"+f"(d[100]),"+f"(d[101]),"+f"(d[102]),"+f"(d[103]),"+f"(d[104]),"+f"(d[105]),"+f"(d[106]),"+f"(d[107]),"+f"(d[108]),"+f"(d[109]),"+f"(d[110]),"+f"(d[111]),"+f"(d[112]),"+f"(d[113]),"+f"(d[114]),"+f"(d[115]),"+f"(d[116]),"+f"(d[117]),"+f"(d[118]),"+f"(d[119])
  : "r"(a[0]), "r"(a[1]), "r"(a[2]), "r"(a[3]), "l"(db), "r"(sc));
}
template<> __device__ __forceinline__ void wgmma_rs<256>(float* d, const uint32_t* a, uint64_t db, int sc) {
  asm volatile("{.reg .pred p; setp.ne.b32 p, %133, 0;\n"
  "wgmma.mma_async.sync.aligned.m64n256k16.f32.bf16.bf16 {%0,%1,%2,%3,%4,%5,%6,%7,%8,%9,%10,%11,%12,%13,%14,%15,%16,%17,%18,%19,%20,%21,%22,%23,%24,%25,%26,%27,%28,%29,%30,%31,%32,%33,%34,%35,%36,%37,%38,%39,%40,%41,%42,%43,%44,%45,%46,%47,%48,%49,%50,%51,%52,%53,%54,%55,%56,%57,%58,%59,%60,%61,%62,%63,%64,%65,%66,%67,%68,%69,%70,%71,%72,%73,%74,%75,%76,%77,%78,%79,%80,%81,%82,%83,%84,%85,%86,%87,%88,%89,%90,%91,%92,%93,%94,%95,%96,%97,%98,%99,%100,%101,%102,%103,%104,%105,%106,%107,%108,%109,%110,%111,%112,%113,%114,%115,%116,%117,%118,%119,%120,%121,%122,%123,%124,%125,%126,%127}, {%128,%129,%130,%131}, %132, p, 1, 1, 0;}\n"
  : "+f"(d[0]),"+f"(d[1]),"+f"(d[2]),"+f"(d[3]),"+f"(d[4]),"+f"(d[5]),"+f"(d[6]),"+f"(d[7]),"+f"(d[8]),"+f"(d[9]),"+f"(d[10]),"+f"(d[11]),"+f"(d[12]),"+f"(d[13]),"+f"(d[14]),"+f"(d[15]),"+f"(d[16]),"+f"(d[17]),"+f"(d[18]),"+f"(d[19]),"+f"(d[20]),"+f"(d[21]),"+f"(d[22]),"+f"(d[23]),"+f"(d[24]),"+f"(d[25]),"+f"(d[26]),"+f"(d[27]),"+f"(d[28]),"+f"(d[29]),"+f"(d[30]),"+f"(d[31]),"+f"(d[32]),"+f"(d[33]),"+f"(d[34]),"+f"(d[35]),"+f"(d[36]),"+f"(d[37]),"+f"(d[38]),"+f"(d[39]),"+f"(d[40]),"+f"(d[41]),"+f"(d[42]),"+f"(d[43]),"+f"(d[44]),"+f"(d[45]),"+f"(d[46]),"+f"(d[47]),"+f"(d[48]),"+f"(d[49]),"+f"(d[50]),"+f"(d[51]),"+f"(d[52]),"+f"(d[53]),"+f"(d[54]),"+f"(d[55]),"+f"(d[56]),"+f"(d[57]),"+f"(d[58]),"+f"(d[59]),"+f"(d[60]),"+f"(d[61]),"+f"(d[62]),"+f"(d[63]),"+f"(d[64]),"+f"(d[65]),"+f"(d[66]),"+f"(d[67]),"+f"(d[68]),"+f"(d[69]),"+f"(d[70]),"+f"(d[71]),"+f"(d[72]),"+f"(d[73]),"+f"(d[74]),"+f"(d[75]),"+f"(d[76]),"+f"(d[77]),"+f"(d[78]),"+f"(d[79]),"+f"(d[80]),"+f"(d[81]),"+f"(d[82]),"+f"(d[83]),"+f"(d[84]),"+f"(d[85]),"+f"(d[86]),"+f"(d[87]),"+f"(d[88]),"+f"(d[89]),"+f"(d[90]),"+f"(d[91]),"+f"(d[92]),"+f"(d[93]),"+f"(d[94]),"+f"(d[95]),"+f"(d[96]),"+f"(d[97]),"+f"(d[98]),"+f"(d[99]),"+f"(d[100]),"+f"(d[101]),"+f"(d[102]),"+f"(d[103]),"+f"(d[104]),"+f"(d[105]),"+f"(d[106]),"+f"(d[107]),"+f"(d[108]),"+f"(d[109]),"+f"(d[110]),"+f"(d[111]),"+f"(d[112]),"+f"(d[113]),"+f"(d[114]),"+f"(d[115]),"+f"(d[116]),"+f"(d[117]),"+f"(d[118]),"+f"(d[119]),"+f"(d[120]),"+f"(d[121]),"+f"(d[122]),"+f"(d[123]),"+f"(d[124]),"+f"(d[125]),"+f"(d[126]),"+f"(d[127])
  : "r"(a[0]), "r"(a[1]), "r"(a[2]), "r"(a[3]), "l"(db), "r"(sc));
}
template<> __device__ __forceinline__ void wgmma_ss<128>(float* d, uint64_t da, uint64_t db, int sc) {
  asm volatile("{.reg .pred p; setp.ne.b32 p, %66, 0;\n"
  "wgmma.mma_async.sync.aligned.m64n128k16.f32.bf16.bf16 {%0,%1,%2,%3,%4,%5,%6,%7,%8,%9,%10,%11,%12,%13,%14,%15,%16,%17,%18,%19,%20,%21,%22,%23,%24,%25,%26,%27,%28,%29,%30,%31,%32,%33,%34,%35,%36,%37,%38,%39,%40,%41,%42,%43,%44,%45,%46,%47,%48,%49,%50,%51,%52,%53,%54,%55,%56,%57,%58,%59,%60,%61,%62,%63}, %64, %65, p, 1, 1, 0, 1;}\n"
  : "+f"(d[0]),"+f"(d[1]),"+f"(d[2]),"+f"(d[3]),"+f"(d[4]),"+f"(d[5]),"+f"(d[6]),"+f"(d[7]),"+f"(d[8]),"+f"(d[9]),"+f"(d[10]),"+f"(d[11]),"+f"(d[12]),"+f"(d[13]),"+f"(d[14]),"+f"(d[15]),"+f"(d[16]),"+f"(d[17]),"+f"(d[18]),"+f"(d[19]),"+f"(d[20]),"+f"(d[21]),"+f"(d[22]),"+f"(d[23]),"+f"(d[24]),"+f"(d[25]),"+f"(d[26]),"+f"(d[27]),"+f"(d[28]),"+f"(d[29]),"+f"(d[30]),"+f"(d[31]),"+f"(d[32]),"+f"(d[33]),"+f"(d[34]),"+f"(d[35]),"+f"(d[36]),"+f"(d[37]),"+f"(d[38]),"+f"(d[39]),"+f"(d[40]),"+f"(d[41]),"+f"(d[42]),"+f"(d[43]),"+f"(d[44]),"+f"(d[45]),"+f"(d[46]),"+f"(d[47]),"+f"(d[48]),"+f"(d[49]),"+f"(d[50]),"+f"(d[51]),"+f"(d[52]),"+f"(d[53]),"+f"(d[54]),"+f"(d[55]),"+f"(d[56]),"+f"(d[57]),"+f"(d[58]),"+f"(d[59]),"+f"(d[60]),"+f"(d[61]),"+f"(d[62]),"+f"(d[63])
  : "l"(da), "l"(db), "r"(sc));
}
template<> __device__ __forceinline__ void wgmma_ss<192>(float* d, uint64_t da, uint64_t db, int sc) {
  asm volatile("{.reg .pred p; setp.ne.b32 p, %98, 0;\n"
  "wgmma.mma_async.sync.aligned.m64n192k16.f32.bf16.bf16 {%0,%1,%2,%3,%4,%5,%6,%7,%8,%9,%10,%11,%12,%13,%14,%15,%16,%17,%18,%19,%20,%21,%22,%23,%24,%25,%26,%27,%28,%29,%30,%31,%32,%33,%34,%35,%36,%37,%38,%39,%40,%41,%42,%43,%44,%45,%46,%47,%48,%49,%50,%51,%52,%53,%54,%55,%56,%57,%58,%59,%60,%61,%62,%63,%64,%65,%66,%67,%68,%69,%70,%71,%72,%73,%74,%75,%76,%77,%78,%79,%80,%81,%82,%83,%84,%85,%86,%87,%88,%89,%90,%91,%92,%93,%94,%95}, %96, %97, p, 1, 1, 0, 1;}\n"
  : "+f"(d[0]),"+f"(d[1]),"+f"(d[2]),"+f"(d[3]),"+f"(d[4]),"+f"(d[5]),"+f"(d[6]),"+f"(d[7]),"+f"(d[8]),"+f"(d[9]),"+f"(d[10]),"+f"(d[11]),"+f"(d[12]),"+f"(d[13]),"+f"(d[14]),"+f"(d[15]),"+f"(d[16]),"+f"(d[17]),"+f"(d[18]),"+f"(d[19]),"+f"(d[20]),"+f"(d[21]),"+f"(d[22]),"+f"(d[23]),"+f"(d[24]),"+f"(d[25]),"+f"(d[26]),"+f"(d[27]),"+f"(d[28]),"+f"(d[29]),"+f"(d[30]),"+f"(d[31]),"+f"(d[32]),"+f"(d[33]),"+f"(d[34]),"+f"(d[35]),"+f"(d[36]),"+f"(d[37]),"+f"(d[38]),"+f"(d[39]),"+f"(d[40]),"+f"(d[41]),"+f"(d[42]),"+f"(d[43]),"+f"(d[44]),"+f"(d[45]),"+f"(d[46]),"+f"(d[47]),"+f"(d[48]),"+f"(d[49]),"+f"(d[50]),"+f"(d[51]),"+f"(d[52]),"+f"(d[53]),"+f"(d[54]),"+f"(d[55]),"+f"(d[56]),"+f"(d[57]),"+f"(d[58]),"+f"(d[59]),"+f"(d[60]),"+f"(d[61]),"+f"(d[62]),"+f"(d[63]),"+f"(d[64]),"+f"(d[65]),"+f"(d[66]),"+f"(d[67]),"+f"(d[68]),"+f"(d[69]),"+f"(d[70]),"+f"(d[71]),"+f"(d[72]),"+f"(d[73]),"+f"(d[74]),"+f"(d[75]),"+f"(d[76]),"+f"(d[77]),"+f"(d[78]),"+f"(d[79]),"+f"(d[80]),"+f"(d[81]),"+f"(d[82]),"+f"(d[83]),"+f"(d[84]),"+f"(d[85]),"+f"(d[86]),"+f"(d[87]),"+f"(d[88]),"+f"(d[89]),"+f"(d[90]),"+f"(d[91]),"+f"(d[92]),"+f"(d[93]),"+f"(d[94]),"+f"(d[95])
  : "l"(da), "l"(db), "r"(sc));
}
template<> __device__ __forceinline__ void wgmma_ss<256>(float* d, uint64_t da, uint64_t db, int sc) {
  asm volatile("{.reg .pred p; setp.ne.b32 p, %130, 0;\n"
  "wgmma.mma_async.sync.aligned.m64n256k16.f32.bf16.bf16 {%0,%1,%2,%3,%4,%5,%6,%7,%8,%9,%10,%11,%12,%13,%14,%15,%16,%17,%18,%19,%20,%21,%22,%23,%24,%25,%26,%27,%28,%29,%30,%31,%32,%33,%34,%35,%36,%37,%38,%39,%40,%41,%42,%43,%44,%45,%46,%47,%48,%49,%50,%51,%52,%53,%54,%55,%56,%57,%58,%59,%60,%61,%62,%63,%64,%65,%66,%67,%68,%69,%70,%71,%72,%73,%74,%75,%76,%77,%78,%79,%80,%81,%82,%83,%84,%85,%86,%87,%88,%89,%90,%91,%92,%93,%94,%95,%96,%97,%98,%99,%100,%101,%102,%103,%104,%105,%106,%107,%108,%109,%110,%111,%112,%113,%114,%115,%116,%117,%118,%119,%120,%121,%122,%123,%124,%125,%126,%127}, %128, %129, p, 1, 1, 0, 1;}\n"
  : "+f"(d[0]),"+f"(d[1]),"+f"(d[2]),"+f"(d[3]),"+f"(d[4]),"+f"(d[5]),"+f"(d[6]),"+f"(d[7]),"+f"(d[8]),"+f"(d[9]),"+f"(d[10]),"+f"(d[11]),"+f"(d[12]),"+f"(d[13]),"+f"(d[14]),"+f"(d[15]),"+f"(d[16]),"+f"(d[17]),"+f"(d[18]),"+f"(d[19]),"+f"(d[20]),"+f"(d[21]),"+f"(d[22]),"+f"(d[23]),"+f"(d[24]),"+f"(d[25]),"+f"(d[26]),"+f"(d[27]),"+f"(d[28]),"+f"(d[29]),"+f"(d[30]),"+f"(d[31]),"+f"(d[32]),"+f"(d[33]),"+f"(d[34]),"+f"(d[35]),"+f"(d[36]),"+f"(d[37]),"+f"(d[38]),"+f"(d[39]),"+f"(d[40]),"+f"(d[41]),"+f"(d[42]),"+f"(d[43]),"+f"(d[44]),"+f"(d[45]),"+f"(d[46]),"+f"(d[47]),"+f"(d[48]),"+f"(d[49]),"+f"(d[50]),"+f"(d[51]),"+f"(d[52]),"+f"(d[53]),"+f"(d[54]),"+f"(d[55]),"+f"(d[56]),"+f"(d[57]),"+f"(d[58]),"+f"(d[59]),"+f"(d[60]),"+f"(d[61]),"+f"(d[62]),"+f"(d[63]),"+f"(d[64]),"+f"(d[65]),"+f"(d[66]),"+f"(d[67]),"+f"(d[68]),"+f"(d[69]),"+f"(d[70]),"+f"(d[71]),"+f"(d[72]),"+f"(d[73]),"+f"(d[74]),"+f"(d[75]),"+f"(d[76]),"+f"(d[77]),"+f"(d[78]),"+f"(d[79]),"+f"(d[80]),"+f"(d[81]),"+f"(d[82]),"+f"(d[83]),"+f"(d[84]),"+f"(d[85]),"+f"(d[86]),"+f"(d[87]),"+f"(d[88]),"+f"(d[89]),"+f"(d[90]),"+f"(d[91]),"+f"(d[92]),"+f"(d[93]),"+f"(d[94]),"+f"(d[95]),"+f"(d[96]),"+f"(d[97]),"+f"(d[98]),"+f"(d[99]),"+f"(d[100]),"+f"(d[101]),"+f"(d[102]),"+f"(d[103]),"+f"(d[104]),"+f"(d[105]),"+f"(d[106]),"+f"(d[107]),"+f"(d[108]),"+f"(d[109]),"+f"(d[110]),"+f"(d[111]),"+f"(d[112]),"+f"(d[113]),"+f"(d[114]),"+f"(d[115]),"+f"(d[116]),"+f"(d[117]),"+f"(d[118]),"+f"(d[119]),"+f"(d[120]),"+f"(d[121]),"+f"(d[122]),"+f"(d[123]),"+f"(d[124]),"+f"(d[125]),"+f"(d[126]),"+f"(d[127])
  : "l"(da), "l"(db), "r"(sc));
}

__device__ __forceinline__ void wg_fence() { asm volatile("wgmma.fence.sync.aligned;" ::: "memory"); }
__device__ __forceinline__ void wg_commit() { asm volatile("wgmma.commit_group.sync.aligned;" ::: "memory"); }
template <int N> __device__ __forceinline__ void wg_wait() { asm volatile("wgmma.wait_group.sync.aligned %0;" ::"n"(N) : "memory"); }
__device__ __forceinline__ uint64_t mkdesc(uint32_t addr, uint32_t lbo, uint32_t sbo, uint32_t swz) {
  return (uint64_t)((addr & 0x3FFFF) >> 4) | ((uint64_t)(lbo >> 4) << 16) | ((uint64_t)(sbo >> 4) << 32) | ((uint64_t)swz << 62);
}
__device__ __forceinline__ void mbar_init(uint32_t a, uint32_t c) { asm volatile("mbarrier.init.shared.b64 [%0], %1;" ::"r"(a), "r"(c) : "memory"); }
__device__ __forceinline__ void mbar_expect_tx(uint32_t a, uint32_t b) { asm volatile("mbarrier.arrive.expect_tx.shared.b64 _, [%0], %1;" ::"r"(a), "r"(b) : "memory"); }
__device__ __forceinline__ void mbar_arrive(uint32_t a) { asm volatile("mbarrier.arrive.shared.b64 _, [%0];" ::"r"(a) : "memory"); }
__device__ __forceinline__ void mbar_arrive_c(uint32_t a, uint32_t n) { asm volatile("mbarrier.arrive.shared::cluster.b64 _, [%0], %1;" ::"r"(a), "r"(n) : "memory"); }
__device__ __forceinline__ void mbar_wait(uint32_t a, uint32_t parity) {
  asm volatile("{.reg .pred p, q; .reg .u32 n; mov.u32 n, 0;\n"
               "W: mbarrier.try_wait.parity.shared.b64 p, [%0], %1;\n"
               "add.u32 n, n, 1; setp.eq.u32 q, n, 0x100000; @q trap; @!p bra.uni W;}" ::"r"(a), "r"(parity) : "memory");
}
__device__ __forceinline__ uint32_t mapa(uint32_t a, uint32_t rank) { uint32_t r; asm("mapa.shared::cluster.u32 %0, %1, %2;" : "=r"(r) : "r"(a), "r"(rank)); return r; }
__device__ __forceinline__ void tma2d(uint32_t dst, const CUtensorMap* m, uint32_t bar, int c0, int c1) {
  asm volatile("cp.async.bulk.tensor.2d.shared::cluster.global.mbarrier::complete_tx::bytes [%0], [%1, {%3,%4}], [%2];"
               ::"r"(dst), "l"(m), "r"(bar), "r"(c0), "r"(c1) : "memory");
}
__device__ __forceinline__ void tma3d(uint32_t dst, const CUtensorMap* m, uint32_t bar, int c0, int c1, int c2) {
  asm volatile("cp.async.bulk.tensor.3d.shared::cluster.global.mbarrier::complete_tx::bytes [%0], [%1, {%3,%4,%5}], [%2];"
               ::"r"(dst), "l"(m), "r"(bar), "r"(c0), "r"(c1), "r"(c2) : "memory");
}
__device__ __forceinline__ void tma3d_mc(uint32_t dst, const CUtensorMap* m, uint32_t bar, int c0, int c1, int c2) {
  asm volatile("cp.async.bulk.tensor.3d.shared::cluster.global.mbarrier::complete_tx::bytes.multicast::cluster [%0], [%1, {%3,%4,%5}], [%2], %6;"
               ::"r"(dst), "l"(m), "r"(bar), "r"(c0), "r"(c1), "r"(c2), "h"((uint16_t)3) : "memory");
}
__device__ __forceinline__ void tma_store(const CUtensorMap* m, uint32_t src, int c0, int c1) {
  asm volatile("cp.async.bulk.tensor.2d.global.shared::cta.bulk_group [%0, {%2,%3}], [%1];" ::"l"(m), "r"(src), "r"(c0), "r"(c1) : "memory");
}
__device__ __forceinline__ void bulk_commit() { asm volatile("cp.async.bulk.commit_group;" ::: "memory"); }
__device__ __forceinline__ void bulk_wait_read() { asm volatile("cp.async.bulk.wait_group.read 0;" ::: "memory"); }
__device__ __forceinline__ void bulk_wait() { asm volatile("cp.async.bulk.wait_group 0;" ::: "memory"); }
__device__ __forceinline__ void bulk_g2s(uint32_t dst, const void* src, uint32_t bytes, uint32_t bar) {
  asm volatile("cp.async.bulk.shared::cluster.global.mbarrier::complete_tx::bytes [%0], [%1], %2, [%3];"
               ::"r"(dst), "l"(src), "r"(bytes), "r"(bar) : "memory");
}
__device__ __forceinline__ void prefetch_l2(const void* src, uint32_t bytes) {
  asm volatile("cp.async.bulk.prefetch.L2.global [%0], %1;" ::"l"(src), "r"(bytes) : "memory");
}
__device__ __forceinline__ void prefetch_tmap(const CUtensorMap* m) { asm volatile("prefetch.tensormap [%0];" ::"l"(m) : "memory"); }
__device__ __forceinline__ void fence_async_smem() { asm volatile("fence.proxy.async.shared::cta;" ::: "memory"); }
__device__ __forceinline__ void fence_async_global() { asm volatile("fence.proxy.async.global;" ::: "memory"); }
__device__ __forceinline__ void acquire_async() { asm volatile("fence.acquire.gpu; fence.proxy.async.global;" ::: "memory"); }
__device__ __forceinline__ void bar_sync(int id, int n) { asm volatile("bar.sync %0, %1;" ::"r"(id), "r"(n) : "memory"); }
__device__ __forceinline__ void cluster_wait() { asm volatile("barrier.cluster.wait.aligned;" ::: "memory"); }
__device__ __forceinline__ uint32_t lds32(uint32_t a) { uint32_t v; asm volatile("ld.volatile.shared.b32 %0,[%1];" : "=r"(v) : "r"(a)); return v; }
__device__ __forceinline__ uint2 lds64(uint32_t a) { uint2 v; asm volatile("ld.shared.v2.b32 {%0,%1},[%2];" : "=r"(v.x), "=r"(v.y) : "r"(a) : "memory"); return v; }
__device__ __forceinline__ uint4 lds128(uint32_t a) { uint4 v; asm volatile("ld.shared.v4.b32 {%0,%1,%2,%3},[%4];" : "=r"(v.x), "=r"(v.y), "=r"(v.z), "=r"(v.w) : "r"(a) : "memory"); return v; }
__device__ __forceinline__ void sts128(uint32_t a, uint32_t x, uint32_t y, uint32_t z, uint32_t w) { asm volatile("st.shared.v4.b32 [%0],{%1,%2,%3,%4};" ::"r"(a), "r"(x), "r"(y), "r"(z), "r"(w) : "memory"); }
__device__ __forceinline__ void stsm4(uint32_t a, uint32_t x, uint32_t y, uint32_t z, uint32_t w) { asm volatile("stmatrix.sync.aligned.m8n8.x4.shared.b16 [%0],{%1,%2,%3,%4};" ::"r"(a), "r"(x), "r"(y), "r"(z), "r"(w) : "memory"); }
__device__ __forceinline__ uint32_t packbf(float lo, float hi) { uint32_t r; asm("cvt.rn.bf16x2.f32 %0, %1, %2;" : "=r"(r) : "f"(hi), "f"(lo)); return r; }
__device__ __forceinline__ uint32_t packbf_relu(float lo, float hi) { uint32_t r; asm("cvt.rn.relu.bf16x2.f32 %0, %1, %2;" : "=r"(r) : "f"(hi), "f"(lo)); return r; }
__device__ __forceinline__ uint32_t bmul2(uint32_t a, uint32_t b) { uint32_t r; asm("mul.rn.bf16x2 %0, %1, %2;" : "=r"(r) : "r"(a), "r"(b)); return r; }
__device__ __forceinline__ uint32_t bfma2(uint32_t a, uint32_t b, uint32_t c) { uint32_t r; asm("fma.rn.bf16x2 %0, %1, %2, %3;" : "=r"(r) : "r"(a), "r"(b), "r"(c)); return r; }
__device__ __forceinline__ uint32_t badd2(uint32_t a, uint32_t b) { uint32_t r; asm("add.rn.bf16x2 %0, %1, %2;" : "=r"(r) : "r"(a), "r"(b)); return r; }
__device__ __forceinline__ uint32_t bsub2(uint32_t a, uint32_t b) { uint32_t r; asm("sub.rn.bf16x2 %0, %1, %2;" : "=r"(r) : "r"(a), "r"(b)); return r; }
__device__ __forceinline__ float bflo(uint32_t v) { return __uint_as_float(v << 16); }
__device__ __forceinline__ float bfhi(uint32_t v) { return __uint_as_float(v & 0xffff0000u); }
__device__ __forceinline__ uint32_t ldg_relaxed(const uint32_t* p) { uint32_t v; asm volatile("ld.relaxed.gpu.global.b32 %0,[%1];" : "=r"(v) : "l"(p) : "memory"); return v; }
__device__ __forceinline__ uint4 ldg_b128(const void* p) {
  uint4 v;
  asm volatile("{.reg .b128 r; .reg .b64 a, b; ld.relaxed.gpu.global.b128 r, [%4]; mov.b128 {a, b}, r; mov.b64 {%0,%1}, a; mov.b64 {%2,%3}, b;}"
               : "=r"(v.x), "=r"(v.y), "=r"(v.z), "=r"(v.w) : "l"(p) : "memory");
  return v;
}
__device__ __forceinline__ void stg_b128(void* p, uint32_t x, uint32_t y, uint32_t z, uint32_t w) {
  asm volatile("{.reg .b128 r; .reg .b64 a, b; mov.b64 a, {%1,%2}; mov.b64 b, {%3,%4}; mov.b128 r, {a, b}; st.relaxed.gpu.global.b128 [%0], r;}"
               ::"l"(p), "r"(x), "r"(y), "r"(z), "r"(w) : "memory");
}
__device__ __forceinline__ void signal(uint32_t* cnt) { asm volatile("red.release.gpu.global.add.u32 [%0], 1;" ::"l"(cnt) : "memory"); }
__device__ __forceinline__ void wait_count(const uint32_t* cnt, uint32_t target) {
  int it = 0;
  while (true) {
    uint32_t v;
    asm volatile("ld.acquire.gpu.global.b32 %0,[%1];" : "=r"(v) : "l"(cnt) : "memory");
    if ((int)(v - target) >= 0) break;
    __nanosleep(32);
    if (++it > (1 << 21)) __trap();
  }
}

__device__ __forceinline__ void wait_count_warp(const uint32_t* cnt, uint32_t target) {
  asm volatile("{.reg .pred p, q; .reg .u32 n, v; mov.u32 n, 0;\n"
               "W: ld.acquire.gpu.global.b32 v, [%0]; sub.u32 v, v, %1; setp.lt.s32 p, v, 0;\n"
               "@p nanosleep.u32 " STR(POLL_SLEEP) "; add.u32 n, n, 1; setp.eq.u32 q, n, 0x200000; @q trap; @p bra.uni W;}" ::"l"(cnt), "r"(target) : "memory");
}

template <int LO, int HI> __device__ __forceinline__ void rename(float* d) {
#pragma unroll
  for (int i = LO; i < HI; i++) { float e; asm volatile("mov.b32 %0, %1;" : "=f"(e) : "f"(d[i])); d[i] = e; }
}
template <int M> __device__ __forceinline__ void drain4(const float* d, uint32_t ya, uint32_t ybar, bool lane0) {
  uint32_t r[4];
#pragma unroll
  for (int q = 0; q < 4; q++) {
    const int mu = M + q;
    float v0 = d[4 * mu], v1 = d[4 * mu + 1];
    if (mu > 0) { v0 += d[4 * mu - 2]; v1 += d[4 * mu - 1]; }
    r[q] = packbf(v0, v1);
  }
  asm volatile("stmatrix.sync.aligned.m8n8.x4.trans.shared.b16 [%0],{%1,%2,%3,%4};" ::"r"(ya + M * 128), "r"(r[0]), "r"(r[1]), "r"(r[2]), "r"(r[3]) : "memory");
  if constexpr ((M & 15) == 12) {
    __syncwarp();
    if (lane0) mbar_arrive(ybar + (M >> 4) * 8);
  }
}
struct ZTask {
  uint32_t ybar, yb, za;
  __device__ __forceinline__ void load(uint2* p) const {
    mbar_wait(ybar, 0);
#pragma unroll
    for (int i = 0; i < 8; i++) p[i] = lds64(yb + i * YW);
  }
  __device__ __forceinline__ void store(const uint2* p, uint32_t par, bool lane0) const {
    const uint32_t a0 = badd2(badd2(p[0].x, p[1].x), badd2(p[2].x, p[3].x)), a1 = badd2(badd2(p[0].y, p[1].y), badd2(p[2].y, p[3].y));
    const uint32_t b0 = badd2(badd2(p[4].x, p[5].x), badd2(p[6].x, p[7].x)), b1 = badd2(badd2(p[4].y, p[5].y), badd2(p[6].y, p[7].y));
    __syncwarp();
    sts128(za, (__byte_perm(a0, b0, 0x5410) & ~1u) | par, __byte_perm(a0, b0, 0x7632), __byte_perm(a1, b1, 0x5410), __byte_perm(a1, b1, 0x7632));
    if (ZFENCE) fence_async_smem();
    __syncwarp();
    if (lane0) mbar_arrive(ybar + 8 * (B_ZFULL - B_YFULL));
  }
};
__device__ __forceinline__ void lda(uint32_t* a, uint32_t ua) { a[0] = lds32(ua); a[1] = lds32(ua + 128); a[2] = lds32(ua - 16); a[3] = lds32(ua + 112); }
struct Round {
  uint32_t ua, ua_next, ya, zero_a, bar, ybar, kbar_next, ybuf_free, ybuf_free2, par;
  uint64_t db;
  ZTask zprev, zcur;
  bool lane0, zero;
};
template <int P, bool FIRST> struct Pass {
  static __device__ __forceinline__ void run(float* d, uint32_t (*a)[4], uint2* zp, const Round& R) {
    if constexpr (P > 0) rename<8 * (P - 1), 128>(d);
    wg_fence();
    wgmma_rs<256 - 16 * P>(d + 8 * P, a[P & 1], R.db, P != 0);
    wg_commit();
    if constexpr (P < 15) {
      if constexpr (FIRST && (P & 1)) mbar_wait(R.bar + 8 * (B_UFULL + (P + 1) / 2), 0);
      if constexpr (!FIRST && P == 7) mbar_wait(R.bar + 8 * (B_UREST + 1), 0);
      lda(a[(P + 1) & 1], R.ua + (P + 1) * 256);
    } else {
      if constexpr (FIRST) mbar_wait(R.bar + 8 * B_UREST, 0);
      lda(a[0], R.ua_next);
    }
    if constexpr (P == 0) {
      if constexpr (!FIRST) { mbar_wait(R.ybuf_free, 0); mbar_wait(R.ybuf_free2, 0); }
      if (R.zero) sts128(R.zero_a, 0, 0, 0, 0);
    }
    if constexpr (P >= 3 && (P & 1)) drain4<2 * P - 6>(d, R.ya, R.ybar, R.lane0);
    if constexpr (!FIRST && P == ZP0) R.zprev.load(zp);
    if constexpr (!FIRST && P == ZP0 + 1) R.zprev.store(zp, R.par, R.lane0);
    if constexpr (P == 10) R.zcur.load(zp);
    if constexpr (P == 12) R.zcur.store(zp, R.par, R.lane0);
    if constexpr (P == 14) mbar_wait(R.kbar_next, 0);
    wg_wait<0>();
    if constexpr (P < 15) Pass<P + 1, FIRST>::run(d, a, zp, R);
    else { rename<120, 128>(d); drain4<28>(d, R.ya, R.ybar, R.lane0); }
  }
};

__device__ __forceinline__ uint32_t off_T(int r) { return r == 0 ? OFF_T0 : r == 1 ? OFF_T1 : r == 2 ? OFF_T2 : OFF_T3; }
__device__ __forceinline__ uint32_t off_Y(int r) { return r == 1 ? OFF_KVA : r == 2 ? OFF_KVB : OFF_X; }
__device__ __forceinline__ uint32_t off_kv(int st) {
  const int sl = st < 5 ? st : st - 5;
  return sl == 0 ? 0 : sl < 3 ? OFF_KVA + (sl - 1) * KV_SLOT : OFF_KVB + (sl - 3) * KV_SLOT;
}
__device__ __forceinline__ ZTask ztask(uint32_t sb, int r, int half, int warp, int lane) {
  const uint32_t yb = sb + off_Y(r) + (8 * half + warp) * 256;
  return ZTask{sb + OFF_BAR + 8 * (B_YFULL + 2 * r + half), yb + lane * 8, yb + (lane >> 4) * YW + (lane & 15) * 16};
}
template <bool FIRST>
__device__ __forceinline__ void conv_round(uint32_t* a0, uint32_t sb, int r, int warp, int lane, uint32_t uoff, uint32_t par) {
  float d[128];
  uint32_t a[2][4] = {{a0[0], a0[1], a0[2], a0[3]}, {0, 0, 0, 0}};
  uint2 zp[8];
  const int wg = warp >> 2, w = warp & 3, rn = min(r + 1, 3);
  const uint32_t bar = sb + OFF_BAR, tb = sb + off_T(r), yb = sb + off_Y(r) + wg * YBUF + w * YW;
  const Round R{tb + uoff, sb + off_T(rn) + uoff, yb + (2 * w + lane) * 16, yb + lane * 16, bar, bar + 8 * (B_YFULL + 2 * r),
                bar + 8 * (B_KFULL + 2 * rn + wg), bar + 8 * (r == 3 ? B_ZDONE : r == 2 ? B_XREAD : B_UREST), bar + 8 * (r == 1 ? B_UREST : B_XDONE), par, mkdesc(tb + 2 * UT_SIZE + wg * KT_SIZE, 16, 128, 0),
                ztask(sb, r - 1, 1, warp, lane), ztask(sb, r, 0, warp, lane), lane == 0, lane < 2 * w};
  if (threadIdx.x == 0) TSM(r);
  Pass<0, FIRST>::run(d, a, zp, R);
#pragma unroll
  for (int i = 0; i < 4; i++) a0[i] = a[0][i];
}
__device__ __forceinline__ uint32_t off_act(int tile, int wg, int b) {
  return b < 2 ? OFF_X + wg * 16384 + b * 8192 : tile == 0 ? (b - 2 * wg) * 49152 + 40960 : 180224 + wg * 8192;
}

struct Check {
  uint32_t off;
  const __nv_bfloat16* hp;
  __device__ __forceinline__ void peek(uint32_t* t, uint32_t sa, uint32_t fb, uint32_t parity) const {
    asm volatile("{.reg .pred p; mbarrier.test_wait.parity.shared.b64 p, [%5], %6; mov.b32 %0, 0; mov.b32 %1, 0; mov.b32 %2, 0; mov.b32 %3, 0;\n"
                 "@p ld.volatile.shared.b32 %0, [%4]; @p ld.volatile.shared.b32 %1, [%4+512]; @p ld.volatile.shared.b32 %2, [%4+1024]; @p ld.volatile.shared.b32 %3, [%4+1536];}"
                 : "=&r"(t[0]), "=&r"(t[1]), "=&r"(t[2]), "=&r"(t[3]) : "r"(sa + off), "r"(fb), "r"(parity) : "memory");
  }
  __device__ __forceinline__ void run(const uint32_t* t, uint32_t sa, uint32_t fb, uint32_t parity, int kb) const {
    if (__all_sync(0xffffffffu, t[0] & t[1] & t[2] & t[3] & 1)) return;
    mbar_wait(fb, parity);
    const uint32_t ok = lds32(sa + off) & lds32(sa + off + 512) & lds32(sa + off + 1024) & lds32(sa + off + 1536);
    if (__builtin_expect(!__all_sync(0xffffffffu, ok & 1), 0)) {
      const int lane = threadIdx.x & 31;
      if (lane == 0) CNT(kb);
#pragma unroll 1
      for (int i = 0; i < 4; i++) {
        const int row = 4 * i + (lane >> 3);
        uint4 v;
        int it = 0;
        do {
          v = ldg_b128(hp + (size_t)row * D + 64 * kb + 8 * ((lane ^ row) & 7));
          if (++it > (1 << 20)) __trap();
        } while (!__all_sync(0xffffffffu, v.x & 1));
        sts128(sa + off + i * 512, v.x, v.y, v.z, v.w);
      }
      fence_async_smem();
      __syncwarp();
    }
  }
};
template <int NT, bool CHECK>
__device__ __forceinline__ void mainloop(float* acc, uint32_t sb, int wg, bool rel, int nkb, const Check& ck, uint32_t* tg) {
  const uint32_t bar = sb + OFF_BAR;
  const uint64_t da0 = mkdesc(sb + wg * 8192, 16, 1024, 1), db0 = mkdesc(sb + 16384, 8192, 1024, 1);
  if (CHECK) { ck.run(tg, sb, bar + 8 * B_FULL, 0, 0); ck.peek(tg, sb + 49152, bar + 8 * (B_FULL + 1), 0); }
  else mbar_wait(bar + 8 * B_FULL, 0);
  wg_fence();
#pragma unroll
  for (int kk = 0; kk < 4; kk++) wgmma_ss<NT>(acc, da0 + kk * 2, db0 + kk * 128, kk != 0);
  wg_commit();
#pragma unroll 1
  for (int kb = 1; kb < nkb; kb++) {
    const int s = kb & 3;
    if (CHECK) ck.run(tg, sb + s * 49152, bar + 8 * (B_FULL + s), (kb >> 2) & 1, kb);
    else mbar_wait(bar + 8 * (B_FULL + s), (kb >> 2) & 1);
    const uint64_t da = da0 + s * 3072, db = db0 + s * 3072;
    wg_fence();
    wgmma_ss<NT>(acc, da, db, 1);
    wg_commit();
    wg_wait<1>();
    if (rel) mbar_arrive(bar + 8 * (B_EMPTY + ((kb - 1) & 3)));
    if (CHECK) ck.peek(tg, sb + ((kb + 1) & 3) * 49152, bar + 8 * (B_FULL + ((kb + 1) & 3)), ((kb + 1) >> 2) & 1);
#pragma unroll
    for (int kk = 1; kk < 4; kk++) wgmma_ss<NT>(acc, da + kk * 2, db + kk * 128, 1);
    wg_commit();
  }
}
template <int NT>
__device__ __forceinline__ void gemm1_main(float* out, uint32_t sb, int wg, bool rel, uint32_t hs, bool t3, const Check& ck) {
  const uint32_t bar = sb + OFF_BAR;
  float acc[NT / 2];
  uint32_t tg[4] = {0, 0, 0, 0};
  mainloop<NT, NT == 256>(acc, sb, wg, rel, 15, ck, tg);
  mbar_wait(bar + 8 * B_CSFULL, NT == 256 ? 0 : 1);
  uint32_t a[4] = {lds32(hs), lds32(hs + 128), 0, 0};
  if (t3) a[0] = a[1] = 0;
  if (NT == 256) ck.run(tg, sb + 3 * 49152, bar + 8 * (B_FULL + 3), 1, 15);
  else mbar_wait(bar + 8 * (B_FULL + 3), 1);
  const uint64_t da = mkdesc(sb + 3 * 49152 + wg * 8192, 16, 1024, 1), db = mkdesc(sb + 3 * 49152 + 16384, 8192, 1024, 1);
  wg_fence();
  wgmma_rs<NT>(acc, a, mkdesc(sb + OFF_X + wg * 16384, 0, 128, 0), 1);
  wg_commit();
  wg_wait<1>();
  if (rel) mbar_arrive(bar + 8 * (B_EMPTY + 2));
#pragma unroll
  for (int kk = AUG_LAST; kk < 4; kk++) wgmma_ss<NT>(acc, da + kk * 2, db + kk * 128, 1);
  wg_commit();
  wg_wait<0>();
  if (rel) mbar_arrive(bar + 8 * (B_EMPTY + 3));
#pragma unroll
  for (int i = 0; i < NT / 2; i++) asm volatile("mov.b32 %0, %1;" : "=f"(out[i]) : "f"(acc[i]));
}

__global__ void __cluster_dims__(2, 1, 1) __launch_bounds__(NTHREADS, 1) fused_kernel(const __grid_constant__ Params P) {
  extern __shared__ __align__(1024) unsigned char smem[];
  const uint32_t sb = (uint32_t)__cvta_generic_to_shared(smem);
  const uint32_t bar = sb + OFF_BAR;
  const int tid = threadIdx.x, warp = __shfl_sync(0xffffffffu, tid >> 5, 0), lane = tid & 31;
  const int rank = blockIdx.x & 1, cl = blockIdx.x >> 1;
  const int lp = cl < 4 ? 60 + cl : cl < 36 ? 4 * ((cl - 4) & 7) + ((cl - 4) >> 3) : 32 + 4 * ((cl - 36) % 7) + (cl - 36) / 7;
  const int c = 2 * lp + rank;
  const int grp = lp >> 2, pi = grp < 8 ? 2 * grp : 2 * (grp - 8) + 1;
  const int hi = pi >> 2, lo = (hi & 1) ? 3 - (pi & 3) : pi & 3;
  const int m = 4 * (JGROUP == 4 ? lo : hi) + (lp & 3), j = 2 * (JGROUP == 4 ? hi : lo) + rank;

  uint32_t* const cnt = g_cnt + 32 * m;
  if (lane == 0) {
    if (warp == 8) {
      TS(0);
      mbar_init(bar + 8 * B_KVFULL, 1); mbar_init(bar + 8 * B_KFULL, 2); mbar_init(bar + 8 * (B_KFULL + 1), 2);
      mbar_expect_tx(bar + 8 * B_KVFULL, KV_SLOT);
#pragma unroll 1
      for (int i = 0; i < 2; i++) {
        tma3d(sb + i * KV_BOX, &P.tm_k, bar + 8 * B_KVFULL, 8 * (c & ~1), 16 * i - 1, 0);
        tma3d(sb + (2 + i) * KV_BOX, &P.tm_v, bar + 8 * B_KVFULL, 8 * (c & ~1), 16 * i - 1, 0);
      }
#pragma unroll 1
      for (int i = 0; i < 2; i++) {
        mbar_expect_tx(bar + 8 * (B_KFULL + i), 4080);
        bulk_g2s(sb + OFF_T0 + 2 * UT_SIZE + i * KT_SIZE + 32, P.ssm_k + (size_t)(8 * c + i) * S + 8, 4080, bar + 8 * (B_KFULL + i));
      }
    } else if (warp < 8) {
      const uint32_t na = (0x18211881u >> (4 * warp)) & 15;
#pragma unroll
      for (int i = 0; i < 8; i++) mbar_init(bar + 8 * (16 + 8 * warp + i), na);
      if (warp == 4) { mbar_expect_tx(bar + 8 * B_RECV, 16384); mbar_expect_tx(bar + 8 * (B_RECV + 1), 16384); }
    } else if (warp == 9) {
#pragma unroll
      for (int i = 1; i < 8; i++) { mbar_init(bar + 8 * (B_KVFULL + i), 1); mbar_expect_tx(bar + 8 * (B_KVFULL + i), KV_SLOT); }
    } else if (warp == 10) {
#pragma unroll
      for (int i = 2; i < 8; i++) mbar_init(bar + 8 * (B_KFULL + i), 2);
    }
    asm volatile("fence.mbarrier_init.release.cluster;" ::: "memory");
  }
  if (warp == 11 && lane < 16) sts128(sb + off_T(lane >> 2) + (lane & 3) * UT_COPY, 0, 0, 0, 0);
  __syncthreads();
  asm volatile("barrier.cluster.arrive.relaxed.aligned;" ::: "memory");

  if (tid == 32) TS(46);
  if (warp < 8) {
    if (warp == 7 && lane < 8) {
      const uint4 v = __ldg((const uint4*)(P.ssm_k + (size_t)(8 * c + lane) * S));
      const float k0 = bflo(v.x) + __bfloat162float(P.ssm_D[8 * c + lane]);
      const uint32_t kt = sb + off_T(lane >> 1) + 2 * UT_SIZE + (lane & 1) * KT_SIZE;
      sts128(kt, 0, 0, 0, 0);
      sts128(kt + 16, (v.x & 0xffff0000u) | (packbf(k0, 0.f) & 0xffffu), v.y, v.z, v.w);
      fence_async_smem();
      mbar_arrive(bar + 8 * (B_KFULL + lane));
    }
    __syncwarp();
  }
  cluster_wait();
  if (warp < NU_MMA || warp > 8) {
      uint32_t W[4][4];
      const uint4* wp = (const uint4*)(P.shift_k + (size_t)32 * c);
#pragma unroll
      for (int p = 0; p < 4; p++) {
        const uint4 v = __ldg(wp + p);
        W[0][p] = __byte_perm(v.x, v.z, 0x5410); W[1][p] = __byte_perm(v.x, v.z, 0x7632);
        W[2][p] = __byte_perm(v.y, v.w, 0x5410); W[3][p] = __byte_perm(v.y, v.w, 0x7632);
      }
      uint32_t lo[8];
#pragma unroll
      for (int n = 0; n < 8; n++) {
        const uint32_t o = (lane >> 4) * KV_BOX + ((lane & 15) + n + 1) * 32 + rank * 16;
        lo[n] = o ^ ((o >> 3) & 16);
      }
#pragma unroll 1
      for (int st = warp - 9; st < 8; st += 3) {
        const uint32_t ka = sb + off_kv(st);
        mbar_wait(bar + 8 * (B_KVFULL + st), 0);
        if (lane == 0) TS(48 + st);
        uint32_t k[12][4], v[9][4];
#pragma unroll
        for (int i = 0; i < 12; i++) {
          const uint32_t la = ka + lo[i < 4 ? i + 3 : i - 4] + (i < 4 ? i + 4 : i - 4) * 512;
          const uint4 a = lds128(la);
          k[i][0] = a.x; k[i][1] = a.y; k[i][2] = a.z; k[i][3] = a.w;
          if (i >= 3) {
            const uint4 b = lds128(la + 2 * KV_BOX);
            v[i - 3][0] = b.x; v[i - 3][1] = b.y; v[i - 3][2] = b.z; v[i - 3][3] = b.w;
          }
        }
#pragma unroll
        for (int p = 0; p < 4; p++) {
          uint32_t u[9];
#pragma unroll
          for (int i = 0; i < 9; i++)
            u[i] = bmul2(bfma2(k[i + 3][p], W[0][p], bfma2(k[i + 2][p], W[1][p], bfma2(k[i + 1][p], W[2][p], bmul2(k[i][p], W[3][p])))), v[i][p]);
          const uint32_t ta = sb + off_T(p) + 16 + (32 * st + lane) * 16;
#pragma unroll
          for (int e = 0; e < 2; e++) {
            const uint32_t sel = e ? 0x7632 : 0x5410;
            sts128(ta + e * UT_SIZE, __byte_perm(u[2], u[1], sel), __byte_perm(u[4], u[3], sel), __byte_perm(u[6], u[5], sel), __byte_perm(u[8], u[7], sel));
            sts128(ta + e * UT_SIZE + UT_COPY, __byte_perm(u[1], u[0], sel), __byte_perm(u[3], u[2], sel), __byte_perm(u[5], u[4], sel), __byte_perm(u[7], u[6], sel));
          }
          if (p == 0) {
            __syncwarp();
            if (lane == 0) mbar_arrive(bar + 8 * (B_UFULL + st));
            if (st < 3 && lane < 2) mbar_arrive_c(mapa(bar + 8 * (B_KVFREE + st), lane), 1);
            mbar_wait(bar + 8 * (B_KVFULL + st), 0);
#pragma unroll
            for (int i = 0; i < 12; i++) asm volatile("" : "+r"(k[i][1]), "+r"(k[i][2]), "+r"(k[i][3]));
          }
        }
        __syncwarp();
        if (lane == 0) { mbar_arrive_c(bar + 8 * (B_UREST + (st >> 2)), 2); if (st >= 4) TS(56 + st); }
      }
  }

  if (warp < 8) {
    const int wg = warp >> 2, w = warp & 3, g = lane >> 2, t = lane & 3;
    const uint32_t uoff = wg * UT_SIZE + ((g & 1) ? 0 : UT_COPY) + ((g >> 1) + 8 * w + 8 - t) * 4;
    const uint32_t par = __shfl_sync(0xffffffffu, ((ldg_relaxed(cnt + C_ACT + 1) >> 3) + 1) & 1, 0);
    uint32_t a0[4];
    mbar_wait(bar + 8 * (B_KFULL + wg), 0);
    mbar_wait(bar + 8 * B_UFULL, 0);
    mbar_wait(bar + 8 * (B_UFULL + START_GATE), 0);
    lda(a0, sb + OFF_T0 + uoff);
    conv_round<true>(a0, sb, 0, warp, lane, uoff, par);
#pragma unroll 1
    for (int r = 1; r < 4; r++) {
      conv_round<false>(a0, sb, r, warp, lane, uoff, par);
      if (r == 1) {
        int ln;
        asm volatile("mov.u32 %0, %laneid;" : "=r"(ln));
        const int row = 8 * (warp & 1) + (ln >> 2);
        const uint32_t xa = sb + OFF_KVB + row * 2048 + (row >> 2) * 32 + (warp >> 1) * 512 + (ln & 3) * 16, xs = (ln & 4) * 16;
        float e[4][4] = {};
        uint4 v[8];
        mbar_wait(bar + 8 * B_XFULL, 0);
#pragma unroll
        for (int i = 0; i < 8; i++) v[i] = lds128(((i & 1) ? xa - xs : xa + xs) + i * 64);
#pragma unroll
        for (int i = 0; i < 8; i++) {
          asm volatile("mma.sync.aligned.m16n8k16.row.col.f32.bf16.bf16.f32 {%0,%1,%2,%3},{%4,%6,%5,%6},{%4,%5},{%0,%1,%2,%3};"
                       : "+f"(e[i & 1][0]), "+f"(e[i & 1][1]), "+f"(e[i & 1][2]), "+f"(e[i & 1][3]) : "r"(v[i].x), "r"(v[i].y), "r"(0x3f803f80u));
          asm volatile("mma.sync.aligned.m16n8k16.row.col.f32.bf16.bf16.f32 {%0,%1,%2,%3},{%4,%6,%5,%6},{%4,%5},{%0,%1,%2,%3};"
                       : "+f"(e[2 + (i & 1)][0]), "+f"(e[2 + (i & 1)][1]), "+f"(e[2 + (i & 1)][2]), "+f"(e[2 + (i & 1)][3]) : "r"(v[i].z), "r"(v[i].w), "r"(0x3f803f80u));
        }
#pragma unroll
        for (int i = 0; i < 4; i++) e[0][i] = (e[0][i] + e[1][i]) + (e[2][i] + e[3][i]);
        if ((ln & 3) == (ln >> 3))
          ((float2*)(smem + OFF_XS))[row * 4 + (warp >> 1)] = (ln & 4) ? make_float2(e[0][3], e[0][1]) : make_float2(e[0][2], e[0][0]);
        __syncwarp();
        if (lane == 0) mbar_arrive(bar + 8 * B_XDONE);
        if (tid == 0) TSM(5);
      }
    }
    {
      uint2 zp[8];
      const ZTask z = ztask(sb, 3, 1, warp, lane);
      z.load(zp);
      z.store(zp, par, lane == 0);
    }
    if (tid == 0) TSM(4);
    if (EXP & 2) { if (tid == 0) TSDUMP(); return; }
    const bool rel = lane == 0 && w == 0;
    const int id = lane >> 3, srow = 16 * w + (lane & 7) + 8 * (id & 1);
    const uint32_t soff = srow * 128, sx = ((id >> 1) ^ (srow & 7)) << 4;
    const uint32_t hs = sb + OFF_HS + (64 * wg + 16 * w + g) * 16;
    const Check ck{(uint32_t)(warp * 2048 + lane * 16), g_h + (size_t)(par * S + 128 * m + 16 * warp) * D};
#pragma unroll 1
    for (int tile = 0; tile < 2; tile++) {
      float acc[128];
      if (tile == 0) {
        gemm1_main<256>(acc, sb, wg, rel, hs + 4 * t, t == 3, ck);
      } else {
        gemm1_main<192>(acc, sb, wg, rel, hs + 4 * t, t == 3, ck);
#pragma unroll
        for (int i = 96; i < 128; i++) asm volatile("mov.b32 %0, 0;" : "=f"(acc[i]));
      }
      if (tid == 0) TSM(6 + tile);
#pragma unroll
      for (int b = 0; b < 4; b++) {
        if (b == 3 && tile) break;
        if (b == 2) mbar_wait(bar + 8 * (B_EMPTY + 3 - 2 * wg), 1);
        const uint32_t dst = sb + off_act(tile, wg, b) + soff;
#pragma unroll
        for (int p = 0; p < 4; p++) {
          uint32_t o[4];
#pragma unroll
          for (int e = 0; e < 4; e++) {
            const uint32_t u = packbf_relu(acc[32 * b + 8 * p + 2 * e], acc[32 * b + 8 * p + 2 * e + 1]);
            o[e] = bmul2(u, u);
          }
          stsm4(dst + (sx ^ (p << 5)), o[0], o[1], o[2], o[3]);
        }
      }
      fence_async_smem();
      __syncwarp();
      if (lane == 0) mbar_arrive(bar + 8 * (B_ADONE + tile));
      if (tid == 0) TSM(8 + tile);
    }
    {
      float acc[64], res[64];
      {
        float big[128];
        mainloop<256, false>(big, sb, wg, rel, NBIG, ck, nullptr);
        wg_wait<0>();
#pragma unroll
        for (int i = 0; i < 64; i++) { asm volatile("mov.b32 %0, %1;" : "=f"(acc[i]) : "f"(big[i])); asm volatile("mov.b32 %0, %1;" : "=f"(res[i]) : "f"(big[64 + i])); }
      }
      if (rel) mbar_arrive(bar + 8 * (B_EMPTY + ((NBIG - 1) & 3)));
      if (tid == 0) TSM(10);
      if (tid == 128) TSM(14);
      const uint64_t da0 = mkdesc(sb + wg * 8192, 16, 1024, 1), db0 = mkdesc(sb + 16384, 8192, 1024, 1);
      const uint32_t ro = sb + ((NBIG - 1 - wg) & 3) * 49152 + 32768 + (tid & 127) * 16, so = sb + ((NBIG + 1 - wg) & 3) * 49152 + 32768 + (tid & 127) * 16;
      auto small = [&](int kb) {
        const int s = kb & 3;
        mbar_wait(bar + 8 * (B_FULL + s), (kb >> 2) & 1);
        wg_fence();
        wgmma_ss<128>(acc, da0 + s * 3072, db0 + s * 3072, 1);
        if (kb > NBIG && kb - 1 < NBIG + NSMALL - 4) {
          wg_commit();
          wg_wait<1>();
          if (rel) mbar_arrive(bar + 8 * (B_EMPTY + ((kb - 1) & 3)));
        }
#pragma unroll
        for (int kk = 1; kk < 4; kk++) wgmma_ss<128>(acc, da0 + s * 3072 + kk * 2, db0 + s * 3072 + kk * 128, 1);
        wg_commit();
      };
      mbar_wait(bar + 8 * (B_FULL + ((NBIG + 1 - wg) & 3)), ((NBIG + 1 - wg) >> 2) & 1);
#pragma unroll
      for (int i = 0; i < 8; i++)
        sts128(so + i * 2048, packbf(res[8 * i], res[8 * i + 1]), packbf(res[8 * i + 2], res[8 * i + 3]),
               packbf(res[8 * i + 4], res[8 * i + 5]), packbf(res[8 * i + 6], res[8 * i + 7]));
      fence_async_smem();
      __syncwarp();
      if (lane == 0) mbar_arrive_c(bar + 8 * (B_SEND + wg), 2);
      if (tid == TW) TSM(12);
#pragma unroll
      for (int kb = NBIG; kb < NBIG + NSMALL - 3; kb++) small(kb);
      const float sc0 = __uint_as_float(lds32(hs + 12)), sc1 = __uint_as_float(lds32(hs + 140));
      mbar_wait(bar + 8 * B_HRES, 0);
#pragma unroll
      for (int cc = 0; cc < 4; cc++) {
        const uint4 b = lds128(sb + OFF_RED + t * 64 + cc * 16);
#pragma unroll
        for (int h = 0; h < 2; h++) {
          const int row = 64 * wg + 16 * w + 8 * h + g;
          const uint4 v = lds128(sb + OFF_X + row * 256 + t * 64 + ((cc ^ ((2 * row + (t >> 1)) & 3)) << 4));
          const uint32_t hb[4] = {badd2(v.x, b.x), badd2(v.y, b.y), badd2(v.z, b.z), badd2(v.w, b.w)};
#pragma unroll
          for (int q = 0; q < 4; q++) { res[16 * cc + 4 * q + 2 * h] = bflo(hb[q]); res[16 * cc + 4 * q + 2 * h + 1] = bfhi(hb[q]); }
        }
      }
      small(NBIG + NSMALL - 3);
      if (ORD < 2) small(NBIG + NSMALL - 2);
      if (ORD == 0) small(NBIG + NSMALL - 1);
      if (tid == TW) TSM(5);
      mbar_wait(bar + 8 * (B_RECV + wg), 0);
      if (tid == TW) TSM(13);
#pragma unroll
      for (int i = 0; i < 8; i++) {
        const uint4 v = lds128(ro + i * 2048);
        const uint32_t vv[4] = {v.x, v.y, v.z, v.w};
#pragma unroll
        for (int e = 0; e < 4; e++) {
          const float sc = (e & 1) ? sc1 : sc0;
          res[8 * i + 2 * e] = fmaf(bflo(vv[e]), sc, res[8 * i + 2 * e]);
          res[8 * i + 2 * e + 1] = fmaf(bfhi(vv[e]), sc, res[8 * i + 2 * e + 1]);
        }
      }
      if (ORD == 2) small(NBIG + NSMALL - 2);
      if (ORD > 0) small(NBIG + NSMALL - 1);
      if (rel) mbar_arrive_c(mapa(bar + 8 * B_GOT, rank ^ 1), 4);
      bar_sync(3 + wg, 128);
      wg_wait<0>();
      rename<0, 64>(acc);
      if (tid == 0) TSM(11);
      if (tid == 128) TSM(15);
      const uint32_t ob = sb + OFF_X + wg * 16384;
#pragma unroll
      for (int mu = 0; mu < 16; mu += 2) {
        const float* a = acc + 4 * mu;
        const float* q = res + 4 * mu;
        stsm4(ob + (mu >> 3) * 8192 + soff + (sx ^ ((mu & 6) << 4)),
              packbf(fmaf(a[0], sc0, q[0]), fmaf(a[1], sc0, q[1])), packbf(fmaf(a[2], sc1, q[2]), fmaf(a[3], sc1, q[3])),
              packbf(fmaf(a[4], sc0, q[4]), fmaf(a[5], sc0, q[5])), packbf(fmaf(a[6], sc1, q[6]), fmaf(a[7], sc1, q[7])));
      }
      fence_async_smem();
      bar_sync(3 + wg, 128);
      if (w == 0 && lane == 0) {
        tma_store(&P.tm_out, ob, 128 * j, 128 * m + 64 * wg);
        tma_store(&P.tm_out, ob + 8192, 128 * j + 64, 128 * m + 64 * wg);
        bulk_commit();
        mbar_wait(bar + 8 * B_GOT, 0);
        bulk_wait_read();
        if (tid == 0) { TS(9); TSDUMP(); }
      }
    }
  } else if (warp == 8) {
    if (lane == 0) {
#pragma unroll 1
      for (int i = 1; i < 8; i++) {
        if (i >= 5) mbar_wait(bar + 8 * (B_KVFREE + i - 5), 0);
        const uint32_t dst = sb + off_kv(i) + rank * KV_BOX;
        tma3d_mc(dst, &P.tm_k, bar + 8 * (B_KVFULL + i), 8 * (c & ~1), 32 * i + 16 * rank - 1, 0);
        tma3d_mc(dst + 2 * KV_BOX, &P.tm_v, bar + 8 * (B_KVFULL + i), 8 * (c & ~1), 32 * i + 16 * rank - 1, 0);
      }
      const uint32_t epoch = (ldg_relaxed(cnt + C_ACT + 1) >> 3) + 1;
      mbar_wait(bar + 8 * (B_KVFULL + KV_GATE), 0);
#pragma unroll 1
      for (int ch = 2; ch < 8; ch++) {
        if (ch == 4) {
          mbar_wait(bar + 8 * (B_KVFULL + X_GATE), 0);
          mbar_wait(bar + 8 * (B_UFULL + 3), 0);
          mbar_wait(bar + 8 * (B_UFULL + 4), 0);
          mbar_expect_tx(bar + 8 * B_XFULL, 32768);
#pragma unroll 1
          for (int i = 0; i < 4; i++) bulk_g2s(sb + OFF_KVB + i * 8224, P.x + (size_t)(128 * m + 16 * j + 4 * i) * D, 8192, bar + 8 * B_XFULL);
          prefetch_tmap(&P.tm_z); prefetch_tmap(&P.tm_hst); prefetch_tmap(&P.tm_h); prefetch_tmap(&P.tm_w1); prefetch_tmap(&P.tm_w1c); prefetch_tmap(&P.tm_act);
          prefetch_tmap(&P.tm_w2); prefetch_tmap(&P.tm_actst); prefetch_tmap(&P.tm_hres); prefetch_tmap(&P.tm_out);
          mbar_wait(bar + 8 * (B_UREST + 1), 0);
        }
        mbar_expect_tx(bar + 8 * (B_KFULL + ch), 4080);
        bulk_g2s(sb + off_T(ch >> 1) + 2 * UT_SIZE + (ch & 1) * KT_SIZE + 32, P.ssm_k + (size_t)(8 * c + ch) * S + 8, 4080, bar + 8 * (B_KFULL + ch));
      }
      mbar_wait(bar + 8 * B_XFULL, 0);
      TS(31);
      if ((EXP & 2) && !(EXP & 32)) return;
      mbar_wait(bar + 8 * (B_KFULL + 7), 0);
      prefetch_l2(P.w1 + (size_t)c * 8 * F, 2 * F * 2);
#pragma unroll 1
      for (int i = 1; i <= PF_EARLY; i++) {
        mbar_wait(bar + 8 * (B_ZFULL + 4 - PF_EARLY + i), 0);
        prefetch_l2(P.w1 + (size_t)(c * 8 + 2 * i) * F, 2 * F * 2);
      }
      if (EXP & 2) return;
      uint32_t early = epoch * 16 - 1;
      mbar_wait(bar + 8 * (B_ZDONE + 1), 0);
      fence_async_smem();
#pragma unroll 1
      for (int i = 0; i < 8; i++) {
        const uint32_t fb = bar + 8 * (B_FULL + (i >> 2));
        if ((i & 3) == 0) mbar_expect_tx(fb, 49152);
        tma3d(sb + (i >> 2) * 49152 + 16384 + (i & 3) * 8192, &P.tm_w1, fb, 448 * j + 64 * (i & 3), 0, 32 * (i >> 2));
      }
#pragma unroll 1
      for (int it = 0; it < 32; it++) {
        const int s = it & 3, kb = it & 15, tile = it >> 4;
        const uint32_t sa = sb + s * 49152, fb = bar + 8 * (B_FULL + s);
        if (it >= 2) {
          mbar_wait(bar + 8 * (it == 2 ? B_ZDONE + 2 : it == 3 ? B_YFULL + 7 : B_EMPTY + s), it < 4 ? 0 : ((it >> 2) - 1) & 1);
          if (it == 3) { mbar_wait(bar + 8 * B_HOUT, 0); mbar_wait(bar + 8 * (B_HOUT + 1), 0); }
          if (it < 4) fence_async_smem();
          const int nb = tile ? 3 : 4, n0 = 448 * j + 256 * tile;
          mbar_expect_tx(fb, 16384 + nb * 8192);
#pragma unroll 1
          for (int i = 0; i < nb; i++) tma3d(sa + 16384 + i * 8192, &P.tm_w1, fb, n0 + 64 * i, 2 * (kb >> 2), 32 * (kb & 3));
        }
        if (it < 16 && (it & 3) == 0) {
          if (!(EXP & 64) && (int)(early - epoch * 16) < 0) wait_count(cnt + C_H + (it >> 2), epoch * 16);
          acquire_async();
          TS(11 + (it >> 2));
        }
        tma2d(sa, &P.tm_h, fb, 64 * kb, 128 * m + (epoch & 1) * S);
        if ((it & 3) == 3) early = ldg_relaxed(cnt + (it < 12 ? C_H + (it >> 2) + 1 : C_ACT));
        if (PF_EARLY < 3 && it % 3 == 2 && PF_EARLY + 1 + it / 3 < 4) prefetch_l2(P.w1 + (size_t)(c * 8 + 2 * (PF_EARLY + 1 + it / 3)) * F, 2 * F * 2);
        if (it >= 12 && it < 26) prefetch_l2(P.w2 + (size_t)(c * 28 + 2 * (it - 12)) * D, 2 * D * 2);
      }
      mbar_wait(bar + 8 * B_XFREE, 0);
#pragma unroll 1
      for (int kb = 0; kb < NBIG + NSMALL; kb++) {
        const int s = kb & 3;
        mbar_wait(bar + 8 * (B_EMPTY + s), ((kb >> 2) + 1) & 1);
        if (kb == 3) mbar_wait(bar + 8 * B_SFREE, 0);
        if (kb == NBIG + 2 || kb == NBIG + 3) mbar_arrive_c(mapa(bar + 8 * (B_PEER + NBIG + 3 - kb), rank ^ 1), 1);
        const int t1 = kb < NBIG ? (NBIG - 16) * rank + kb - 16 : kb + NBIG - 32;
        const int col = kb < 16 ? 448 * (4 * rank + (kb >> 2)) + 64 * (kb & 3) : 448 * (t1 / 3) + 256 + 64 * (t1 % 3);
        const uint32_t sa = sb + s * 49152, fb = bar + 8 * (B_FULL + s);
        const int nb = kb < NBIG ? 4 : 2;
        mbar_expect_tx(fb, 16384 + nb * 8192);
#pragma unroll 1
        for (int i = 0; i < nb; i++) tma2d(sa + 16384 + i * 8192, &P.tm_w2, fb, 128 * (j ^ (i >> 1)) + 64 * (i & 1), col);
        if ((kb & 15) == 0) {
          if ((int)(early - epoch * 8) < 0) wait_count(cnt + C_ACT + (kb >> 4), epoch * 8);
          acquire_async();
          TS(15 + (kb >> 4));
        }
        tma2d(sa, &P.tm_act, fb, col, 128 * m);
        if (kb == 15) early = ldg_relaxed(cnt + C_ACT + 1);
      }
    }
  } else {
    const int zw = warp - 9;
    const uint32_t epoch = (ldg_relaxed(cnt + C_ACT + 1) >> 3) + 1;
    if (zw == 0) {
#pragma unroll 1
      for (int e = 0; e < 8; e++) {
        mbar_wait(bar + 8 * (B_ZFULL + e), 0);
        if (lane == 0) {
          if (!ZFENCE) fence_async_smem();
#pragma unroll
          for (int p = 0; p < 2; p++)
            asm volatile("cp.async.bulk.global.shared::cta.bulk_group [%0], [%1], 2048;"
                         ::"l"(g_z + (size_t)((e >> 1) * NCTA + c) * S + (e & 1) * 1024 + p * 512), "r"(sb + off_Y(e >> 1) + p * YW + (e & 1) * 2048) : "memory");
          bulk_commit();
          bulk_wait();
          if (e & 1) mbar_arrive(bar + 8 * (B_ZDONE + (e >> 1)));
        }
        __syncwarp();
        if (ZHINT_DELAY) __nanosleep(ZHINT_DELAY);
        if (lane < 8) asm volatile("red.relaxed.gpu.global.add.u32 [%0], 1;" ::"l"(g_cnt + 32 * (8 * (e & 1) + lane) + C_Z + (e >> 1)) : "memory");
        if (lane == 0 && (e & 1)) TS(17 + (e >> 1));
      }
      if (EXP & 2) { if (lane == 0) signal(cnt + C_ACT + 1); return; }
      const int nbox = m < 12 ? 8 : 4;
      const uint32_t wb = sb + OFF_X + 16384;
      if (lane == 0) {
        fence_async_smem();
#pragma unroll 1
        for (int b = 0; b < 2; b++) {
          mbar_expect_tx(bar + 8 * (B_WFULL + b), 8192);
          tma2d(wb + b * 8192, &P.tm_w1c, bar + 8 * (B_WFULL + b), 448 * j + 16 * m, 256 * b);
        }
      }
#pragma unroll 1
      for (int tile = 0; tile < nbox / 4; tile++) {
        const int n0 = 448 * j + 256 * tile + 16 * m;
        const uint32_t bv = __ldg((const unsigned short*)P.b1 + n0 + 8 * (lane & 1) + ((lane >> 1) & 7));
        float cs[8];
#pragma unroll
        for (int i = 0; i < 8; i++) cs[i] = 0.f;
#pragma unroll 1
        for (int b = 0; b < 8; b++) {
          const int box = 4 * tile + (b >> 1), sl = box & 1;
          mbar_wait(bar + 8 * (B_WFULL + sl), (box >> 1) & 1);
          uint4 v[8];
#pragma unroll
          for (int i = 0; i < 8; i++) v[i] = lds128(wb + (8 * (b & 3) + i) * 512 + lane * 16);
          const uint32_t a0 = badd2(badd2(badd2(v[0].x, v[1].x), badd2(v[2].x, v[3].x)), badd2(badd2(v[4].x, v[5].x), badd2(v[6].x, v[7].x)));
          const uint32_t a1 = badd2(badd2(badd2(v[0].y, v[1].y), badd2(v[2].y, v[3].y)), badd2(badd2(v[4].y, v[5].y), badd2(v[6].y, v[7].y)));
          const uint32_t a2 = badd2(badd2(badd2(v[0].z, v[1].z), badd2(v[2].z, v[3].z)), badd2(badd2(v[4].z, v[5].z), badd2(v[6].z, v[7].z)));
          const uint32_t a3 = badd2(badd2(badd2(v[0].w, v[1].w), badd2(v[2].w, v[3].w)), badd2(badd2(v[4].w, v[5].w), badd2(v[6].w, v[7].w)));
          if ((b & 1) && box + 2 < nbox) {
            __syncwarp();
            if (lane == 0) {
              mbar_expect_tx(bar + 8 * (B_WFULL + sl), 8192);
              tma2d(wb + sl * 8192, &P.tm_w1c, bar + 8 * (B_WFULL + sl), 448 * j + 256 * ((box + 2) >> 2) + 16 * m, 256 * ((box + 2) & 3));
            }
          }
          cs[0] += bflo(a0); cs[1] += bfhi(a0); cs[2] += bflo(a1); cs[3] += bfhi(a1);
          cs[4] += bflo(a2); cs[5] += bfhi(a2); cs[6] += bflo(a3); cs[7] += bfhi(a3);
        }
#pragma unroll 1
        for (int o = 2; o < 32; o <<= 1) {
#pragma unroll
          for (int i = 0; i < 8; i++) cs[i] += __shfl_xor_sync(0xffffffffu, cs[i], o);
        }
        float cv = cs[0];
#pragma unroll
        for (int i = 1; i < 8; i++) cv = ((lane >> 1) & 7) == i ? cs[i] : cv;
        const uint32_t hi = packbf(cv, 0.f), lo = packbf(cv - bflo(hi), 0.f);
        if (lane < 16) stg_b128(g_baug + n0 + 8 * (lane & 1) + (lane >> 1), hi | (lo << 16), hi | (bv << 16), bv, epoch);
        if (lane == 0) TS(38 + tile);
      }
#pragma unroll 1
      for (int tile = 0; tile < 2; tile++) {
        const int n0 = 448 * j + 256 * tile;
        uint4 v[8], hv[4];
        int it = 0;
        while (true) {
          bool ok = true;
#pragma unroll
          for (int i = 0; i < 8; i++) v[i] = ldg_b128(g_baug + n0 + min(lane + 32 * i, tile ? 191 : 255));
#pragma unroll
          for (int i = 0; i < 4; i++) hv[i] = ldg_b128(g_hstat + 128 * m + lane + 32 * i);
#pragma unroll
          for (int i = 0; i < 8; i++) ok = ok && v[i].w == epoch;
#pragma unroll
          for (int i = 0; i < 4; i++) ok = ok && (hv[i].z >> 16) == (epoch & 0xffffu);
          if (__all_sync(0xffffffffu, ok)) break;
          __nanosleep(200);
          if (++it > (1 << 20)) __trap();
        }
        mbar_wait(bar + 8 * (tile ? B_XFREE : B_HOUT + 2), 0);
#pragma unroll
        for (int i = 0; i < 8; i++) {
          sts128(sb + OFF_X + (lane + 32 * i) * 16, v[i].x, v[i].y, v[i].z, 0);
          sts128(sb + OFF_X + 16384 + (lane + 32 * i) * 16, v[i].x, v[i].y, v[i].z, 0);
        }
        if (tile == 0) {
#pragma unroll
          for (int i = 0; i < 4; i++) sts128(sb + OFF_HS + (lane + 32 * i) * 16, hv[i].x, hv[i].y, hv[i].z & 0xffffu, hv[i].w);
        } else {
          const uint32_t* b2p = (const uint32_t*)(P.b2 + 128 * j);
          ((uint32_t*)(smem + OFF_RED))[(lane & 3) * 16 + (lane >> 2)] = __ldg(b2p + lane);
          ((uint32_t*)(smem + OFF_RED))[(lane & 3) * 16 + 8 + (lane >> 2)] = __ldg(b2p + 32 + lane);
        }
        fence_async_smem();
        __syncwarp();
        if (lane == 0) { mbar_arrive(bar + 8 * B_CSFULL); TS(21 + 19 * tile); }
      }
    } else {
      if ((EXP & 2) && !(EXP & 4)) { if (lane == 0) mbar_arrive(bar + 8 * B_XREAD); return; }
      const int hw = zw - 1, rowb = 128 * m + 16 * j;
      const int q = lane & 3, sl = ((lane >> 2) & 3) + 16 * (lane >> 4);
      float2* red = (float2*)(smem + OFF_RED);
      uint32_t xr[4][8][4];
      uint32_t pv[4];
      const uint32_t xa = sb + OFF_KVB + q * 8224 + (64 * hw + sl) * 16;
      mbar_wait(bar + 8 * B_XFULL, 0);
#pragma unroll
      for (int a = 0; a < 4; a++) {
#pragma unroll
        for (int i = 0; i < 8; i++) {
          const uint4 v = lds128(xa + a * 2048 + (4 * (i & 3) + 32 * (i >> 2)) * 16);
          xr[a][i][0] = v.x; xr[a][i][1] = v.y; xr[a][i][2] = v.z; xr[a][i][3] = v.w;
        }
      }
      __syncwarp();
      if (lane == 0) mbar_arrive(bar + 8 * B_XREAD);
      auto fetch_z = [&](int r) {
        if (lane == 0) {
          acquire_async();
          mbar_expect_tx(bar + 8 * (B_ZIN + hw), 4096);
          tma2d(sb + (r < 2 ? OFF_HB : OFF_X) + hw * HB_WARP, &P.tm_z, bar + 8 * (B_ZIN + hw),
                2 * ((rowb & 1024) + ((rowb >> 6) & 1) * 512 + (m & 7) * 64 + (rowb & 63)), r * NCTA + 64 * hw);
        }
        __syncwarp();
      };
      if ((EXP & 2) && !(EXP & 8)) return;
      uint32_t zph = 0;
      const uint32_t tag = (lane & 12) == 0;
      if (!(EXP & 64)) wait_count_warp(cnt + C_Z, epoch * NCTA);
      fetch_z(0);
      {
        uint32_t rs2[4], nm2[4];
        mbar_wait(bar + 8 * B_XDONE, 0);
#pragma unroll
        for (int a = 0; a < 4; a++) {
          const float4 r0 = ((const float4*)(smem + OFF_XS))[2 * (4 * q + a)], r1 = ((const float4*)(smem + OFF_XS))[2 * (4 * q + a) + 1];
          const float mu = ((r0.x + r0.z) + (r1.x + r1.z)) * (1.f / D);
          const float rs = rsqrtf(fmaxf(fmaf(-mu, mu, ((r0.y + r0.w) + (r1.y + r1.w)) * (1.f / D)), 0.f) + 1e-5f);
          rs2[a] = packbf(rs, rs);
          nm2[a] = packbf(-mu * bflo(rs2[a]), -mu * bflo(rs2[a]));
        }
        if (tid == 320) TS(37);
#pragma unroll
        for (int r = 0; r < 4; r++) {
          const uint32_t hb = sb + (r < 2 ? OFF_HB : OFF_X) + hw * HB_WARP;
          for (int it = 0;; it++) {
            mbar_wait(bar + 8 * (B_ZIN + hw), zph);
            zph ^= 1;
            uint32_t sum = 0;
#pragma unroll
            for (int i = 0; i < 8; i++) sum += lds32(hb + lane * 16 + i * 512) & 1;
            if (__all_sync(0xffffffffu, sum == (epoch & 1) * 8)) break;
            if (it > (1 << 16)) __trap();
            if (lane == 0) CNT(16 + r);
            fetch_z(r);
          }
          if (tid == 320) TS(27 + r);
          uint32_t zc = 0;
          if (r < 3) zc = ldg_relaxed(cnt + C_Z + r + 1);
          uint32_t za = hb + sl * 64 + q * 16;
#pragma unroll 1
          for (int once = blockIdx.y; once < 1; once++)
#pragma unroll
          for (int i = 0; i < 8; i += 2) {
            const uint4 z0 = lds128(za + (4 * (i & 3) + 32 * (i >> 2)) * 64), z1 = lds128(za + (4 * (i & 3) + 4 + 32 * (i >> 2)) * 64);
            const uint32_t zz[2][4] = {{z0.x & ~1u, z0.y, z0.z, z0.w}, {z1.x & ~1u, z1.y, z1.z, z1.w}};
#pragma unroll
            for (int e = 0; e < 2; e++)
#pragma unroll
              for (int a = 0; a < 4; a++)
                asm volatile("{.reg .b32 t; fma.rn.bf16x2 t, %0, %1, %2; fma.rn.bf16x2 t, t, %3, %0; or.b32 %0, t, %4;}"
                             : "+r"(xr[a][i + e][r]) : "r"(rs2[a]), "r"(nm2[a]), "r"(zz[e][a]), "r"(tag));
            if (i < 6) za += xr[3][i][r] & blockIdx.y;
          }
          __syncwarp();
          const uint32_t ha = hb + q * 128 + (((lane >> 4) * 4 + q) << 4) + (lane & 12);
#pragma unroll
          for (int i = 0; i < 4; i++)
#pragma unroll
            for (int a = 0; a < 2; a++) {
              const uint32_t p = ha ^ ((i << 4) | (a * 576));
              asm volatile("st.shared.b32 [%0], %1; st.shared.b32 [%0+1024], %2; st.shared.b32 [%0+2048], %3; st.shared.b32 [%0+3072], %4;"
                           ::"r"(p), "r"(xr[a][i][r]), "r"(xr[a + 2][i][r]), "r"(xr[a][i + 4][r]), "r"(xr[a + 2][i + 4][r]) : "memory");
            }
          fence_async_smem();
          __syncwarp();
          if (tid == 320) TS(23 + r);
          if (lane == 0) {
#pragma unroll
            for (int b = 0; b < 2; b++)
              asm volatile("cp.async.bulk.tensor.3d.global.shared::cta.bulk_group [%0, {%2,%3,%4}], [%1];"
                           ::"l"(&P.tm_hst), "r"(hb + b * 2048), "r"(256 * r + 128 * hw + 64 * b), "r"((rowb + (epoch & 1) * S) >> 2), "r"(0) : "memory");
            bulk_commit();
            bulk_wait();
            if (HINT_DELAY) __nanosleep(HINT_DELAY);
            asm volatile("red.relaxed.gpu.global.add.u32 [%0], 1;" ::"l"(cnt + C_H + r) : "memory");
            if (r & 1) mbar_arrive(bar + 8 * (B_HOUT + 2 * (r >> 1) + hw));
            if (tid == 320) TS(32 + r);
          }
          __syncwarp();
          if (r < 3) {
            if (!__all_sync(0xffffffffu, (int)(zc - epoch * NCTA) >= 0)) wait_count_warp(cnt + C_Z + r + 1, epoch * NCTA);
            if (r == 1) mbar_wait(bar + 8 * (B_ZDONE + 3), 0);
            fetch_z(r + 1);
          }
        }
#pragma unroll
        for (int a = 0; a < 4; a++) {
          const float4 r0 = ((const float4*)(smem + OFF_XS))[2 * (4 * q + a)], r1 = ((const float4*)(smem + OFF_XS))[2 * (4 * q + a) + 1];
          const float mu = ((r0.x + r0.z) + (r1.x + r1.z)) * (1.f / D);
          pv[a] = packbf(mu, mu);
        }
        float t1[4], t2[4];
#pragma unroll
        for (int a = 0; a < 4; a++) {
          t1[a] = 0.f; t2[a] = 0.f;
          uint32_t p1, p2;
#pragma unroll
          for (int ch = 0; ch < 4; ch++) {
            uint32_t c1 = 0, c2 = 0;
#pragma unroll
            for (int i = 0; i < 8; i++) {
              const uint32_t dd = bsub2(xr[a][2 * ch + (i >> 2)][i & 3], pv[a]);
              c1 = i ? badd2(c1, dd) : dd;
              c2 = i ? bfma2(dd, dd, c2) : bmul2(dd, dd);
            }
            if (ch & 1) {
              p1 = badd2(p1, c1); p2 = badd2(p2, c2);
              t1[a] += bflo(p1) + bfhi(p1);
              t2[a] += bflo(p2) + bfhi(p2);
            } else {
              p1 = c1; p2 = c2;
            }
          }
          const float pf = bflo(pv[a]);
          t2[a] = fmaf(pf, fmaf(pf, 64.f, 2.f * t1[a]), t2[a]);
          t1[a] = fmaf(pf, 64.f, t1[a]);
        }
#pragma unroll
        for (int o = 4; o < 32; o <<= 1) {
#pragma unroll
          for (int a = 0; a < 4; a++) { t1[a] += __shfl_xor_sync(0xffffffffu, t1[a], o); t2[a] += __shfl_xor_sync(0xffffffffu, t2[a], o); }
        }
        if (lane < 4) {
          ((float4*)red)[hw * 8 + 2 * q] = make_float4(t1[0], t2[0], t1[1], t2[1]);
          ((float4*)red)[hw * 8 + 2 * q + 1] = make_float4(t1[2], t2[2], t1[3], t2[3]);
        }
        bar_sync(1, 64);
      }
      if (EXP & 2) return;
      if (hw == 0 && lane < 16) {
        const float2 r0 = red[lane], r1 = red[16 + lane];
        const float mu = (r0.x + r1.x) * (1.f / D);
        const float var = fmaxf(fmaf(-mu, mu, (r0.y + r1.y) * (1.f / D)), 0.f) + 1e-5f;
        const float sd = sqrtf(var);
        const uint32_t hi = packbf(-mu, sd), lo = packbf(-mu - bflo(hi), sd - bfhi(hi));
        stg_b128(g_hstat + rowb + lane, __byte_perm(hi, 0, 0x1010), __byte_perm(lo, hi, 0x7610), __byte_perm(lo, epoch, 0x5432), __float_as_uint(1.f / var));
        if (lane == 0) TS(43);
      }
      if (hw == 0 && lane == 0) {
#pragma unroll 1
        for (int tile = 0; tile < 2; tile++) {
          mbar_wait(bar + 8 * (B_ADONE + tile), 0);
          const int nb = tile ? 6 : 8;
#pragma unroll 1
          for (int i = nb - 1; i >= 0; i--) {
            if (!(EXP & 1) || tile == 0) tma_store(&P.tm_actst, sb + off_act(tile, i & 1, i >> 1), 448 * j + 256 * tile + 64 * (i >> 1), 128 * m + 64 * (i & 1));
            bulk_commit();
            bulk_wait_read();
            if (tile == 1 && i == 4) mbar_arrive(bar + 8 * B_SFREE);
            if (tile == 0 || i <= 4) __nanosleep(ST_SLEEP);
          }
          if (tile == 0) {
            mbar_arrive(bar + 8 * B_XFREE);
          } else {
            mbar_expect_tx(bar + 8 * B_HRES, 32768);
            tma3d(sb + OFF_X, &P.tm_hres, bar + 8 * B_HRES, 32 * j, 0, 128 * m + (epoch & 1) * S);
          }
          bulk_wait();
          fence_async_global();
          signal(cnt + C_ACT + tile);
          TS(41 + tile);
        }
      }
      if (hw == 1 && !(EXP & 256)) {
        mbar_wait(bar + 8 * B_HRES, 0);
        uint4* p = (uint4*)(g_h + (size_t)((~epoch & 1) * S + rowb) * D) + lane;
#pragma unroll 1
        for (int i = 0; i < 64; i++) {
          p[32 * i] = make_uint4(0, 0, 0, 0);
          __nanosleep(64);
        }
      }
      if (lane == 0) {
        const uint32_t pb = mapa(sb, rank ^ 1);
        mbar_wait(bar + 8 * (B_PEER + hw), 1);
        mbar_wait(bar + 8 * (B_SEND + hw), 0);
        asm volatile("cp.async.bulk.shared::cluster.shared::cta.mbarrier::complete_tx::bytes [%0], [%1], 16384, [%2];"
                     ::"r"(pb + ((NBIG - 1 - hw) & 3) * 49152 + 32768), "r"(sb + ((NBIG + 1 - hw) & 3) * 49152 + 32768), "r"(pb + OFF_BAR + 8 * (B_RECV + hw)) : "memory");
      }
    }
  }
}

typedef CUresult (*PFN_encode)(CUtensorMap*, CUtensorMapDataType, cuuint32_t, void*, const cuuint64_t*, const cuuint64_t*, const cuuint32_t*,
                               const cuuint32_t*, CUtensorMapInterleave, CUtensorMapSwizzle, CUtensorMapL2promotion, CUtensorMapFloatOOBfill);

void encode(PFN_encode enc, CUtensorMap* m, const void* ptr, int rank, const cuuint64_t* dims, const cuuint64_t* strides, const cuuint32_t* box,
            CUtensorMapSwizzle swz) {
  const cuuint32_t es[5] = {1, 1, 1, 1, 1};
  enc(m, CU_TENSOR_MAP_DATA_TYPE_BFLOAT16, rank, (void*)ptr, dims, strides, box, es, CU_TENSOR_MAP_INTERLEAVE_NONE, swz,
      CU_TENSOR_MAP_L2_PROMOTION_L2_128B, CU_TENSOR_MAP_FLOAT_OOB_FILL_NONE);
}

}

extern "C" void kernel_launch(void* const* d_in, const int* in_sizes, int n_in, void* d_out, int out_size) {
  static PFN_encode enc = nullptr;
  static void *p_h = nullptr, *p_act = nullptr, *p_z = nullptr;
  if (!enc) {
    cudaDriverEntryPointQueryResult qr;
    cudaGetDriverEntryPoint("cuTensorMapEncodeTiled", (void**)&enc, cudaEnableDefault, &qr);
    cudaGetSymbolAddress(&p_h, g_h);
    cudaGetSymbolAddress(&p_act, g_act);
    cudaGetSymbolAddress(&p_z, g_z);
    cudaFuncSetAttribute(fused_kernel, cudaFuncAttributeMaxDynamicSharedMemorySize, SMEM_BYTES);
  }
  Params P;
  P.x = (const __nv_bfloat16*)d_in[0];
  P.shift_k = (const __nv_bfloat16*)d_in[3];
  P.ssm_k = (const __nv_bfloat16*)d_in[4];
  P.ssm_D = (const __nv_bfloat16*)d_in[5];
  P.w1 = (const __nv_bfloat16*)d_in[7];
  P.b1 = (const __nv_bfloat16*)d_in[8];
  P.w2 = (const __nv_bfloat16*)d_in[9];
  P.b2 = (const __nv_bfloat16*)d_in[10];
  {
    const cuuint64_t dims[3] = {D, S / 8, 8}, str[2] = {8 * D * 2, D * 2};
    const cuuint32_t box[3] = {16, 17, 8};
    encode(enc, &P.tm_k, d_in[1], 3, dims, str, box, CU_TENSOR_MAP_SWIZZLE_32B);
    encode(enc, &P.tm_v, d_in[2], 3, dims, str, box, CU_TENSOR_MAP_SWIZZLE_32B);
  }
  {
    const cuuint64_t dims[2] = {D, S}, dimh[2] = {D, 2 * S}, str[1] = {D * 2};
    const cuuint32_t box[2] = {64, 128}, boxo[2] = {64, 64};
    encode(enc, &P.tm_h, p_h, 2, dimh, str, box, CU_TENSOR_MAP_SWIZZLE_128B);
    encode(enc, &P.tm_out, d_out, 2, dims, str, boxo, CU_TENSOR_MAP_SWIZZLE_128B);
  }
  {
    const cuuint64_t dims[3] = {F, 8, D / 8}, str[2] = {F * 2, 8 * F * 2};
    const cuuint32_t box[3] = {64, 2, 32};
    encode(enc, &P.tm_w1, P.w1, 3, dims, str, box, CU_TENSOR_MAP_SWIZZLE_128B);
  }
  {
    const cuuint64_t dims[2] = {2 * S, 4 * NCTA}, str[1] = {S * 4};
    const cuuint32_t box[2] = {32, 64};
    encode(enc, &P.tm_z, p_z, 2, dims, str, box, CU_TENSOR_MAP_SWIZZLE_NONE);
  }
  {
    const cuuint64_t dims[3] = {D, S / 2, 4}, str[2] = {4 * D * 2, D * 2};
    const cuuint32_t box[3] = {64, 4, 4};
    encode(enc, &P.tm_hst, p_h, 3, dims, str, box, CU_TENSOR_MAP_SWIZZLE_128B);
  }
  {
    const cuuint64_t dims[2] = {F, D}, str[1] = {F * 2};
    const cuuint32_t box[2] = {16, 256};
    encode(enc, &P.tm_w1c, P.w1, 2, dims, str, box, CU_TENSOR_MAP_SWIZZLE_NONE);
  }
  {
    const cuuint64_t dims[2] = {F, S}, str[1] = {F * 2};
    const cuuint32_t box[2] = {64, 128}, boxs[2] = {64, 64};
    encode(enc, &P.tm_act, p_act, 2, dims, str, box, CU_TENSOR_MAP_SWIZZLE_128B);
    encode(enc, &P.tm_actst, p_act, 2, dims, str, boxs, CU_TENSOR_MAP_SWIZZLE_128B);
  }
  {
    const cuuint64_t dims[2] = {D, F}, str[1] = {D * 2};
    const cuuint32_t box[2] = {64, 64};
    encode(enc, &P.tm_w2, P.w2, 2, dims, str, box, CU_TENSOR_MAP_SWIZZLE_128B);
  }
  {
    const cuuint64_t dims[3] = {256, 4, 2 * S}, str[2] = {512, D * 2};
    const cuuint32_t box[3] = {32, 4, 128};
    encode(enc, &P.tm_hres, p_h, 3, dims, str, box, CU_TENSOR_MAP_SWIZZLE_64B);
  }
  fused_kernel<<<NCTA, NTHREADS, SMEM_BYTES>>>(P);
}
```

```cpp
#include <cuda_runtime.h>
#include <cuda_bf16.h>
#include <cuda.h>
#include <stdint.h>

#define DBG_TS 0
#define KV_GATE 3
#define NU_MMA 0
#define POLL_SLEEP 60
#define CS_LATE 0
#define ZFENCE 0
#define X_GATE 6
#define START_GATE 0
#define AUG_LAST 0
#define ZNA 2
#define KP 2
#define HINT_DELAY 0
#define ZHINT_DELAY 0
#define PF_EARLY 3
#define XPOS 6
#define CLR_LATE 0
#define HR_SLEEP 250
#define LAG 4
#define KFIRST 2
#define MC0 0
#define XPF 0
#define XPF0 1
#define LAG0 0
#define LAG1 0
#define Z3_LATE 1
#define SPLIT 1
#define T_EP 0
#define T_ZC 0
#define T_P8 0
#define YP 2
#define EARLY_ARR 1
#define DEFER0 2
#define DEFER1 1
#define EXP 0
#define ST_SLEEP 200

#define STR2(x) #x
#define STR(x) STR2(x)

namespace {

constexpr int S = 2048, D = 1024, F = 3584;
constexpr int NCTA = 128, NTHREADS = 384;

constexpr int UT_COPY = 1040 * 4;
constexpr int UT_SIZE = 2 * UT_COPY;
constexpr int KT_SIZE = 16 + 4096;
constexpr int T_SIZE = 2 * (UT_SIZE + KT_SIZE);
constexpr int KV_BOX = 17 * 8 * 32;
constexpr int KV_SLOT = 4 * KV_BOX;
constexpr int KV_SIZE = 2 * KV_SLOT;
constexpr int YW0 = 2048, YW1 = 2048 + 96, YH1 = 8 * YW0;
constexpr int YBUF = 4 * (YW0 + YW1);
constexpr int OFF_T3 = 196608 - T_SIZE;
constexpr int HB_WARP = 4096;
constexpr int OFF_HB = (OFF_T3 - 2 * HB_WARP) & ~1023;
constexpr int OFF_KVB = (OFF_HB - 2 * YBUF) & ~255;
constexpr int OFF_T2 = OFF_KVB - T_SIZE;
constexpr int OFF_KVA = (OFF_T2 - KV_SIZE) & ~255;
constexpr int OFF_T1 = OFF_KVA - T_SIZE;
constexpr int OFF_T0 = OFF_T1 - T_SIZE;
constexpr int OFF_X = 196608;
constexpr int OFF_HS = OFF_X + 32768;
constexpr int OFF_XS = OFF_X + 34304;
constexpr int OFF_RED = OFF_X + 34816;
constexpr int OFF_BAR = OFF_X + 35072;
constexpr int SMEM_BYTES = 232448;
static_assert(OFF_T0 >= KV_SLOT && 2 * YBUF <= KV_SIZE && OFF_X + 2 * YBUF <= OFF_RED && OFF_BAR + 640 <= SMEM_BYTES, "smem map");
static_assert(OFF_KVB + KV_SIZE <= OFF_T3 && OFF_HB >= 147456, "smem map");
static_assert(OFF_KVB + 32864 <= OFF_HB, "x rows");
static_assert(OFF_T2 >= 98304, "stage 1 must only overlap T0,T1,KVA");
static_assert(OFF_T3 >= 147456, "stage 2 must not overlap T3");

enum {
  B_KVFULL = 0, B_KFULL = 8, B_UFULL = 16, B_YFULL = 24  , B_ZFULL = 32  ,
  B_FULL = 40, B_ZDONE = 44  , B_FULL2 = 0, B_EMPTY2 = 24  ,
  B_CSFULL = 48, B_HRES = 49, B_XFREE = 50, B_SFREE = 51, B_HSFULL = 52, B_XLOW = 53, B_XFULL = 54, B_XSTAT = 55,
  B_EMPTY = 56, B_KVFREE = 60  , B_XREAD = 63, B_ADONE = 64, B_UREST = 66  , B_XDONE = 68, B_ASLOT = 69,
  B_ZIN = 72  , B_WFULL = 74  , B_HOUT = 76
};

struct Params {
  CUtensorMap tm_k, tm_v, tm_z, tm_hst, tm_h, tm_w1a, tm_w1b, tm_w1c, tm_actst, tm_w2, tm_hres, tm_out;
  const __nv_bfloat16 *x, *shift_k, *ssm_k, *ssm_D, *w1, *b1, *w2, *b2;
};

__device__ __align__(1024) uint32_t g_z[4 * NCTA * S];
__device__ __align__(1024) __nv_bfloat16 g_h[2 * S * D];
__device__ __align__(1024) __nv_bfloat16 g_act[S * F];
__device__ __align__(128) uint4 g_hstat[S];
__device__ __align__(128) uint4 g_cs[4 * F / 2];
enum { C_Z = 0, C_H = 4, C_ACT = 8 };
__device__ __align__(128) uint32_t g_cnt[16 * 32];
#define CNT(i)
#define TSM(idx) do {} while (0)
#define TSMT(idx, thr) do {} while (0)
#define TSDUMP() do {} while (0)
#define TS(slot) do {} while (0)
#define TS0(slot) do {} while (0)

template<int N> __device__ __forceinline__ void wgmma_rs(float* d, const uint32_t* a, uint64_t db, int sc);
template<int N> __device__ __forceinline__ void wgmma_ss(float* d, uint64_t da, uint64_t db, int sc);
template<> __device__ __forceinline__ void wgmma_rs<16>(float* d, const uint32_t* a, uint64_t db, int sc) {
  asm volatile("{.reg .pred p; setp.ne.b32 p, %13, 0;\n"
  "wgmma.mma_async.sync.aligned.m64n16k16.f32.bf16.bf16 {%0,%1,%2,%3,%4,%5,%6,%7}, {%8,%9,%10,%11}, %12, p, 1, 1, 0;}\n"
  : "+f"(d[0]),"+f"(d[1]),"+f"(d[2]),"+f"(d[3]),"+f"(d[4]),"+f"(d[5]),"+f"(d[6]),"+f"(d[7])
  : "r"(a[0]), "r"(a[1]), "r"(a[2]), "r"(a[3]), "l"(db), "r"(sc));
}
template<> __device__ __forceinline__ void wgmma_rs<32>(float* d, const uint32_t* a, uint64_t db, int sc) {
  asm volatile("{.reg .pred p; setp.ne.b32 p, %21, 0;\n"
  "wgmma.mma_async.sync.aligned.m64n32k16.f32.bf16.bf16 {%0,%1,%2,%3,%4,%5,%6,%7,%8,%9,%10,%11,%12,%13,%14,%15}, {%16,%17,%18,%19}, %20, p, 1, 1, 0;}\n"
  : "+f"(d[0]),"+f"(d[1]),"+f"(d[2]),"+f"(d[3]),"+f"(d[4]),"+f"(d[5]),"+f"(d[6]),"+f"(d[7]),"+f"(d[8]),"+f"(d[9]),"+f"(d[10]),"+f"(d[11]),"+f"(d[12]),"+f"(d[13]),"+f"(d[14]),"+f"(d[15])
  : "r"(a[0]), "r"(a[1]), "r"(a[2]), "r"(a[3]), "l"(db), "r"(sc));
}
template<> __device__ __forceinline__ void wgmma_rs<48>(float* d, const uint32_t* a, uint64_t db, int sc) {
  asm volatile("{.reg .pred p; setp.ne.b32 p, %29, 0;\n"
  "wgmma.mma_async.sync.aligned.m64n48k16.f32.bf16.bf16 {%0,%1,%2,%3,%4,%5,%6,%7,%8,%9,%10,%11,%12,%13,%14,%15,%16,%17,%18,%19,%20,%21,%22,%23}, {%24,%25,%26,%27}, %28, p, 1, 1, 0;}\n"
  : "+f"(d[0]),"+f"(d[1]),"+f"(d[2]),"+f"(d[3]),"+f"(d[4]),"+f"(d[5]),"+f"(d[6]),"+f"(d[7]),"+f"(d[8]),"+f"(d[9]),"+f"(d[10]),"+f"(d[11]),"+f"(d[12]),"+f"(d[13]),"+f"(d[14]),"+f"(d[15]),"+f"(d[16]),"+f"(d[17]),"+f"(d[18]),"+f"(d[19]),"+f"(d[20]),"+f"(d[21]),"+f"(d[22]),"+f"(d[23])
  : "r"(a[0]), "r"(a[1]), "r"(a[2]), "r"(a[3]), "l"(db), "r"(sc));
}
template<> __device__ __forceinline__ void wgmma_rs<64>(float* d, const uint32_t* a, uint64_t db, int sc) {
  asm volatile("{.reg .pred p; setp.ne.b32 p, %37, 0;\n"
  "wgmma.mma_async.sync.aligned.m64n64k16.f32.bf16.bf16 {%0,%1,%2,%3,%4,%5,%6,%7,%8,%9,%10,%11,%12,%13,%14,%15,%16,%17,%18,%19,%20,%21,%22,%23,%24,%25,%26,%27,%28,%29,%30,%31}, {%32,%33,%34,%35}, %36, p, 1, 1, 0;}\n"
  : "+f"(d[0]),"+f"(d[1]),"+f"(d[2]),"+f"(d[3]),"+f"(d[4]),"+f"(d[5]),"+f"(d[6]),"+f"(d[7]),"+f"(d[8]),"+f"(d[9]),"+f"(d[10]),"+f"(d[11]),"+f"(d[12]),"+f"(d[13]),"+f"(d[14]),"+f"(d[15]),"+f"(d[16]),"+f"(d[17]),"+f"(d[18]),"+f"(d[19]),"+f"(d[20]),"+f"(d[21]),"+f"(d[22]),"+f"(d[23]),"+f"(d[24]),"+f"(d[25]),"+f"(d[26]),"+f"(d[27]),"+f"(d[28]),"+f"(d[29]),"+f"(d[30]),"+f"(d[31])
  : "r"(a[0]), "r"(a[1]), "r"(a[2]), "r"(a[3]), "l"(db), "r"(sc));
}
template<> __device__ __forceinline__ void wgmma_rs<80>(float* d, const uint32_t* a, uint64_t db, int sc) {
  asm volatile("{.reg .pred p; setp.ne.b32 p, %45, 0;\n"
  "wgmma.mma_async.sync.aligned.m64n80k16.f32.bf16.bf16 {%0,%1,%2,%3,%4,%5,%6,%7,%8,%9,%10,%11,%12,%13,%14,%15,%16,%17,%18,%19,%20,%21,%22,%23,%24,%25,%26,%27,%28,%29,%30,%31,%32,%33,%34,%35,%36,%37,%38,%39}, {%40,%41,%42,%43}, %44, p, 1, 1, 0;}\n"
  : "+f"(d[0]),"+f"(d[1]),"+f"(d[2]),"+f"(d[3]),"+f"(d[4]),"+f"(d[5]),"+f"(d[6]),"+f"(d[7]),"+f"(d[8]),"+f"(d[9]),"+f"(d[10]),"+f"(d[11]),"+f"(d[12]),"+f"(d[13]),"+f"(d[14]),"+f"(d[15]),"+f"(d[16]),"+f"(d[17]),"+f"(d[18]),"+f"(d[19]),"+f"(d[20]),"+f"(d[21]),"+f"(d[22]),"+f"(d[23]),"+f"(d[24]),"+f"(d[25]),"+f"(d[26]),"+f"(d[27]),"+f"(d[28]),"+f"(d[29]),"+f"(d[30]),"+f"(d[31]),"+f"(d[32]),"+f"(d[33]),"+f"(d[34]),"+f"(d[35]),"+f"(d[36]),"+f"(d[37]),"+f"(d[38]),"+f"(d[39])
  : "r"(a[0]), "r"(a[1]), "r"(a[2]), "r"(a[3]), "l"(db), "r"(sc));
}
template<> __device__ __forceinline__ void wgmma_rs<96>(float* d, const uint32_t* a, uint64_t db, int sc) {
  asm volatile("{.reg .pred p; setp.ne.b32 p, %53, 0;\n"
  "wgmma.mma_async.sync.aligned.m64n96k16.f32.bf16.bf16 {%0,%1,%2,%3,%4,%5,%6,%7,%8,%9,%10,%11,%12,%13,%14,%15,%16,%17,%18,%19,%20,%21,%22,%23,%24,%25,%26,%27,%28,%29,%30,%31,%32,%33,%34,%35,%36,%37,%38,%39,%40,%41,%42,%43,%44,%45,%46,%47}, {%48,%49,%50,%51}, %52, p, 1, 1, 0;}\n"
  : "+f"(d[0]),"+f"(d[1]),"+f"(d[2]),"+f"(d[3]),"+f"(d[4]),"+f"(d[5]),"+f"(d[6]),"+f"(d[7]),"+f"(d[8]),"+f"(d[9]),"+f"(d[10]),"+f"(d[11]),"+f"(d[12]),"+f"(d[13]),"+f"(d[14]),"+f"(d[15]),"+f"(d[16]),"+f"(d[17]),"+f"(d[18]),"+f"(d[19]),"+f"(d[20]),"+f"(d[21]),"+f"(d[22]),"+f"(d[23]),"+f"(d[24]),"+f"(d[25]),"+f"(d[26]),"+f"(d[27]),"+f"(d[28]),"+f"(d[29]),"+f"(d[30]),"+f"(d[31]),"+f"(d[32]),"+f"(d[33]),"+f"(d[34]),"+f"(d[35]),"+f"(d[36]),"+f"(d[37]),"+f"(d[38]),"+f"(d[39]),"+f"(d[40]),"+f"(d[41]),"+f"(d[42]),"+f"(d[43]),"+f"(d[44]),"+f"(d[45]),"+f"(d[46]),"+f"(d[47])
  : "r"(a[0]), "r"(a[1]), "r"(a[2]), "r"(a[3]), "l"(db), "r"(sc));
}
template<> __device__ __forceinline__ void wgmma_rs<112>(float* d, const uint32_t* a, uint64_t db, int sc) {
  asm volatile("{.reg .pred p; setp.ne.b32 p, %61, 0;\n"
  "wgmma.mma_async.sync.aligned.m64n112k16.f32.bf16.bf16 {%0,%1,%2,%3,%4,%5,%6,%7,%8,%9,%10,%11,%12,%13,%14,%15,%16,%17,%18,%19,%20,%21,%22,%23,%24,%25,%26,%27,%28,%29,%30,%31,%32,%33,%34,%35,%36,%37,%38,%39,%40,%41,%42,%43,%44,%45,%46,%47,%48,%49,%50,%51,%52,%53,%54,%55}, {%56,%57,%58,%59}, %60, p, 1, 1, 0;}\n"
  : "+f"(d[0]),"+f"(d[1]),"+f"(d[2]),"+f"(d[3]),"+f"(d[4]),"+f"(d[5]),"+f"(d[6]),"+f"(d[7]),"+f"(d[8]),"+f"(d[9]),"+f"(d[10]),"+f"(d[11]),"+f"(d[12]),"+f"(d[13]),"+f"(d[14]),"+f"(d[15]),"+f"(d[16]),"+f"(d[17]),"+f"(d[18]),"+f"(d[19]),"+f"(d[20]),"+f"(d[21]),"+f"(d[22]),"+f"(d[23]),"+f"(d[24]),"+f"(d[25]),"+f"(d[26]),"+f"(d[27]),"+f"(d[28]),"+f"(d[29]),"+f"(d[30]),"+f"(d[31]),"+f"(d[32]),"+f"(d[33]),"+f"(d[34]),"+f"(d[35]),"+f"(d[36]),"+f"(d[37]),"+f"(d[38]),"+f"(d[39]),"+f"(d[40]),"+f"(d[41]),"+f"(d[42]),"+f"(d[43]),"+f"(d[44]),"+f"(d[45]),"+f"(d[46]),"+f"(d[47]),"+f"(d[48]),"+f"(d[49]),"+f"(d[50]),"+f"(d[51]),"+f"(d[52]),"+f"(d[53]),"+f"(d[54]),"+f"(d[55])
  : "r"(a[0]), "r"(a[1]), "r"(a[2]), "r"(a[3]), "l"(db), "r"(sc));
}
template<> __device__ __forceinline__ void wgmma_rs<128>(float* d, const uint32_t* a, uint64_t db, int sc) {
  asm volatile("{.reg .pred p; setp.ne.b32 p, %69, 0;\n"
  "wgmma.mma_async.sync.aligned.m64n128k16.f32.bf16.bf16 {%0,%1,%2,%3,%4,%5,%6,%7,%8,%9,%10,%11,%12,%13,%14,%15,%16,%17,%18,%19,%20,%21,%22,%23,%24,%25,%26,%27,%28,%29,%30,%31,%32,%33,%34,%35,%36,%37,%38,%39,%40,%41,%42,%43,%44,%45,%46,%47,%48,%49,%50,%51,%52,%53,%54,%55,%56,%57,%58,%59,%60,%61,%62,%63}, {%64,%65,%66,%67}, %68, p, 1, 1, 0;}\n"
  : "+f"(d[0]),"+f"(d[1]),"+f"(d[2]),"+f"(d[3]),"+f"(d[4]),"+f"(d[5]),"+f"(d[6]),"+f"(d[7]),"+f"(d[8]),"+f"(d[9]),"+f"(d[10]),"+f"(d[11]),"+f"(d[12]),"+f"(d[13]),"+f"(d[14]),"+f"(d[15]),"+f"(d[16]),"+f"(d[17]),"+f"(d[18]),"+f"(d[19]),"+f"(d[20]),"+f"(d[21]),"+f"(d[22]),"+f"(d[23]),"+f"(d[24]),"+f"(d[25]),"+f"(d[26]),"+f"(d[27]),"+f"(d[28]),"+f"(d[29]),"+f"(d[30]),"+f"(d[31]),"+f"(d[32]),"+f"(d[33]),"+f"(d[34]),"+f"(d[35]),"+f"(d[36]),"+f"(d[37]),"+f"(d[38]),"+f"(d[39]),"+f"(d[40]),"+f"(d[41]),"+f"(d[42]),"+f"(d[43]),"+f"(d[44]),"+f"(d[45]),"+f"(d[46]),"+f"(d[47]),"+f"(d[48]),"+f"(d[49]),"+f"(d[50]),"+f"(d[51]),"+f"(d[52]),"+f"(d[53]),"+f"(d[54]),"+f"(d[55]),"+f"(d[56]),"+f"(d[57]),"+f"(d[58]),"+f"(d[59]),"+f"(d[60]),"+f"(d[61]),"+f"(d[62]),"+f"(d[63])
  : "r"(a[0]), "r"(a[1]), "r"(a[2]), "r"(a[3]), "l"(db), "r"(sc));
}
template<> __device__ __forceinline__ void wgmma_rs<144>(float* d, const uint32_t* a, uint64_t db, int sc) {
  asm volatile("{.reg .pred p; setp.ne.b32 p, %77, 0;\n"
  "wgmma.mma_async.sync.aligned.m64n144k16.f32.bf16.bf16 {%0,%1,%2,%3,%4,%5,%6,%7,%8,%9,%10,%11,%12,%13,%14,%15,%16,%17,%18,%19,%20,%21,%22,%23,%24,%25,%26,%27,%28,%29,%30,%31,%32,%33,%34,%35,%36,%37,%38,%39,%40,%41,%42,%43,%44,%45,%46,%47,%48,%49,%50,%51,%52,%53,%54,%55,%56,%57,%58,%59,%60,%61,%62,%63,%64,%65,%66,%67,%68,%69,%70,%71}, {%72,%73,%74,%75}, %76, p, 1, 1, 0;}\n"
  : "+f"(d[0]),"+f"(d[1]),"+f"(d[2]),"+f"(d[3]),"+f"(d[4]),"+f"(d[5]),"+f"(d[6]),"+f"(d[7]),"+f"(d[8]),"+f"(d[9]),"+f"(d[10]),"+f"(d[11]),"+f"(d[12]),"+f"(d[13]),"+f"(d[14]),"+f"(d[15]),"+f"(d[16]),"+f"(d[17]),"+f"(d[18]),"+f"(d[19]),"+f"(d[20]),"+f"(d[21]),"+f"(d[22]),"+f"(d[23]),"+f"(d[24]),"+f"(d[25]),"+f"(d[26]),"+f"(d[27]),"+f"(d[28]),"+f"(d[29]),"+f"(d[30]),"+f"(d[31]),"+f"(d[32]),"+f"(d[33]),"+f"(d[34]),"+f"(d[35]),"+f"(d[36]),"+f"(d[37]),"+f"(d[38]),"+f"(d[39]),"+f"(d[40]),"+f"(d[41]),"+f"(d[42]),"+f"(d[43]),"+f"(d[44]),"+f"(d[45]),"+f"(d[46]),"+f"(d[47]),"+f"(d[48]),"+f"(d[49]),"+f"(d[50]),"+f"(d[51]),"+f"(d[52]),"+f"(d[53]),"+f"(d[54]),"+f"(d[55]),"+f"(d[56]),"+f"(d[57]),"+f"(d[58]),"+f"(d[59]),"+f"(d[60]),"+f"(d[61]),"+f"(d[62]),"+f"(d[63]),"+f"(d[64]),"+f"(d[65]),"+f"(d[66]),"+f"(d[67]),"+f"(d[68]),"+f"(d[69]),"+f"(d[70]),"+f"(d[71])
  : "r"(a[0]), "r"(a[1]), "r"(a[2]), "r"(a[3]), "l"(db), "r"(sc));
}
template<> __device__ __forceinline__ void wgmma_rs<160>(float* d, const uint32_t* a, uint64_t db, int sc) {
  asm volatile("{.reg .pred p; setp.ne.b32 p, %85, 0;\n"
  "wgmma.mma_async.sync.aligned.m64n160k16.f32.bf16.bf16 {%0,%1,%2,%3,%4,%5,%6,%7,%8,%9,%10,%11,%12,%13,%14,%15,%16,%17,%18,%19,%20,%21,%22,%23,%24,%25,%26,%27,%28,%29,%30,%31,%32,%33,%34,%35,%36,%37,%38,%39,%40,%41,%42,%43,%44,%45,%46,%47,%48,%49,%50,%51,%52,%53,%54,%55,%56,%57,%58,%59,%60,%61,%62,%63,%64,%65,%66,%67,%68,%69,%70,%71,%72,%73,%74,%75,%76,%77,%78,%79}, {%80,%81,%82,%83}, %84, p, 1, 1, 0;}\n"
  : "+f"(d[0]),"+f"(d[1]),"+f"(d[2]),"+f"(d[3]),"+f"(d[4]),"+f"(d[5]),"+f"(d[6]),"+f"(d[7]),"+f"(d[8]),"+f"(d[9]),"+f"(d[10]),"+f"(d[11]),"+f"(d[12]),"+f"(d[13]),"+f"(d[14]),"+f"(d[15]),"+f"(d[16]),"+f"(d[17]),"+f"(d[18]),"+f"(d[19]),"+f"(d[20]),"+f"(d[21]),"+f"(d[22]),"+f"(d[23]),"+f"(d[24]),"+f"(d[25]),"+f"(d[26]),"+f"(d[27]),"+f"(d[28]),"+f"(d[29]),"+f"(d[30]),"+f"(d[31]),"+f"(d[32]),"+f"(d[33]),"+f"(d[34]),"+f"(d[35]),"+f"(d[36]),"+f"(d[37]),"+f"(d[38]),"+f"(d[39]),"+f"(d[40]),"+f"(d[41]),"+f"(d[42]),"+f"(d[43]),"+f"(d[44]),"+f"(d[45]),"+f"(d[46]),"+f"(d[47]),"+f"(d[48]),"+f"(d[49]),"+f"(d[50]),"+f"(d[51]),"+f"(d[52]),"+f"(d[53]),"+f"(d[54]),"+f"(d[55]),"+f"(d[56]),"+f"(d[57]),"+f"(d[58]),"+f"(d[59]),"+f"(d[60]),"+f"(d[61]),"+f"(d[62]),"+f"(d[63]),"+f"(d[64]),"+f"(d[65]),"+f"(d[66]),"+f"(d[67]),"+f"(d[68]),"+f"(d[69]),"+f"(d[70]),"+f"(d[71]),"+f"(d[72]),"+f"(d[73]),"+f"(d[74]),"+f"(d[75]),"+f"(d[76]),"+f"(d[77]),"+f"(d[78]),"+f"(d[79])
  : "r"(a[0]), "r"(a[1]), "r"(a[2]), "r"(a[3]), "l"(db), "r"(sc));
}
template<> __device__ __forceinline__ void wgmma_rs<176>(float* d, const uint32_t* a, uint64_t db, int sc) {
  asm volatile("{.reg .pred p; setp.ne.b32 p, %93, 0;\n"
  "wgmma.mma_async.sync.aligned.m64n176k16.f32.bf16.bf16 {%0,%1,%2,%3,%4,%5,%6,%7,%8,%9,%10,%11,%12,%13,%14,%15,%16,%17,%18,%19,%20,%21,%22,%23,%24,%25,%26,%27,%28,%29,%30,%31,%32,%33,%34,%35,%36,%37,%38,%39,%40,%41,%42,%43,%44,%45,%46,%47,%48,%49,%50,%51,%52,%53,%54,%55,%56,%57,%58,%59,%60,%61,%62,%63,%64,%65,%66,%67,%68,%69,%70,%71,%72,%73,%74,%75,%76,%77,%78,%79,%80,%81,%82,%83,%84,%85,%86,%87}, {%88,%89,%90,%91}, %92, p, 1, 1, 0;}\n"
  : "+f"(d[0]),"+f"(d[1]),"+f"(d[2]),"+f"(d[3]),"+f"(d[4]),"+f"(d[5]),"+f"(d[6]),"+f"(d[7]),"+f"(d[8]),"+f"(d[9]),"+f"(d[10]),"+f"(d[11]),"+f"(d[12]),"+f"(d[13]),"+f"(d[14]),"+f"(d[15]),"+f"(d[16]),"+f"(d[17]),"+f"(d[18]),"+f"(d[19]),"+f"(d[20]),"+f"(d[21]),"+f"(d[22]),"+f"(d[23]),"+f"(d[24]),"+f"(d[25]),"+f"(d[26]),"+f"(d[27]),"+f"(d[28]),"+f"(d[29]),"+f"(d[30]),"+f"(d[31]),"+f"(d[32]),"+f"(d[33]),"+f"(d[34]),"+f"(d[35]),"+f"(d[36]),"+f"(d[37]),"+f"(d[38]),"+f"(d[39]),"+f"(d[40]),"+f"(d[41]),"+f"(d[42]),"+f"(d[43]),"+f"(d[44]),"+f"(d[45]),"+f"(d[46]),"+f"(d[47]),"+f"(d[48]),"+f"(d[49]),"+f"(d[50]),"+f"(d[51]),"+f"(d[52]),"+f"(d[53]),"+f"(d[54]),"+f"(d[55]),"+f"(d[56]),"+f"(d[57]),"+f"(d[58]),"+f"(d[59]),"+f"(d[60]),"+f"(d[61]),"+f"(d[62]),"+f"(d[63]),"+f"(d[64]),"+f"(d[65]),"+f"(d[66]),"+f"(d[67]),"+f"(d[68]),"+f"(d[69]),"+f"(d[70]),"+f"(d[71]),"+f"(d[72]),"+f"(d[73]),"+f"(d[74]),"+f"(d[75]),"+f"(d[76]),"+f"(d[77]),"+f"(d[78]),"+f"(d[79]),"+f"(d[80]),"+f"(d[81]),"+f"(d[82]),"+f"(d[83]),"+f"(d[84]),"+f"(d[85]),"+f"(d[86]),"+f"(d[87])
  : "r"(a[0]), "r"(a[1]), "r"(a[2]), "r"(a[3]), "l"(db), "r"(sc));
}
template<> __device__ __forceinline__ void wgmma_rs<192>(float* d, const uint32_t* a, uint64_t db, int sc) {
  asm volatile("{.reg .pred p; setp.ne.b32 p, %101, 0;\n"
  "wgmma.mma_async.sync.aligned.m64n192k16.f32.bf16.bf16 {%0,%1,%2,%3,%4,%5,%6,%7,%8,%9,%10,%11,%12,%13,%14,%15,%16,%17,%18,%19,%20,%21,%22,%23,%24,%25,%26,%27,%28,%29,%30,%31,%32,%33,%34,%35,%36,%37,%38,%39,%40,%41,%42,%43,%44,%45,%46,%47,%48,%49,%50,%51,%52,%53,%54,%55,%56,%57,%58,%59,%60,%61,%62,%63,%64,%65,%66,%67,%68,%69,%70,%71,%72,%73,%74,%75,%76,%77,%78,%79,%80,%81,%82,%83,%84,%85,%86,%87,%88,%89,%90,%91,%92,%93,%94,%95}, {%96,%97,%98,%99}, %100, p, 1, 1, 0;}\n"
  : "+f"(d[0]),"+f"(d[1]),"+f"(d[2]),"+f"(d[3]),"+f"(d[4]),"+f"(d[5]),"+f"(d[6]),"+f"(d[7]),"+f"(d[8]),"+f"(d[9]),"+f"(d[10]),"+f"(d[11]),"+f"(d[12]),"+f"(d[13]),"+f"(d[14]),"+f"(d[15]),"+f"(d[16]),"+f"(d[17]),"+f"(d[18]),"+f"(d[19]),"+f"(d[20]),"+f"(d[21]),"+f"(d[22]),"+f"(d[23]),"+f"(d[24]),"+f"(d[25]),"+f"(d[26]),"+f"(d[27]),"+f"(d[28]),"+f"(d[29]),"+f"(d[30]),"+f"(d[31]),"+f"(d[32]),"+f"(d[33]),"+f"(d[34]),"+f"(d[35]),"+f"(d[36]),"+f"(d[37]),"+f"(d[38]),"+f"(d[39]),"+f"(d[40]),"+f"(d[41]),"+f"(d[42]),"+f"(d[43]),"+f"(d[44]),"+f"(d[45]),"+f"(d[46]),"+f"(d[47]),"+f"(d[48]),"+f"(d[49]),"+f"(d[50]),"+f"(d[51]),"+f"(d[52]),"+f"(d[53]),"+f"(d[54]),"+f"(d[55]),"+f"(d[56]),"+f"(d[57]),"+f"(d[58]),"+f"(d[59]),"+f"(d[60]),"+f"(d[61]),"+f"(d[62]),"+f"(d[63]),"+f"(d[64]),"+f"(d[65]),"+f"(d[66]),"+f"(d[67]),"+f"(d[68]),"+f"(d[69]),"+f"(d[70]),"+f"(d[71]),"+f"(d[72]),"+f"(d[73]),"+f"(d[74]),"+f"(d[75]),"+f"(d[76]),"+f"(d[77]),"+f"(d[78]),"+f"(d[79]),"+f"(d[80]),"+f"(d[81]),"+f"(d[82]),"+f"(d[83]),"+f"(d[84]),"+f"(d[85]),"+f"(d[86]),"+f"(d[87]),"+f"(d[88]),"+f"(d[89]),"+f"(d[90]),"+f"(d[91]),"+f"(d[92]),"+f"(d[93]),"+f"(d[94]),"+f"(d[95])
  : "r"(a[0]), "r"(a[1]), "r"(a[2]), "r"(a[3]), "l"(db), "r"(sc));
}
template<> __device__ __forceinline__ void wgmma_rs<208>(float* d, const uint32_t* a, uint64_t db, int sc) {
  asm volatile("{.reg .pred p; setp.ne.b32 p, %109, 0;\n"
  "wgmma.mma_async.sync.aligned.m64n208k16.f32.bf16.bf16 {%0,%1,%2,%3,%4,%5,%6,%7,%8,%9,%10,%11,%12,%13,%14,%15,%16,%17,%18,%19,%20,%21,%22,%23,%24,%25,%26,%27,%28,%29,%30,%31,%32,%33,%34,%35,%36,%37,%38,%39,%40,%41,%42,%43,%44,%45,%46,%47,%48,%49,%50,%51,%52,%53,%54,%55,%56,%57,%58,%59,%60,%61,%62,%63,%64,%65,%66,%67,%68,%69,%70,%71,%72,%73,%74,%75,%76,%77,%78,%79,%80,%81,%82,%83,%84,%85,%86,%87,%88,%89,%90,%91,%92,%93,%94,%95,%96,%97,%98,%99,%100,%101,%102,%103}, {%104,%105,%106,%107}, %108, p, 1, 1, 0;}\n"
  : "+f"(d[0]),"+f"(d[1]),"+f"(d[2]),"+f"(d[3]),"+f"(d[4]),"+f"(d[5]),"+f"(d[6]),"+f"(d[7]),"+f"(d[8]),"+f"(d[9]),"+f"(d[10]),"+f"(d[11]),"+f"(d[12]),"+f"(d[13]),"+f"(d[14]),"+f"(d[15]),"+f"(d[16]),"+f"(d[17]),"+f"(d[18]),"+f"(d[19]),"+f"(d[20]),"+f"(d[21]),"+f"(d[22]),"+f"(d[23]),"+f"(d[24]),"+f"(d[25]),"+f"(d[26]),"+f"(d[27]),"+f"(d[28]),"+f"(d[29]),"+f"(d[30]),"+f"(d[31]),"+f"(d[32]),"+f"(d[33]),"+f"(d[34]),"+f"(d[35]),"+f"(d[36]),"+f"(d[37]),"+f"(d[38]),"+f"(d[39]),"+f"(d[40]),"+f"(d[41]),"+f"(d[42]),"+f"(d[43]),"+f"(d[44]),"+f"(d[45]),"+f"(d[46]),"+f"(d[47]),"+f"(d[48]),"+f"(d[49]),"+f"(d[50]),"+f"(d[51]),"+f"(d[52]),"+f"(d[53]),"+f"(d[54]),"+f"(d[55]),"+f"(d[56]),"+f"(d[57]),"+f"(d[58]),"+f"(d[59]),"+f"(d[60]),"+f"(d[61]),"+f"(d[62]),"+f"(d[63]),"+f"(d[64]),"+f"(d[65]),"+f"(d[66]),"+f"(d[67]),"+f"(d[68]),"+f"(d[69]),"+f"(d[70]),"+f"(d[71]),"+f"(d[72]),"+f"(d[73]),"+f"(d[74]),"+f"(d[75]),"+f"(d[76]),"+f"(d[77]),"+f"(d[78]),"+f"(d[79]),"+f"(d[80]),"+f"(d[81]),"+f"(d[82]),"+f"(d[83]),"+f"(d[84]),"+f"(d[85]),"+f"(d[86]),"+f"(d[87]),"+f"(d[88]),"+f"(d[89]),"+f"(d[90]),"+f"(d[91]),"+f"(d[92]),"+f"(d[93]),"+f"(d[94]),"+f"(d[95]),"+f"(d[96]),"+f"(d[97]),"+f"(d[98]),"+f"(d[99]),"+f"(d[100]),"+f"(d[101]),"+f"(d[102]),"+f"(d[103])
  : "r"(a[0]), "r"(a[1]), "r"(a[2]), "r"(a[3]), "l"(db), "r"(sc));
}
template<> __device__ __forceinline__ void wgmma_rs<224>(float* d, const uint32_t* a, uint64_t db, int sc) {
  asm volatile("{.reg .pred p; setp.ne.b32 p, %117, 0;\n"
  "wgmma.mma_async.sync.aligned.m64n224k16.f32.bf16.bf16 {%0,%1,%2,%3,%4,%5,%6,%7,%8,%9,%10,%11,%12,%13,%14,%15,%16,%17,%18,%19,%20,%21,%22,%23,%24,%25,%26,%27,%28,%29,%30,%31,%32,%33,%34,%35,%36,%37,%38,%39,%40,%41,%42,%43,%44,%45,%46,%47,%48,%49,%50,%51,%52,%53,%54,%55,%56,%57,%58,%59,%60,%61,%62,%63,%64,%65,%66,%67,%68,%69,%70,%71,%72,%73,%74,%75,%76,%77,%78,%79,%80,%81,%82,%83,%84,%85,%86,%87,%88,%89,%90,%91,%92,%93,%94,%95,%96,%97,%98,%99,%100,%101,%102,%103,%104,%105,%106,%107,%108,%109,%110,%111}, {%112,%113,%114,%115}, %116, p, 1, 1, 0;}\n"
  : "+f"(d[0]),"+f"(d[1]),"+f"(d[2]),"+f"(d[3]),"+f"(d[4]),"+f"(d[5]),"+f"(d[6]),"+f"(d[7]),"+f"(d[8]),"+f"(d[9]),"+f"(d[10]),"+f"(d[11]),"+f"(d[12]),"+f"(d[13]),"+f"(d[14]),"+f"(d[15]),"+f"(d[16]),"+f"(d[17]),"+f"(d[18]),"+f"(d[19]),"+f"(d[20]),"+f"(d[21]),"+f"(d[22]),"+f"(d[23]),"+f"(d[24]),"+f"(d[25]),"+f"(d[26]),"+f"(d[27]),"+f"(d[28]),"+f"(d[29]),"+f"(d[30]),"+f"(d[31]),"+f"(d[32]),"+f"(d[33]),"+f"(d[34]),"+f"(d[35]),"+f"(d[36]),"+f"(d[37]),"+f"(d[38]),"+f"(d[39]),"+f"(d[40]),"+f"(d[41]),"+f"(d[42]),"+f"(d[43]),"+f"(d[44]),"+f"(d[45]),"+f"(d[46]),"+f"(d[47]),"+f"(d[48]),"+f"(d[49]),"+f"(d[50]),"+f"(d[51]),"+f"(d[52]),"+f"(d[53]),"+f"(d[54]),"+f"(d[55]),"+f"(d[56]),"+f"(d[57]),"+f"(d[58]),"+f"(d[59]),"+f"(d[60]),"+f"(d[61]),"+f"(d[62]),"+f"(d[63]),"+f"(d[64]),"+f"(d[65]),"+f"(d[66]),"+f"(d[67]),"+f"(d[68]),"+f"(d[69]),"+f"(d[70]),"+f"(d[71]),"+f"(d[72]),"+f"(d[73]),"+f"(d[74]),"+f"(d[75]),"+f"(d[76]),"+f"(d[77]),"+f"(d[78]),"+f"(d[79]),"+f"(d[80]),"+f"(d[81]),"+f"(d[82]),"+f"(d[83]),"+f"(d[84]),"+f"(d[85]),"+f"(d[86]),"+f"(d[87]),"+f"(d[88]),"+f"(d[89]),"+f"(d[90]),"+f"(d[91]),"+f"(d[92]),"+f"(d[93]),"+f"(d[94]),"+f"(d[95]),"+f"(d[96]),"+f"(d[97]),"+f"(d[98]),"+f"(d[99]),"+f"(d[100]),"+f"(d[101]),"+f"(d[102]),"+f"(d[103]),"+f"(d[104]),"+f"(d[105]),"+f"(d[106]),"+f"(d[107]),"+f"(d[108]),"+f"(d[109]),"+f"(d[110]),"+f"(d[111])
  : "r"(a[0]), "r"(a[1]), "r"(a[2]), "r"(a[3]), "l"(db), "r"(sc));
}
template<> __device__ __forceinline__ void wgmma_rs<240>(float* d, const uint32_t* a, uint64_t db, int sc) {
  asm volatile("{.reg .pred p; setp.ne.b32 p, %125, 0;\n"
  "wgmma.mma_async.sync.aligned.m64n240k16.f32.bf16.bf16 {%0,%1,%2,%3,%4,%5,%6,%7,%8,%9,%10,%11,%12,%13,%14,%15,%16,%17,%18,%19,%20,%21,%22,%23,%24,%25,%26,%27,%28,%29,%30,%31,%32,%33,%34,%35,%36,%37,%38,%39,%40,%41,%42,%43,%44,%45,%46,%47,%48,%49,%50,%51,%52,%53,%54,%55,%56,%57,%58,%59,%60,%61,%62,%63,%64,%65,%66,%67,%68,%69,%70,%71,%72,%73,%74,%75,%76,%77,%78,%79,%80,%81,%82,%83,%84,%85,%86,%87,%88,%89,%90,%91,%92,%93,%94,%95,%96,%97,%98,%99,%100,%101,%102,%103,%104,%105,%106,%107,%108,%109,%110,%111,%112,%113,%114,%115,%116,%117,%118,%119}, {%120,%121,%122,%123}, %124, p, 1, 1, 0;}\n"
  : "+f"(d[0]),"+f"(d[1]),"+f"(d[2]),"+f"(d[3]),"+f"(d[4]),"+f"(d[5]),"+f"(d[6]),"+f"(d[7]),"+f"(d[8]),"+f"(d[9]),"+f"(d[10]),"+f"(d[11]),"+f"(d[12]),"+f"(d[13]),"+f"(d[14]),"+f"(d[15]),"+f"(d[16]),"+f"(d[17]),"+f"(d[18]),"+f"(d[19]),"+f"(d[20]),"+f"(d[21]),"+f"(d[22]),"+f"(d[23]),"+f"(d[24]),"+f"(d[25]),"+f"(d[26]),"+f"(d[27]),"+f"(d[28]),"+f"(d[29]),"+f"(d[30]),"+f"(d[31]),"+f"(d[32]),"+f"(d[33]),"+f"(d[34]),"+f"(d[35]),"+f"(d[36]),"+f"(d[37]),"+f"(d[38]),"+f"(d[39]),"+f"(d[40]),"+f"(d[41]),"+f"(d[42]),"+f"(d[43]),"+f"(d[44]),"+f"(d[45]),"+f"(d[46]),"+f"(d[47]),"+f"(d[48]),"+f"(d[49]),"+f"(d[50]),"+f"(d[51]),"+f"(d[52]),"+f"(d[53]),"+f"(d[54]),"+f"(d[55]),"+f"(d[56]),"+f"(d[57]),"+f"(d[58]),"+f"(d[59]),"+f"(d[60]),"+f"(d[61]),"+f"(d[62]),"+f"(d[63]),"+f"(d[64]),"+f"(d[65]),"+f"(d[66]),"+f"(d[67]),"+f"(d[68]),"+f"(d[69]),"+f"(d[70]),"+f"(d[71]),"+f"(d[72]),"+f"(d[73]),"+f"(d[74]),"+f"(d[75]),"+f"(d[76]),"+f"(d[77]),"+f"(d[78]),"+f"(d[79]),"+f"(d[80]),"+f"(d[81]),"+f"(d[82]),"+f"(d[83]),"+f"(d[84]),"+f"(d[85]),"+f"(d[86]),"+f"(d[87]),"+f"(d[88]),"+f"(d[89]),"+f"(d[90]),"+f"(d[91]),"+f"(d[92]),"+f"(d[93]),"+f"(d[94]),"+f"(d[95]),"+f"(d[96]),"+f"(d[97]),"+f"(d[98]),"+f"(d[99]),"+f"(d[100]),"+f"(d[101]),"+f"(d[102]),"+f"(d[103]),"+f"(d[104]),"+f"(d[105]),"+f"(d[106]),"+f"(d[107]),"+f"(d[108]),"+f"(d[109]),"+f"(d[110]),"+f"(d[111]),"+f"(d[112]),"+f"(d[113]),"+f"(d[114]),"+f"(d[115]),"+f"(d[116]),"+f"(d[117]),"+f"(d[118]),"+f"(d[119])
  : "r"(a[0]), "r"(a[1]), "r"(a[2]), "r"(a[3]), "l"(db), "r"(sc));
}
template<> __device__ __forceinline__ void wgmma_rs<256>(float* d, const uint32_t* a, uint64_t db, int sc) {
  asm volatile("{.reg .pred p; setp.ne.b32 p, %133, 0;\n"
  "wgmma.mma_async.sync.aligned.m64n256k16.f32.bf16.bf16 {%0,%1,%2,%3,%4,%5,%6,%7,%8,%9,%10,%11,%12,%13,%14,%15,%16,%17,%18,%19,%20,%21,%22,%23,%24,%25,%26,%27,%28,%29,%30,%31,%32,%33,%34,%35,%36,%37,%38,%39,%40,%41,%42,%43,%44,%45,%46,%47,%48,%49,%50,%51,%52,%53,%54,%55,%56,%57,%58,%59,%60,%61,%62,%63,%64,%65,%66,%67,%68,%69,%70,%71,%72,%73,%74,%75,%76,%77,%78,%79,%80,%81,%82,%83,%84,%85,%86,%87,%88,%89,%90,%91,%92,%93,%94,%95,%96,%97,%98,%99,%100,%101,%102,%103,%104,%105,%106,%107,%108,%109,%110,%111,%112,%113,%114,%115,%116,%117,%118,%119,%120,%121,%122,%123,%124,%125,%126,%127}, {%128,%129,%130,%131}, %132, p, 1, 1, 0;}\n"
  : "+f"(d[0]),"+f"(d[1]),"+f"(d[2]),"+f"(d[3]),"+f"(d[4]),"+f"(d[5]),"+f"(d[6]),"+f"(d[7]),"+f"(d[8]),"+f"(d[9]),"+f"(d[10]),"+f"(d[11]),"+f"(d[12]),"+f"(d[13]),"+f"(d[14]),"+f"(d[15]),"+f"(d[16]),"+f"(d[17]),"+f"(d[18]),"+f"(d[19]),"+f"(d[20]),"+f"(d[21]),"+f"(d[22]),"+f"(d[23]),"+f"(d[24]),"+f"(d[25]),"+f"(d[26]),"+f"(d[27]),"+f"(d[28]),"+f"(d[29]),"+f"(d[30]),"+f"(d[31]),"+f"(d[32]),"+f"(d[33]),"+f"(d[34]),"+f"(d[35]),"+f"(d[36]),"+f"(d[37]),"+f"(d[38]),"+f"(d[39]),"+f"(d[40]),"+f"(d[41]),"+f"(d[42]),"+f"(d[43]),"+f"(d[44]),"+f"(d[45]),"+f"(d[46]),"+f"(d[47]),"+f"(d[48]),"+f"(d[49]),"+f"(d[50]),"+f"(d[51]),"+f"(d[52]),"+f"(d[53]),"+f"(d[54]),"+f"(d[55]),"+f"(d[56]),"+f"(d[57]),"+f"(d[58]),"+f"(d[59]),"+f"(d[60]),"+f"(d[61]),"+f"(d[62]),"+f"(d[63]),"+f"(d[64]),"+f"(d[65]),"+f"(d[66]),"+f"(d[67]),"+f"(d[68]),"+f"(d[69]),"+f"(d[70]),"+f"(d[71]),"+f"(d[72]),"+f"(d[73]),"+f"(d[74]),"+f"(d[75]),"+f"(d[76]),"+f"(d[77]),"+f"(d[78]),"+f"(d[79]),"+f"(d[80]),"+f"(d[81]),"+f"(d[82]),"+f"(d[83]),"+f"(d[84]),"+f"(d[85]),"+f"(d[86]),"+f"(d[87]),"+f"(d[88]),"+f"(d[89]),"+f"(d[90]),"+f"(d[91]),"+f"(d[92]),"+f"(d[93]),"+f"(d[94]),"+f"(d[95]),"+f"(d[96]),"+f"(d[97]),"+f"(d[98]),"+f"(d[99]),"+f"(d[100]),"+f"(d[101]),"+f"(d[102]),"+f"(d[103]),"+f"(d[104]),"+f"(d[105]),"+f"(d[106]),"+f"(d[107]),"+f"(d[108]),"+f"(d[109]),"+f"(d[110]),"+f"(d[111]),"+f"(d[112]),"+f"(d[113]),"+f"(d[114]),"+f"(d[115]),"+f"(d[116]),"+f"(d[117]),"+f"(d[118]),"+f"(d[119]),"+f"(d[120]),"+f"(d[121]),"+f"(d[122]),"+f"(d[123]),"+f"(d[124]),"+f"(d[125]),"+f"(d[126]),"+f"(d[127])
  : "r"(a[0]), "r"(a[1]), "r"(a[2]), "r"(a[3]), "l"(db), "r"(sc));
}
template<> __device__ __forceinline__ void wgmma_ss<128>(float* d, uint64_t da, uint64_t db, int sc) {
  asm volatile("{.reg .pred p; setp.ne.b32 p, %66, 0;\n"
  "wgmma.mma_async.sync.aligned.m64n128k16.f32.bf16.bf16 {%0,%1,%2,%3,%4,%5,%6,%7,%8,%9,%10,%11,%12,%13,%14,%15,%16,%17,%18,%19,%20,%21,%22,%23,%24,%25,%26,%27,%28,%29,%30,%31,%32,%33,%34,%35,%36,%37,%38,%39,%40,%41,%42,%43,%44,%45,%46,%47,%48,%49,%50,%51,%52,%53,%54,%55,%56,%57,%58,%59,%60,%61,%62,%63}, %64, %65, p, 1, 1, 0, 1;}\n"
  : "+f"(d[0]),"+f"(d[1]),"+f"(d[2]),"+f"(d[3]),"+f"(d[4]),"+f"(d[5]),"+f"(d[6]),"+f"(d[7]),"+f"(d[8]),"+f"(d[9]),"+f"(d[10]),"+f"(d[11]),"+f"(d[12]),"+f"(d[13]),"+f"(d[14]),"+f"(d[15]),"+f"(d[16]),"+f"(d[17]),"+f"(d[18]),"+f"(d[19]),"+f"(d[20]),"+f"(d[21]),"+f"(d[22]),"+f"(d[23]),"+f"(d[24]),"+f"(d[25]),"+f"(d[26]),"+f"(d[27]),"+f"(d[28]),"+f"(d[29]),"+f"(d[30]),"+f"(d[31]),"+f"(d[32]),"+f"(d[33]),"+f"(d[34]),"+f"(d[35]),"+f"(d[36]),"+f"(d[37]),"+f"(d[38]),"+f"(d[39]),"+f"(d[40]),"+f"(d[41]),"+f"(d[42]),"+f"(d[43]),"+f"(d[44]),"+f"(d[45]),"+f"(d[46]),"+f"(d[47]),"+f"(d[48]),"+f"(d[49]),"+f"(d[50]),"+f"(d[51]),"+f"(d[52]),"+f"(d[53]),"+f"(d[54]),"+f"(d[55]),"+f"(d[56]),"+f"(d[57]),"+f"(d[58]),"+f"(d[59]),"+f"(d[60]),"+f"(d[61]),"+f"(d[62]),"+f"(d[63])
  : "l"(da), "l"(db), "r"(sc));
}
template<> __device__ __forceinline__ void wgmma_ss<192>(float* d, uint64_t da, uint64_t db, int sc) {
  asm volatile("{.reg .pred p; setp.ne.b32 p, %98, 0;\n"
  "wgmma.mma_async.sync.aligned.m64n192k16.f32.bf16.bf16 {%0,%1,%2,%3,%4,%5,%6,%7,%8,%9,%10,%11,%12,%13,%14,%15,%16,%17,%18,%19,%20,%21,%22,%23,%24,%25,%26,%27,%28,%29,%30,%31,%32,%33,%34,%35,%36,%37,%38,%39,%40,%41,%42,%43,%44,%45,%46,%47,%48,%49,%50,%51,%52,%53,%54,%55,%56,%57,%58,%59,%60,%61,%62,%63,%64,%65,%66,%67,%68,%69,%70,%71,%72,%73,%74,%75,%76,%77,%78,%79,%80,%81,%82,%83,%84,%85,%86,%87,%88,%89,%90,%91,%92,%93,%94,%95}, %96, %97, p, 1, 1, 0, 1;}\n"
  : "+f"(d[0]),"+f"(d[1]),"+f"(d[2]),"+f"(d[3]),"+f"(d[4]),"+f"(d[5]),"+f"(d[6]),"+f"(d[7]),"+f"(d[8]),"+f"(d[9]),"+f"(d[10]),"+f"(d[11]),"+f"(d[12]),"+f"(d[13]),"+f"(d[14]),"+f"(d[15]),"+f"(d[16]),"+f"(d[17]),"+f"(d[18]),"+f"(d[19]),"+f"(d[20]),"+f"(d[21]),"+f"(d[22]),"+f"(d[23]),"+f"(d[24]),"+f"(d[25]),"+f"(d[26]),"+f"(d[27]),"+f"(d[28]),"+f"(d[29]),"+f"(d[30]),"+f"(d[31]),"+f"(d[32]),"+f"(d[33]),"+f"(d[34]),"+f"(d[35]),"+f"(d[36]),"+f"(d[37]),"+f"(d[38]),"+f"(d[39]),"+f"(d[40]),"+f"(d[41]),"+f"(d[42]),"+f"(d[43]),"+f"(d[44]),"+f"(d[45]),"+f"(d[46]),"+f"(d[47]),"+f"(d[48]),"+f"(d[49]),"+f"(d[50]),"+f"(d[51]),"+f"(d[52]),"+f"(d[53]),"+f"(d[54]),"+f"(d[55]),"+f"(d[56]),"+f"(d[57]),"+f"(d[58]),"+f"(d[59]),"+f"(d[60]),"+f"(d[61]),"+f"(d[62]),"+f"(d[63]),"+f"(d[64]),"+f"(d[65]),"+f"(d[66]),"+f"(d[67]),"+f"(d[68]),"+f"(d[69]),"+f"(d[70]),"+f"(d[71]),"+f"(d[72]),"+f"(d[73]),"+f"(d[74]),"+f"(d[75]),"+f"(d[76]),"+f"(d[77]),"+f"(d[78]),"+f"(d[79]),"+f"(d[80]),"+f"(d[81]),"+f"(d[82]),"+f"(d[83]),"+f"(d[84]),"+f"(d[85]),"+f"(d[86]),"+f"(d[87]),"+f"(d[88]),"+f"(d[89]),"+f"(d[90]),"+f"(d[91]),"+f"(d[92]),"+f"(d[93]),"+f"(d[94]),"+f"(d[95])
  : "l"(da), "l"(db), "r"(sc));
}
template<> __device__ __forceinline__ void wgmma_ss<256>(float* d, uint64_t da, uint64_t db, int sc) {
  asm volatile("{.reg .pred p; setp.ne.b32 p, %130, 0;\n"
  "wgmma.mma_async.sync.aligned.m64n256k16.f32.bf16.bf16 {%0,%1,%2,%3,%4,%5,%6,%7,%8,%9,%10,%11,%12,%13,%14,%15,%16,%17,%18,%19,%20,%21,%22,%23,%24,%25,%26,%27,%28,%29,%30,%31,%32,%33,%34,%35,%36,%37,%38,%39,%40,%41,%42,%43,%44,%45,%46,%47,%48,%49,%50,%51,%52,%53,%54,%55,%56,%57,%58,%59,%60,%61,%62,%63,%64,%65,%66,%67,%68,%69,%70,%71,%72,%73,%74,%75,%76,%77,%78,%79,%80,%81,%82,%83,%84,%85,%86,%87,%88,%89,%90,%91,%92,%93,%94,%95,%96,%97,%98,%99,%100,%101,%102,%103,%104,%105,%106,%107,%108,%109,%110,%111,%112,%113,%114,%115,%116,%117,%118,%119,%120,%121,%122,%123,%124,%125,%126,%127}, %128, %129, p, 1, 1, 0, 1;}\n"
  : "+f"(d[0]),"+f"(d[1]),"+f"(d[2]),"+f"(d[3]),"+f"(d[4]),"+f"(d[5]),"+f"(d[6]),"+f"(d[7]),"+f"(d[8]),"+f"(d[9]),"+f"(d[10]),"+f"(d[11]),"+f"(d[12]),"+f"(d[13]),"+f"(d[14]),"+f"(d[15]),"+f"(d[16]),"+f"(d[17]),"+f"(d[18]),"+f"(d[19]),"+f"(d[20]),"+f"(d[21]),"+f"(d[22]),"+f"(d[23]),"+f"(d[24]),"+f"(d[25]),"+f"(d[26]),"+f"(d[27]),"+f"(d[28]),"+f"(d[29]),"+f"(d[30]),"+f"(d[31]),"+f"(d[32]),"+f"(d[33]),"+f"(d[34]),"+f"(d[35]),"+f"(d[36]),"+f"(d[37]),"+f"(d[38]),"+f"(d[39]),"+f"(d[40]),"+f"(d[41]),"+f"(d[42]),"+f"(d[43]),"+f"(d[44]),"+f"(d[45]),"+f"(d[46]),"+f"(d[47]),"+f"(d[48]),"+f"(d[49]),"+f"(d[50]),"+f"(d[51]),"+f"(d[52]),"+f"(d[53]),"+f"(d[54]),"+f"(d[55]),"+f"(d[56]),"+f"(d[57]),"+f"(d[58]),"+f"(d[59]),"+f"(d[60]),"+f"(d[61]),"+f"(d[62]),"+f"(d[63]),"+f"(d[64]),"+f"(d[65]),"+f"(d[66]),"+f"(d[67]),"+f"(d[68]),"+f"(d[69]),"+f"(d[70]),"+f"(d[71]),"+f"(d[72]),"+f"(d[73]),"+f"(d[74]),"+f"(d[75]),"+f"(d[76]),"+f"(d[77]),"+f"(d[78]),"+f"(d[79]),"+f"(d[80]),"+f"(d[81]),"+f"(d[82]),"+f"(d[83]),"+f"(d[84]),"+f"(d[85]),"+f"(d[86]),"+f"(d[87]),"+f"(d[88]),"+f"(d[89]),"+f"(d[90]),"+f"(d[91]),"+f"(d[92]),"+f"(d[93]),"+f"(d[94]),"+f"(d[95]),"+f"(d[96]),"+f"(d[97]),"+f"(d[98]),"+f"(d[99]),"+f"(d[100]),"+f"(d[101]),"+f"(d[102]),"+f"(d[103]),"+f"(d[104]),"+f"(d[105]),"+f"(d[106]),"+f"(d[107]),"+f"(d[108]),"+f"(d[109]),"+f"(d[110]),"+f"(d[111]),"+f"(d[112]),"+f"(d[113]),"+f"(d[114]),"+f"(d[115]),"+f"(d[116]),"+f"(d[117]),"+f"(d[118]),"+f"(d[119]),"+f"(d[120]),"+f"(d[121]),"+f"(d[122]),"+f"(d[123]),"+f"(d[124]),"+f"(d[125]),"+f"(d[126]),"+f"(d[127])
  : "l"(da), "l"(db), "r"(sc));
}

__device__ __forceinline__ void wg_fence() { asm volatile("wgmma.fence.sync.aligned;" ::: "memory"); }
__device__ __forceinline__ void wg_commit() { asm volatile("wgmma.commit_group.sync.aligned;" ::: "memory"); }
template <int N> __device__ __forceinline__ void wg_wait() { asm volatile("wgmma.wait_group.sync.aligned %0;" ::"n"(N) : "memory"); }
__device__ __forceinline__ uint64_t mkdesc(uint32_t addr, uint32_t lbo, uint32_t sbo, uint32_t swz) {
  return (uint64_t)((addr & 0x3FFFF) >> 4) | ((uint64_t)(lbo >> 4) << 16) | ((uint64_t)(sbo >> 4) << 32) | ((uint64_t)swz << 62);
}
__device__ __forceinline__ void mbar_init(uint32_t a, uint32_t c) { asm volatile("mbarrier.init.shared.b64 [%0], %1;" ::"r"(a), "r"(c) : "memory"); }
__device__ __forceinline__ void mbar_expect_tx(uint32_t a, uint32_t b) { asm volatile("mbarrier.arrive.expect_tx.shared.b64 _, [%0], %1;" ::"r"(a), "r"(b) : "memory"); }
__device__ __forceinline__ void mbar_arrive(uint32_t a) { asm volatile("mbarrier.arrive.shared.b64 _, [%0];" ::"r"(a) : "memory"); }
__device__ __forceinline__ void mbar_arrive_c(uint32_t a, uint32_t n) { asm volatile("mbarrier.arrive.shared::cluster.b64 _, [%0], %1;" ::"r"(a), "r"(n) : "memory"); }
__device__ __forceinline__ void mbar_wait(uint32_t a, uint32_t parity) {
  asm volatile("{.reg .pred p, q; .reg .u32 n; mov.u32 n, 0;\n"
               "W: mbarrier.try_wait.parity.shared.b64 p, [%0], %1;\n"
               "add.u32 n, n, 1; setp.eq.u32 q, n, 0x100000; @q trap; @!p bra.uni W;}" ::"r"(a), "r"(parity) : "memory");
}
__device__ __forceinline__ bool mbar_test(uint32_t a, uint32_t parity) {
  uint32_t done;
  asm volatile("{.reg .pred p; mbarrier.test_wait.parity.shared.b64 p, [%1], %2; selp.u32 %0,1,0,p;}" : "=r"(done) : "r"(a), "r"(parity) : "memory");
  return done != 0;
}
__device__ __forceinline__ uint32_t mapa(uint32_t a, uint32_t rank) { uint32_t r; asm("mapa.shared::cluster.u32 %0, %1, %2;" : "=r"(r) : "r"(a), "r"(rank)); return r; }
__device__ __forceinline__ void tma2d(uint32_t dst, const CUtensorMap* m, uint32_t bar, int c0, int c1) {
  asm volatile("cp.async.bulk.tensor.2d.shared::cluster.global.mbarrier::complete_tx::bytes [%0], [%1, {%3,%4}], [%2];"
               ::"r"(dst), "l"(m), "r"(bar), "r"(c0), "r"(c1) : "memory");
}
__device__ __forceinline__ void tma2d_mc(uint32_t dst, const CUtensorMap* m, uint32_t bar, int c0, int c1) {
  asm volatile("cp.async.bulk.tensor.2d.shared::cluster.global.mbarrier::complete_tx::bytes.multicast::cluster [%0], [%1, {%3,%4}], [%2], %5;"
               ::"r"(dst), "l"(m), "r"(bar), "r"(c0), "r"(c1), "h"((uint16_t)3) : "memory");
}
__device__ __forceinline__ void tma3d(uint32_t dst, const CUtensorMap* m, uint32_t bar, int c0, int c1, int c2) {
  asm volatile("cp.async.bulk.tensor.3d.shared::cluster.global.mbarrier::complete_tx::bytes [%0], [%1, {%3,%4,%5}], [%2];"
               ::"r"(dst), "l"(m), "r"(bar), "r"(c0), "r"(c1), "r"(c2) : "memory");
}
__device__ __forceinline__ void tma4d(uint32_t dst, const CUtensorMap* m, uint32_t bar, int c1, int c2, int c3) {
  asm volatile("cp.async.bulk.tensor.4d.shared::cluster.global.mbarrier::complete_tx::bytes [%0], [%1, {%6,%3,%4,%5}], [%2];"
               ::"r"(dst), "l"(m), "r"(bar), "r"(c1), "r"(c2), "r"(c3), "r"(0) : "memory");
}
__device__ __forceinline__ bool elect() {
  uint32_t p;
  asm volatile("{.reg .pred q; elect.sync _|q, 0xffffffff; selp.u32 %0, 1, 0, q;}" : "=r"(p));
  return p != 0;
}
__device__ __forceinline__ void tma3d_mc(uint32_t dst, const CUtensorMap* m, uint32_t bar, int c0, int c1, int c2) {
  asm volatile("cp.async.bulk.tensor.3d.shared::cluster.global.mbarrier::complete_tx::bytes.multicast::cluster [%0], [%1, {%3,%4,%5}], [%2], %6;"
               ::"r"(dst), "l"(m), "r"(bar), "r"(c0), "r"(c1), "r"(c2), "h"((uint16_t)3) : "memory");
}
__device__ __forceinline__ void tma_store(const CUtensorMap* m, uint32_t src, int c0, int c1) {
  asm volatile("cp.async.bulk.tensor.2d.global.shared::cta.bulk_group [%0, {%2,%3}], [%1];" ::"l"(m), "r"(src), "r"(c0), "r"(c1) : "memory");
}
__device__ __forceinline__ void bulk_commit() { asm volatile("cp.async.bulk.commit_group;" ::: "memory"); }
__device__ __forceinline__ void bulk_wait_read() { asm volatile("cp.async.bulk.wait_group.read 0;" ::: "memory"); }
__device__ __forceinline__ void bulk_wait() { asm volatile("cp.async.bulk.wait_group 0;" ::: "memory"); }
__device__ __forceinline__ void bulk_g2s(uint32_t dst, const void* src, uint32_t bytes, uint32_t bar) {
  asm volatile("cp.async.bulk.shared::cluster.global.mbarrier::complete_tx::bytes [%0], [%1], %2, [%3];"
               ::"r"(dst), "l"(src), "r"(bytes), "r"(bar) : "memory");
}
__device__ __forceinline__ void prefetch_l2(const void* src, uint32_t bytes) {
  asm volatile("cp.async.bulk.prefetch.L2.global [%0], %1;" ::"l"(src), "r"(bytes) : "memory");
}
__device__ __forceinline__ void prefetch_tmap(const CUtensorMap* m) { asm volatile("prefetch.tensormap [%0];" ::"l"(m) : "memory"); }
__device__ __forceinline__ void fence_async_smem() { asm volatile("fence.proxy.async.shared::cta;" ::: "memory"); }
__device__ __forceinline__ void fence_async_global() { asm volatile("fence.proxy.async.global;" ::: "memory"); }
__device__ __forceinline__ void acquire_async() { asm volatile("fence.acquire.gpu; fence.proxy.async.global;" ::: "memory"); }
__device__ __forceinline__ void bar_sync(int id, int n) { asm volatile("bar.sync %0, %1;" ::"r"(id), "r"(n) : "memory"); }
__device__ __forceinline__ void cluster_wait() { asm volatile("barrier.cluster.wait.aligned;" ::: "memory"); }
__device__ __forceinline__ uint32_t lds32(uint32_t a) { uint32_t v; asm volatile("ld.volatile.shared.b32 %0,[%1];" : "=r"(v) : "r"(a)); return v; }
__device__ __forceinline__ uint2 lds64(uint32_t a) { uint2 v; asm volatile("ld.volatile.shared.v2.b32 {%0,%1},[%2];" : "=r"(v.x), "=r"(v.y) : "r"(a) : "memory"); return v; }
__device__ __forceinline__ uint4 lds128(uint32_t a) { uint4 v; asm volatile("ld.shared.v4.b32 {%0,%1,%2,%3},[%4];" : "=r"(v.x), "=r"(v.y), "=r"(v.z), "=r"(v.w) : "r"(a) : "memory"); return v; }
__device__ __forceinline__ void sts128(uint32_t a, uint32_t x, uint32_t y, uint32_t z, uint32_t w) { asm volatile("st.shared.v4.b32 [%0],{%1,%2,%3,%4};" ::"r"(a), "r"(x), "r"(y), "r"(z), "r"(w) : "memory"); }
__device__ __forceinline__ void stsm4(uint32_t a, uint32_t x, uint32_t y, uint32_t z, uint32_t w) { asm volatile("stmatrix.sync.aligned.m8n8.x4.shared.b16 [%0],{%1,%2,%3,%4};" ::"r"(a), "r"(x), "r"(y), "r"(z), "r"(w) : "memory"); }
__device__ __forceinline__ uint32_t packbf(float lo, float hi) { uint32_t r; asm("cvt.rn.bf16x2.f32 %0, %1, %2;" : "=r"(r) : "f"(hi), "f"(lo)); return r; }
__device__ __forceinline__ uint32_t packbf_relu(float lo, float hi) { uint32_t r; asm("cvt.rn.relu.bf16x2.f32 %0, %1, %2;" : "=r"(r) : "f"(hi), "f"(lo)); return r; }
__device__ __forceinline__ uint32_t bmul2(uint32_t a, uint32_t b) { uint32_t r; asm("mul.rn.bf16x2 %0, %1, %2;" : "=r"(r) : "r"(a), "r"(b)); return r; }
__device__ __forceinline__ uint32_t bmul2v(uint32_t a) { uint32_t r; asm volatile("mul.rn.bf16x2 %0, %1, %1;" : "=r"(r) : "r"(a)); return r; }
__device__ __forceinline__ uint32_t bfma2(uint32_t a, uint32_t b, uint32_t c) { uint32_t r; asm("fma.rn.bf16x2 %0, %1, %2, %3;" : "=r"(r) : "r"(a), "r"(b), "r"(c)); return r; }
__device__ __forceinline__ uint32_t badd2(uint32_t a, uint32_t b) { uint32_t r; asm("add.rn.bf16x2 %0, %1, %2;" : "=r"(r) : "r"(a), "r"(b)); return r; }
__device__ __forceinline__ uint32_t bsub2(uint32_t a, uint32_t b) { uint32_t r; asm("sub.rn.bf16x2 %0, %1, %2;" : "=r"(r) : "r"(a), "r"(b)); return r; }
__device__ __forceinline__ float bflo(uint32_t v) { return __uint_as_float(v << 16); }
__device__ __forceinline__ float bfhi(uint32_t v) { return __uint_as_float(v & 0xffff0000u); }
__device__ __forceinline__ uint32_t ldg_relaxed(const uint32_t* p) { uint32_t v; asm volatile("ld.relaxed.gpu.global.b32 %0,[%1];" : "=r"(v) : "l"(p) : "memory"); return v; }
__device__ __forceinline__ uint4 ldg_b128(const void* p) {
  uint4 v;
  asm volatile("{.reg .b128 r; .reg .b64 a, b; ld.relaxed.gpu.global.b128 r, [%4]; mov.b128 {a, b}, r; mov.b64 {%0,%1}, a; mov.b64 {%2,%3}, b;}"
               : "=r"(v.x), "=r"(v.y), "=r"(v.z), "=r"(v.w) : "l"(p) : "memory");
  return v;
}
__device__ __forceinline__ void stg_b128(void* p, uint32_t x, uint32_t y, uint32_t z, uint32_t w) {
  asm volatile("{.reg .b128 r; .reg .b64 a, b; mov.b64 a, {%1,%2}; mov.b64 b, {%3,%4}; mov.b128 r, {a, b}; st.relaxed.gpu.global.b128 [%0], r;}"
               ::"l"(p), "r"(x), "r"(y), "r"(z), "r"(w) : "memory");
}
__device__ __forceinline__ void signal(uint32_t* cnt) { asm volatile("red.release.gpu.global.add.u32 [%0], 1;" ::"l"(cnt) : "memory"); }
__device__ __forceinline__ void wait_count(const uint32_t* cnt, uint32_t target) {
  int it = 0;
  while (true) {
    uint32_t v;
    asm volatile("ld.acquire.gpu.global.b32 %0,[%1];" : "=r"(v) : "l"(cnt) : "memory");
    if ((int)(v - target) >= 0) break;
    __nanosleep(32);
    if (++it > (1 << 21)) __trap();
  }
}

__device__ __forceinline__ void wait_count_warp(const uint32_t* cnt, uint32_t target) {
  asm volatile("{.reg .pred p, q; .reg .u32 n, v; mov.u32 n, 0;\n"
               "W: ld.acquire.gpu.global.b32 v, [%0]; sub.u32 v, v, %1; setp.lt.s32 p, v, 0;\n"
               "@p nanosleep.u32 " STR(POLL_SLEEP) "; add.u32 n, n, 1; setp.eq.u32 q, n, 0x200000; @q trap; @p bra.uni W;}" ::"l"(cnt), "r"(target) : "memory");
}

__device__ __forceinline__ uint32_t laneid() { uint32_t l; asm volatile("mov.u32 %0, %laneid;" : "=r"(l)); return l; }
template <int LO, int HI> __device__ __forceinline__ void rename(float* d) {
#pragma unroll
  for (int i = LO; i < HI; i++) { float e; asm volatile("mov.b32 %0, %1;" : "=f"(e) : "f"(d[i])); d[i] = e; }
}
template <int M> __device__ __forceinline__ void drain4(const float* d, uint32_t ya, uint32_t yd, bool over, uint32_t ybar, bool lane0) {
  if (M >= 16 || (M == 12 && over)) ya += yd;
  uint32_t r[4];
#pragma unroll
  for (int q = 0; q < 4; q++) {
    const int mu = M + q;
    float v0 = d[4 * mu], v1 = d[4 * mu + 1];
    if (mu > 0) { v0 += d[4 * mu - 2]; v1 += d[4 * mu - 1]; }
    r[q] = packbf(v0, v1);
  }
  asm volatile("stmatrix.sync.aligned.m8n8.x4.trans.shared.b16 [%0],{%1,%2,%3,%4};" ::"r"(ya + M * 128), "r"(r[0]), "r"(r[1]), "r"(r[2]), "r"(r[3]) : "memory");
  if constexpr ((M & 15) == 12) {
    __syncwarp();
    if (lane0) mbar_arrive(ybar + (M >> 4) * 8);
  }
}
struct ZTask {
  uint32_t ybar, yb, yw, l;
  template <int LO = 0, int HI = 8> __device__ __forceinline__ void load(uint2* p) const {
    const uint32_t ya = yb + l * 8;
    if (LO == 0) mbar_wait(ybar, 0);
#pragma unroll
    for (int i = LO; i < HI; i++) p[i] = lds64(ya + i * yw);
  }
  __device__ __forceinline__ void store(const uint2* p, bool par, bool lane0) const {
    const uint32_t za = yb + l * 16 + (l >> 4) * (yw - 256);
    const uint32_t a0 = badd2(badd2(p[0].x, p[1].x), badd2(p[2].x, p[3].x)), a1 = badd2(badd2(p[0].y, p[1].y), badd2(p[2].y, p[3].y));
    const uint32_t b0 = badd2(badd2(p[4].x, p[5].x), badd2(p[6].x, p[7].x)), b1 = badd2(badd2(p[4].y, p[5].y), badd2(p[6].y, p[7].y));
    __syncwarp();
    const uint32_t z0 = __byte_perm(a0, b0, 0x5410);
    sts128(za, par ? z0 | 1u : z0 & ~1u, __byte_perm(a0, b0, 0x7632), __byte_perm(a1, b1, 0x5410), __byte_perm(a1, b1, 0x7632));
    if (ZFENCE) fence_async_smem();
    __syncwarp();
    if (lane0) mbar_arrive(ybar + 8 * (B_ZFULL - B_YFULL));
  }
};
__device__ __forceinline__ void lda(uint32_t* a, uint32_t ua) { a[0] = lds32(ua); a[1] = lds32(ua + 128); a[2] = lds32(ua - 16); a[3] = lds32(ua + 112); }
struct Round {
  uint32_t ua, ua_next, ya, yd, zero_a, bar, ybar, kbar_next, ybuf_free;
  uint64_t db;
  ZTask zprev, zcur;
  bool lane0, zero, par, over;
};
template <int P, int RD> struct Pass {
  static __device__ __forceinline__ void run(float* d, uint32_t (*a)[4], uint2* zp, const Round& R) {
    constexpr bool FIRST = RD == 0;
    if constexpr (P > 0) rename<8 * (P - 1), 128>(d);
    wg_fence();
    wgmma_rs<256 - 16 * P>(d + 8 * P, a[P & 1], R.db, P != 0);
    wg_commit();
    if constexpr (P < 15) {
      if constexpr (FIRST && (P & 1)) mbar_wait(R.bar + 8 * (B_UFULL + (P + 1) / 2), 0);
      lda(a[(P + 1) & 1], R.ua + (P + 1) * 256);
    } else {
      if constexpr (FIRST) mbar_wait(R.bar + 8 * B_UREST, 0);
      if constexpr (RD < 3) lda(a[0], R.ua_next);
    }
    if constexpr (P == YP) {
      if constexpr (RD >= 1) mbar_wait(R.ybuf_free, 0);
      if (R.zero) sts128(R.zero_a, 0, 0, 0, 0);
    }
    if constexpr (P >= 3 && (P & 1)) drain4<2 * P - 6>(d, R.ya, R.yd, R.over, R.ybar, R.lane0);
    if constexpr (!FIRST && P < 8 / ZNA) R.zprev.template load<P * ZNA, (P + 1) * ZNA>(zp);
    if constexpr (!FIRST && P == 8 / ZNA) R.zprev.store(zp, R.par, R.lane0);
    if constexpr (P >= 10 && P < 14) R.zcur.template load<2 * (P - 10), 2 * (P - 9)>(zp);
    if constexpr (P == 14) R.zcur.store(zp, R.par, R.lane0);
    if constexpr (P == (FIRST ? 15 : KP)) mbar_wait(R.kbar_next, 0);
    wg_wait<0>();
    if constexpr (P < 15) Pass<P + 1, RD>::run(d, a, zp, R);
    else { rename<120, 128>(d); drain4<28>(d, R.ya, R.yd, R.over, R.ybar, R.lane0); }
  }
};

__device__ __forceinline__ uint32_t off_T(int r) { return r == 0 ? OFF_T0 : r == 1 ? OFF_T1 : r == 2 ? OFF_T2 : OFF_T3; }
__device__ __forceinline__ uint32_t off_Y(int r) { return r == 1 ? OFF_KVA : r == 2 ? OFF_KVB : OFF_X; }
__device__ __forceinline__ uint32_t off_kv(int st) {
  const int sl = st < 5 ? st : st - 5;
  return sl == 0 ? 0 : sl < 3 ? OFF_KVA + (sl - 1) * KV_SLOT : OFF_KVB + (sl - 3) * KV_SLOT;
}
__device__ __forceinline__ ZTask ztask(uint32_t sb, int r, int half, int warp, int lane) {
  const uint32_t yb = sb + off_Y(r) + half * YH1 + warp * 256;
  return ZTask{sb + OFF_BAR + 8 * (B_YFULL + 2 * r + half), yb, (uint32_t)(half ? YW1 : YW0), (uint32_t)lane};
}
template <int RD>
__device__ __forceinline__ void conv_round(uint32_t* a0, uint32_t sb, int r, int warp, int lane, uint32_t uoff, bool par) {
  float d[128];
  uint32_t a[2][4] = {{a0[0], a0[1], a0[2], a0[3]}, {0, 0, 0, 0}};
  uint2 zp[8];
  const int wg = warp >> 2, w = warp & 3, rn = r < 3 ? r + 1 : 3;
  const uint32_t bar = sb + OFF_BAR, tb = sb + off_T(r), yb = sb + off_Y(r) + warp * YW0;
  const Round R{tb + uoff, sb + off_T(rn) + uoff, yb + (2 * w + lane) * 16, (uint32_t)(YH1 - YW0 + warp * (YW1 - YW0)), yb + lane * 16, bar, bar + 8 * (B_YFULL + 2 * r),
                bar + 8 * (B_KFULL + 2 * rn + wg), bar + 8 * (r == 3 ? B_ZDONE : r == 2 ? B_XDONE : B_UREST + 1), mkdesc(tb + 2 * UT_SIZE + wg * KT_SIZE, 16, 128, 0),
                ztask(sb, r - 1, 1, warp, lane), ztask(sb, r, 0, warp, lane), lane == 0, lane < 2 * w, par, lane + 2 * w >= 32};
  TSM(r);
  Pass<0, RD>::run(d, a, zp, R);
#pragma unroll
  for (int i = 0; i < 4; i++) a0[i] = a[0][i];
}
__device__ __forceinline__ uint32_t off_hb(int r) { return r == 0 ? 0 : r == 1 ? OFF_HB : OFF_X + (r - 2) * 2 * HB_WARP; }
__device__ __forceinline__ uint32_t off_act(int tile, int wg, int b) {
  return b < 2 ? OFF_X + wg * 16384 + b * 8192 : tile == 0 ? (b - 2 * wg) * 49152 + 40960 : 180224 + wg * 8192;
}

struct Ids { int rank, c, m, j; };
__device__ __forceinline__ Ids ids() {
  int b;
  b = blockIdx.x;
  const int rank = b & 1, cl = b >> 1;
  const int lp = cl < 4 ? 60 + cl : cl < 36 ? 4 * ((cl - 4) & 7) + ((cl - 4) >> 3) : 32 + 4 * ((cl - 36) % 7) + (cl - 36) / 7;
  const int grp = lp >> 2, pi = grp < 8 ? 2 * grp : 2 * (grp - 8) + 1;
  const int hi = pi >> 2, lo = (hi & 1) ? 3 - (pi & 3) : pi & 3;
  return Ids{rank, 2 * lp + rank, 4 * lo + (lp & 3), 2 * hi + rank};
}

struct Check {
  uint32_t off;
  int row;
  __device__ __forceinline__ void peek(uint32_t* t, uint32_t sa, uint32_t fb, uint32_t parity) const {
    asm volatile("{.reg .pred p; mbarrier.test_wait.parity.shared.b64 p, [%3], %4; mov.b32 %0, 0; mov.b32 %1, 0;\n"
                 "@p ld.volatile.shared.b32 %0, [%2]; @p ld.volatile.shared.b32 %1, [%2+1024];}"
                 : "=&r"(t[0]), "=&r"(t[1]) : "r"(sa + off), "r"(fb), "r"(parity) : "memory");
  }
  __device__ __forceinline__ void run(const uint32_t* t, uint32_t sa, uint32_t fb, uint32_t parity, int kb) const {
    if (__all_sync(0xffffffffu, t[0] & t[1] & 1)) return;
    mbar_wait(fb, parity);
    if (__builtin_expect(!__all_sync(0xffffffffu, lds32(sa + off) & lds32(sa + off + 1024) & 1), 0)) {
      const int lane = threadIdx.x & 31;
      const __nv_bfloat16* hp = g_h + (size_t)(row + 16 * (threadIdx.x >> 5)) * D;
      if (lane == 0) CNT(kb);
#pragma unroll 1
      for (int i = 0; i < 2; i++) {
        const __nv_bfloat16* p = hp + (size_t)(8 * i + (lane >> 2)) * D + 64 * kb + 16 * (lane & 3);
        uint4 v;
        int it = 0;
        do {
          v = ldg_b128(p);
          if (++it > (1 << 20)) __trap();
        } while (!__all_sync(0xffffffffu, v.x & 1));
        sts128(sa + off + i * 1024, v.x, v.y, v.z, v.w);
        v = ldg_b128(p + 8);
        sts128((sa + off + i * 1024) ^ 16, v.x, v.y, v.z, v.w);
      }
      fence_async_smem();
      __syncwarp();
    }
  }
};
template <int NT, bool CHECK, class Hook>
__device__ __forceinline__ void mainloop(float* acc, uint32_t sb, int wg, bool rel, int nkb, const Check& ck, uint32_t* tg, Hook hook) {
  const uint32_t bar = sb + OFF_BAR;
  const uint64_t da0 = mkdesc(sb + wg * 8192, 16, 1024, 1), db0 = mkdesc(sb + 16384, 8192, 1024, 1);
  if (CHECK) { ck.run(tg, sb, bar + 8 * B_FULL, 0, 0); ck.peek(tg, sb + 49152, bar + 8 * (B_FULL + 1), 0); }
  else mbar_wait(bar + 8 * B_FULL, 0);
#pragma unroll
  for (int kk = 0; kk < 4; kk++) {
    wg_fence();
    wgmma_ss<NT>(acc, da0 + kk * 2, db0 + kk * 128, kk != 0);
    wg_commit();
    hook(kk);
  }
#pragma unroll 1
  for (int kb = 1; kb < nkb; kb++) {
    const int s = kb & 3;
    if (kb == 16 - (NT == 256 ? LAG0 : LAG1) && wg == 0) bar_sync(9, 256);
    if (CHECK) ck.run(tg, sb + s * 49152, bar + 8 * (B_FULL + s), (kb >> 2) & 1, kb);
    else mbar_wait(bar + 8 * (B_FULL + s), (kb >> 2) & 1);
    const uint64_t da = da0 + s * 3072, db = db0 + s * 3072;
    wg_fence();
    wgmma_ss<NT>(acc, da, db, 1);
    wg_commit();
    wg_wait<1>();
    if (rel) mbar_arrive(bar + 8 * (B_EMPTY + ((kb - 1) & 3)));
    if (CHECK) ck.peek(tg, sb + ((kb + 1) & 3) * 49152, bar + 8 * (B_FULL + ((kb + 1) & 3)), ((kb + 1) >> 2) & 1);
#pragma unroll
    for (int kk = 1; kk < 4; kk++) wgmma_ss<NT>(acc, da + kk * 2, db + kk * 128, 1);
    wg_commit();
  }
}
template <int NT, class Hook>
__device__ __forceinline__ void gemm1_main(uint32_t* out, uint32_t sb, int wg, bool rel, uint32_t hs, bool t3, const Check& ck, Hook hook) {
  const uint32_t bar = sb + OFF_BAR;
  float acc[NT / 2];
  uint32_t tg[2] = {0, 0};
  mainloop<NT, NT == 256>(acc, sb, wg, rel, 15, ck, tg, hook);
  if ((NT == 256 ? LAG0 : LAG1) == 1 && wg == 0) bar_sync(9, 256);
  mbar_wait(bar + 8 * B_CSFULL, NT == 256 ? 0 : 1);
  if (NT == 256) mbar_wait(bar + 8 * B_HSFULL, 0);
  uint32_t a[4] = {lds32(hs), lds32(hs + 128), 0, 0};
  if (t3) a[0] = a[1] = 0;
  if (NT == 256) ck.run(tg, sb + 3 * 49152, bar + 8 * (B_FULL + 3), 1, 15);
  else mbar_wait(bar + 8 * (B_FULL + 3), 1);
  const uint64_t da = mkdesc(sb + 3 * 49152 + wg * 8192, 16, 1024, 1), db = mkdesc(sb + 3 * 49152 + 16384, 8192, 1024, 1);
  wg_fence();
  wgmma_rs<NT>(acc, a, mkdesc(sb + OFF_X + wg * 16384, 0, 128, 0), 1);
  wg_commit();
  wg_wait<1>();
  if (rel) mbar_arrive(bar + 8 * (B_EMPTY + 2));
#pragma unroll
  for (int kk = AUG_LAST; kk < 4; kk++) wgmma_ss<NT>(acc, da + kk * 2, db + kk * 128, 1);
  wg_commit();
  if ((NT == 256 ? LAG0 : LAG1) && wg == 1) asm volatile("bar.arrive 9, 256;" ::: "memory");
  wg_wait<0>();
  if (rel) mbar_arrive(bar + 8 * (B_EMPTY + 3));
  rename<0, NT / 2>(acc);
#pragma unroll
  for (int i = 0; i < NT / 4; i++) out[i] = packbf_relu(acc[2 * i], acc[2 * i + 1]);
}

__global__ void __cluster_dims__(2, 1, 1) __launch_bounds__(NTHREADS, 1) fused_kernel(const __grid_constant__ Params P) {
  extern __shared__ __align__(1024) unsigned char smem[];
  const uint32_t sb = (uint32_t)__cvta_generic_to_shared(smem);
  const uint32_t bar = sb + OFF_BAR;
  const int tid = threadIdx.x, warp = __shfl_sync(0xffffffffu, tid >> 5, 0), lane = tid & 31;
  const Ids id0 = ids();
  const int rank = id0.rank, c = id0.c, m = id0.m, j = id0.j;
  uint32_t* const cnt = g_cnt + 32 * m;
  if (elect()) {
    if (warp == 8) {
      TS0(0);
      prefetch_tmap(&P.tm_k); prefetch_tmap(&P.tm_v);
#pragma unroll
      for (int i = 0; i < KFIRST; i++) {
        mbar_init(bar + 8 * (B_KFULL + i), 2);
        mbar_expect_tx(bar + 8 * (B_KFULL + i), 4080);
        bulk_g2s(sb + off_T(i >> 1) + 2 * UT_SIZE + (i & 1) * KT_SIZE + 32, P.ssm_k + (size_t)(8 * c + i) * S + 8, 4080, bar + 8 * (B_KFULL + i));
      }
      mbar_init(bar + 8 * B_KVFULL, 1);
      mbar_expect_tx(bar + 8 * B_KVFULL, KV_SLOT);
      if (!MC0) {
#pragma unroll
        for (int i = 0; i < 2; i++) {
          tma3d(sb + i * KV_BOX, &P.tm_k, bar + 8 * B_KVFULL, 8 * (c & ~1), 16 * i - 1, 0);
          tma3d(sb + (2 + i) * KV_BOX, &P.tm_v, bar + 8 * B_KVFULL, 8 * (c & ~1), 16 * i - 1, 0);
        }
      }
    } else if (warp < 8) {
      const uint32_t na = (0x18211881u >> (4 * warp)) & 15;
#pragma unroll
      for (int i = 0; i < 8; i++) mbar_init(bar + 8 * (16 + 8 * warp + i), na);
    } else if (warp == 9) {
#pragma unroll
      for (int i = 1; i < 8; i++) { mbar_init(bar + 8 * (B_KVFULL + i), 1); mbar_expect_tx(bar + 8 * (B_KVFULL + i), KV_SLOT); }
    } else if (warp == 10) {
#pragma unroll
      for (int i = KFIRST; i < 8; i++) mbar_init(bar + 8 * (B_KFULL + i), 2);
    }
    asm volatile("fence.mbarrier_init.release.cluster;" ::: "memory");
  }
  if (warp == 11 && lane < 16) sts128(sb + off_T(lane >> 2) + (lane & 3) * UT_COPY, 0, 0, 0, 0);
  __syncthreads();
  asm volatile("barrier.cluster.arrive.relaxed.aligned;" ::: "memory");

  if (tid == 32) TS(46);
  if (warp < 8) {
    if (warp == 7 && lane < 8) {
      const uint4 v = __ldg((const uint4*)(P.ssm_k + (size_t)(8 * c + lane) * S));
      const float k0 = bflo(v.x) + __bfloat162float(P.ssm_D[8 * c + lane]);
      const uint32_t kt = sb + off_T(lane >> 1) + 2 * UT_SIZE + (lane & 1) * KT_SIZE;
      sts128(kt, 0, 0, 0, 0);
      sts128(kt + 16, (v.x & 0xffff0000u) | (packbf(k0, 0.f) & 0xffffu), v.y, v.z, v.w);
      fence_async_smem();
      mbar_arrive(bar + 8 * (B_KFULL + lane));
    }
    __syncwarp();
  }
  cluster_wait();
  uint32_t ep0 = 0;
  const uint32_t* const epp = cnt + C_ACT + 1 + (T_EP ? lane & blockIdx.y : 0);
  if (warp < 8) ep0 = ldg_relaxed(epp);
  if (warp < NU_MMA || warp > 8) {
      uint32_t W[4][4];
      const uint4* wp = (const uint4*)(P.shift_k + (size_t)32 * c);
#pragma unroll
      for (int p = 0; p < 4; p++) {
        const uint4 v = __ldg(wp + p);
        W[0][p] = __byte_perm(v.x, v.z, 0x5410); W[1][p] = __byte_perm(v.x, v.z, 0x7632);
        W[2][p] = __byte_perm(v.y, v.w, 0x5410); W[3][p] = __byte_perm(v.y, v.w, 0x7632);
      }
      uint32_t lo[8];
#pragma unroll
      for (int n = 0; n < 8; n++) {
        const uint32_t o = (lane >> 4) * KV_BOX + ((lane & 15) + n + 1) * 32 + rank * 16;
        lo[n] = o ^ ((o >> 3) & 16);
      }
#pragma unroll 1
      for (int st = warp - 9; st < 8; st += 3) {
        const uint32_t ka = sb + off_kv(st);
        mbar_wait(bar + 8 * (B_KVFULL + st), 0);
        if (lane == 0) TS(48 + st);
        uint32_t k[12][4], v[9][4];
#pragma unroll
        for (int i = 0; i < 12; i++) {
          const uint32_t la = ka + lo[i < 4 ? i + 3 : i - 4] + (i < 4 ? i + 4 : i - 4) * 512;
          const uint4 a = lds128(la);
          k[i][0] = a.x; k[i][1] = a.y; k[i][2] = a.z; k[i][3] = a.w;
          if (i >= 3) {
            const uint4 b = lds128(la + 2 * KV_BOX);
            v[i - 3][0] = b.x; v[i - 3][1] = b.y; v[i - 3][2] = b.z; v[i - 3][3] = b.w;
          }
        }
#pragma unroll
        for (int p = 0; p < 4; p++) {
          uint32_t u[9];
#pragma unroll
          for (int i = 0; i < 9; i++)
            u[i] = bmul2(bfma2(k[i + 3][p], W[0][p], bfma2(k[i + 2][p], W[1][p], bfma2(k[i + 1][p], W[2][p], bmul2(k[i][p], W[3][p])))), v[i][p]);
          const uint32_t ta = sb + off_T(p) + 16 + (32 * st + lane) * 16;
#pragma unroll
          for (int e = 0; e < 2; e++) {
            const uint32_t sel = e ? 0x7632 : 0x5410;
            sts128(ta + e * UT_SIZE, __byte_perm(u[2], u[1], sel), __byte_perm(u[4], u[3], sel), __byte_perm(u[6], u[5], sel), __byte_perm(u[8], u[7], sel));
            sts128(ta + e * UT_SIZE + UT_COPY, __byte_perm(u[1], u[0], sel), __byte_perm(u[3], u[2], sel), __byte_perm(u[5], u[4], sel), __byte_perm(u[7], u[6], sel));
          }
          if (p == 0) {
            __syncwarp();
            if (lane == 0) mbar_arrive(bar + 8 * (B_UFULL + st));
            if (st < 3 && lane < 2) mbar_arrive_c(mapa(bar + 8 * (B_KVFREE + st), lane), 1);
            mbar_wait(bar + 8 * (B_KVFULL + st), 0);
#pragma unroll
            for (int i = 0; i < 12; i++) asm volatile("" : "+r"(k[i][1]), "+r"(k[i][2]), "+r"(k[i][3]));
          }
        }
        if (st < 3) ep0 = ldg_relaxed(epp);
        __syncwarp();
        if (lane == 0) { mbar_arrive_c(bar + 8 * (B_UREST + (st >> 2)), 2); if (st >= 4) TS(56 + st); }
      }
  }

  if (warp < 8) {
    const int wg = warp >> 2, w = warp & 3, g = lane >> 2, t = lane & 3;
    const uint32_t uoff = wg * UT_SIZE + ((g & 1) ? 0 : UT_COPY) + ((g >> 1) + 8 * w + 8 - t) * 4;
    const bool par = (ep0 & 8) == 0;
    uint32_t a0[4];
    mbar_wait(bar + 8 * (B_KFULL + wg), 0);
    mbar_wait(bar + 8 * B_UFULL, 0);
    mbar_wait(bar + 8 * (B_UFULL + START_GATE), 0);
    lda(a0, sb + OFF_T0 + uoff);
    conv_round<0>(a0, sb, 0, warp, lane, uoff, par);
#pragma unroll 1
    for (int r = 1; r < 4; r++) {
      conv_round<1>(a0, sb, r, warp, lane, uoff, par);
      if (r != 1) continue;
      TSM(10);
      const uint32_t l = laneid(), xs = (l & 4) * 16;
      const uint32_t xa = sb + OFF_KVB + (warp & 1) * 16448 + (warp >> 1) * 512 + (l >> 2) * 2048 + (l >> 4) * 32 + (l & 3) * 16;
      float e[4][4] = {};
      uint4 v[8];
      mbar_wait(bar + 8 * B_XFULL, 0);
#pragma unroll
      for (int i = 0; i < 8; i++) v[i] = lds128(((i & 1) ? xa - xs : xa + xs) + i * 64);
#pragma unroll
      for (int i = 0; i < 8; i++) {
        asm volatile("mma.sync.aligned.m16n8k16.row.col.f32.bf16.bf16.f32 {%0,%1,%2,%3},{%4,%6,%5,%6},{%4,%5},{%0,%1,%2,%3};"
                     : "+f"(e[i & 1][0]), "+f"(e[i & 1][1]), "+f"(e[i & 1][2]), "+f"(e[i & 1][3]) : "r"(v[i].x), "r"(v[i].y), "r"(0x3f803f80u));
        asm volatile("mma.sync.aligned.m16n8k16.row.col.f32.bf16.bf16.f32 {%0,%1,%2,%3},{%4,%6,%5,%6},{%4,%5},{%0,%1,%2,%3};"
                     : "+f"(e[2 + (i & 1)][0]), "+f"(e[2 + (i & 1)][1]), "+f"(e[2 + (i & 1)][2]), "+f"(e[2 + (i & 1)][3]) : "r"(v[i].z), "r"(v[i].w), "r"(0x3f803f80u));
      }
#pragma unroll
      for (int i = 0; i < 4; i++) e[0][i] = (e[0][i] + e[1][i]) + (e[2][i] + e[3][i]);
      if ((l & 3) == (l >> 3))
        ((float2*)(smem + OFF_XS))[(8 * (warp & 1) + (l >> 2)) * 4 + (warp >> 1)] = (l & 4) ? make_float2(e[0][3], e[0][1]) : make_float2(e[0][2], e[0][0]);
      TSM(12);
      if (warp == 0) mbar_wait(bar + 8 * B_XREAD, 0);
      __syncwarp();
      if (lane == 0) mbar_arrive(bar + 8 * B_XDONE);
    }
    TSM(4);
    if (EXP & 2) { if (tid == 0) TSDUMP(); return; }
    const bool rel = lane == 0 && w == 0;
    const int id = lane >> 3, srow = 16 * w + (lane & 7) + 8 * (id & 1);
    const uint32_t soff = srow * 128, sx = ((id >> 1) ^ (srow & 7)) << 4;
    const uint32_t hs = sb + OFF_HS + (64 * wg + 16 * w + g) * 16;
    const Check ck{(uint32_t)(warp * 2048 + g * 128 + ((2 * t) ^ g) * 16), (par ? S : 0) + 128 * m};
    auto put_box = [&](const uint32_t* u, int tile, int b) {
      if (b > 0) mbar_wait(bar + 8 * (B_EMPTY + 3 - 2 * wg), 1);
      const uint32_t dst = sb + off_act(tile, wg, b) + soff;
#pragma unroll
      for (int p = 0; p < 4; p++) {
        const uint32_t* v = u + 16 * b + 4 * p;
        stsm4(dst + (sx ^ (p << 5)), bmul2v(v[0]), bmul2v(v[1]), bmul2v(v[2]), bmul2v(v[3]));
      }
      if (tile ? b > 0 : b == 3) {
        __syncwarp();
        if (lane == 0) mbar_arrive(bar + 8 * (b == 2 ? B_ASLOT : B_ADONE + tile));
      }
    };
    uint32_t u1[48];
    {
      uint32_t u0[64];
      {
        uint2 zp[8];
        const ZTask z = ztask(sb, 3, 1, warp, lane);
        gemm1_main<256>(u0, sb, wg, rel, hs + 4 * t, t == 3, ck, [&](int kk) {
          if (kk == 0) z.load(zp);
          if (kk == 1) z.store(zp, par, lane == 0);
        });
      }
      TSM(6);
      put_box(u0, 0, 0);
      if (DEFER0 < 3) put_box(u0, 0, 1);
      TSM(8);
      gemm1_main<192>(u1, sb, wg, rel, hs + 4 * t, t == 3, ck, [&](int kk) { if (kk < DEFER0) put_box(u0, 0, kk + 4 - DEFER0); });
    }
    TSM(7);
    put_box(u1, 1, 2);
    if (!DEFER1) { put_box(u1, 1, 0); put_box(u1, 1, 1); }
    TSM(9);
    {
      float acc[64], res[64];
      const uint64_t da0 = mkdesc(sb + wg * 8192, 16, 1024, 1), db0 = mkdesc(sb + 16384, 8192, 1024, 1);
      const bool rel2 = lane == 0 && w < 2;
      const uint32_t ebar = mapa(bar + 8 * B_EMPTY2, w & 1);
      int s = 0, ph = 1, prev = 0;
      auto step = [&](int kb) {
        mbar_wait(bar + 8 * (B_FULL2 + s), ph);
        const uint64_t da = da0 + s * 2048, db = db0 + s * 2048;
        wg_fence();
        wgmma_ss<128>(acc, da, db, kb != 0);
        wg_commit();
        wg_wait<1>();
        if (rel2 && kb > 0 && kb <= 50) mbar_arrive_c(ebar + 8 * prev, 2);
#pragma unroll
        for (int kk = 1; kk < 4; kk++) wgmma_ss<128>(acc, da + kk * 2, db + kk * 128, 1);
        wg_commit();
        prev = s;
        if (++s == 6) { s = 0; ph ^= 1; }
      };
#pragma unroll
      for (int kb = 0; kb < 2 * DEFER1; kb++) {
        step(kb);
        if (kb == 0) mbar_wait(bar + 8 * B_XFREE, 0);
        put_box(u1, 1, kb);
      }
#pragma unroll 1
      for (int kb = 2 * DEFER1; kb < 36; kb++) step(kb);
      s = 0; ph = 1; prev = 5;
      mbar_wait(bar + 8 * B_HRES, 0);
      const int row = 64 * wg + 16 * w + g;
      const uint32_t ha = sb + OFF_X + row * 256 + t * 64, hx = ((2 * row + (t >> 1)) & 3) << 4;
#pragma unroll
      for (int cc = 0; cc < 4; cc++) {
        const uint4 b = lds128(sb + OFF_RED + t * 64 + cc * 16), v0 = lds128(ha + ((cc << 4) ^ hx)), v1 = lds128(ha + 2048 + ((cc << 4) ^ hx));
        step(36 + cc);
        const uint32_t hb[8] = {badd2(v0.x, b.x), badd2(v1.x, b.x), badd2(v0.y, b.y), badd2(v1.y, b.y), badd2(v0.z, b.z), badd2(v1.z, b.z), badd2(v0.w, b.w), badd2(v1.w, b.w)};
#pragma unroll
        for (int q = 0; q < 8; q++) { res[16 * cc + 2 * q] = bflo(hb[q]); res[16 * cc + 2 * q + 1] = bfhi(hb[q]); }
      }
#pragma unroll 1
      for (int kb = T_P8 ? 44 : 40; kb < 56 - LAG; kb++) step(kb);
      if (wg == 0) bar_sync(9, 256);
#pragma unroll 1
      for (int kb = 56 - LAG; kb < 56; kb++) {
        mbar_wait(bar + 8 * (B_FULL2 + s), ph);
        if (EARLY_ARR && kb == 55 && wg == 1) asm volatile("bar.arrive 9, 256;" ::: "memory");
        wg_fence();
#pragma unroll
        for (int kk = 0; kk < 4; kk++) wgmma_ss<128>(acc, da0 + s * 2048 + kk * 2, db0 + s * 2048 + kk * 128, 1);
        wg_commit();
        if (++s == 6) { s = 0; ph ^= 1; }
      }
      if (!EARLY_ARR && wg == 1) asm volatile("bar.arrive 9, 256;" ::: "memory");
      const float sc0 = __uint_as_float(lds32(hs + 12)), sc1 = __uint_as_float(lds32(hs + 140));
      wg_wait<0>();
      rename<0, 64>(acc);
      TSM(11);
      TSMT(15, 128);
      const uint32_t ob = sb + OFF_X + warp * 4096;
      __syncwarp();
#pragma unroll
      for (int mu = 0; mu < 16; mu += 2) {
        const float* a = acc + 4 * mu;
        const float* q = res + 4 * mu;
        stsm4(ob + (mu >> 3) * 2048 + (soff & 2047) + (sx ^ ((mu & 6) << 4)),
              packbf(fmaf(a[0], sc0, q[0]), fmaf(a[1], sc0, q[1])), packbf(fmaf(a[2], sc1, q[2]), fmaf(a[3], sc1, q[3])),
              packbf(fmaf(a[4], sc0, q[4]), fmaf(a[5], sc0, q[5])), packbf(fmaf(a[6], sc1, q[6]), fmaf(a[7], sc1, q[7])));
        if ((mu & 7) == 6) {
          fence_async_smem();
          __syncwarp();
          if (elect()) tma_store(&P.tm_out, ob + (mu >> 3) * 2048, 128 * j + 64 * (mu >> 3), 128 * m + 16 * warp);
          if (mu == 6 && SPLIT) mbar_wait(bar + 8 * B_HRES, 0);
        }
      }
      if (elect()) {
        bulk_commit();
        bulk_wait_read();
        if (warp == 0) { TS0(9); TSDUMP(); }
      }
    }
  } else if (warp == 8) {
    if (elect()) {
#pragma unroll 1
      for (int i = MC0 ? 0 : 1; i < 8; i++) {
        if (i >= 5) mbar_wait(bar + 8 * (B_KVFREE + i - 5), 0);
        const uint32_t dst = sb + off_kv(i) + rank * KV_BOX;
        tma3d_mc(dst, &P.tm_k, bar + 8 * (B_KVFULL + i), 8 * (c & ~1), 32 * i + 16 * rank - 1, 0);
        tma3d_mc(dst + 2 * KV_BOX, &P.tm_v, bar + 8 * (B_KVFULL + i), 8 * (c & ~1), 32 * i + 16 * rank - 1, 0);
        if (XPF && i >= XPF0) prefetch_l2(P.x + (size_t)(128 * m + 16 * j) * D + (i - XPF0) * (XPF / 2), XPF);
      }
      const uint32_t epoch = (ldg_relaxed(cnt + C_ACT + 1) >> 3) + 1;
      mbar_wait(bar + 8 * (B_KVFULL + KV_GATE), 0);
#pragma unroll 1
      for (int ch = KFIRST; ch < 9; ch++) {
        if (ch == XPOS) {
          mbar_wait(bar + 8 * (B_KVFULL + X_GATE), 0);
          mbar_wait(bar + 8 * (B_UFULL + 3), 0);
          mbar_wait(bar + 8 * (B_UFULL + 4), 0);
          mbar_expect_tx(bar + 8 * B_XFULL, 32768);
#pragma unroll 1
          for (int i = 0; i < 4; i++) bulk_g2s(sb + OFF_KVB + i * 8224, P.x + (size_t)(128 * m + 16 * j + 4 * i) * D, 8192, bar + 8 * B_XFULL);
          prefetch_tmap(&P.tm_z); prefetch_tmap(&P.tm_hst); prefetch_tmap(&P.tm_h); prefetch_tmap(&P.tm_w1a); prefetch_tmap(&P.tm_w1b); prefetch_tmap(&P.tm_w1c);
          prefetch_tmap(&P.tm_w2); prefetch_tmap(&P.tm_actst); prefetch_tmap(&P.tm_hres); prefetch_tmap(&P.tm_out);
          mbar_wait(bar + 8 * B_ZDONE, 0);
        }
        if (ch == 8) break;
        mbar_expect_tx(bar + 8 * (B_KFULL + ch), 4080);
        bulk_g2s(sb + off_T(ch >> 1) + 2 * UT_SIZE + (ch & 1) * KT_SIZE + 32, P.ssm_k + (size_t)(8 * c + ch) * S + 8, 4080, bar + 8 * (B_KFULL + ch));
      }
      mbar_wait(bar + 8 * B_XFULL, 0);
      TS(31);
      if ((EXP & 2) && !(EXP & 32)) return;
      mbar_wait(bar + 8 * (B_KFULL + 7), 0);
      prefetch_l2(P.w1 + (size_t)c * 8 * F, 2 * F * 2);
#pragma unroll 1
      for (int i = 1; i <= PF_EARLY; i++) {
        mbar_wait(bar + 8 * (B_ZFULL + 4 - PF_EARLY + i), 0);
        prefetch_l2(P.w1 + (size_t)(c * 8 + 2 * i) * F, 2 * F * 2);
      }
      if (EXP & 2) return;
      uint32_t early = epoch * 16 - 1;
      mbar_wait(bar + 8 * (B_ZDONE + 1), 0);
      fence_async_smem();
#pragma unroll
      for (int s = 0; s < 2; s++) {
        mbar_expect_tx(bar + 8 * (B_FULL + s), 49152);
        tma4d(sb + s * 49152 + 16384, &P.tm_w1a, bar + 8 * (B_FULL + s), 0, 32 * s, 7 * j);
      }
      const int hrow = 128 * m + (epoch & 1) * S;
      mbar_wait(bar + 8 * B_KVFREE, 1);
#pragma unroll 1
      for (int q = 0; q < 8; q++) {
        const CUtensorMap* mw = q < 4 ? &P.tm_w1a : &P.tm_w1b;
        const int nb0 = 7 * j + (q & 4), k0 = 256 * (q & 3);
        const uint32_t bytes = q < 4 ? 49152 : 40960, ph = (q - 1) & 1;
#pragma unroll
        for (int s = 0; s < 4; s++) {
          const uint32_t sa = sb + s * 49152, fb = bar + 8 * (B_FULL + s);
          if (q > 0) {
            mbar_wait(bar + 8 * (B_EMPTY + s), ph);
          } else if (s >= 2) {
            mbar_wait(bar + 8 * (s == 2 ? B_ZDONE + 2 : B_YFULL + 7), 0);
            if (s == 3) { mbar_wait(bar + 8 * B_HOUT, 0); mbar_wait(bar + 8 * (B_HOUT + 1), 0); }
            fence_async_smem();
          }
          if (s >= 2 || q > 0) {
            mbar_expect_tx(fb, bytes);
            tma4d(sa + 16384, mw, fb, 2 * (q & 3), 32 * s, nb0);
          }
          if (s == 0 && q < 4) {
            if (!(EXP & 64) && (int)(early - epoch * 16) < 0) wait_count(cnt + C_H + q, epoch * 16);
            acquire_async();
            TS(11 + q);
          }
          tma2d(sa, &P.tm_h, fb, k0 + 64 * s, hrow);
          if (q >= 3 && q < 7) prefetch_l2(P.w2 + (size_t)(c * 28 + 7 * (q - 3)) * D + s * 1792, 3584);
        }
        early = ldg_relaxed(cnt + (q < 3 ? C_H + q + 1 : C_ACT));
      }
      mbar_wait(bar + 8 * B_XFREE, 0);
      int col = 0, left = 4;
#pragma unroll 1
      for (int q = 0; q < 10; q++) {
#pragma unroll
        for (int s = 0; s < 6; s++) {
          if (s == 2 && q == 9) break;
          const uint32_t sa = sb + s * 32768, fb = bar + 8 * (B_FULL2 + s);
          if (q == 0) {
            if (s == 5) mbar_wait(bar + 8 * B_SFREE, 0);
            else mbar_wait(bar + 8 * (B_EMPTY + (2 * s + 1) / 3), 1);
            mbar_arrive_c(mapa(bar + 8 * (B_EMPTY2 + s), 0), 4);
            mbar_arrive_c(mapa(bar + 8 * (B_EMPTY2 + s), 1), 4);
          }
          mbar_wait(bar + 8 * (B_EMPTY2 + s), (q + 1) & 1);
          mbar_expect_tx(fb, 32768);
          tma3d(sa + 16384, &P.tm_w2, fb, 0, col, 2 * j);
          if ((s == 0 && q == 0) || (s == 2 && q == 5)) {
            if ((int)(early - epoch * 8) < 0) wait_count(cnt + C_ACT + (s >> 1), epoch * 8);
            acquire_async();
            TS(15 + (s >> 1));
          }
          tma2d_mc(sa + rank * 8192, &P.tm_actst, fb, col, 128 * m + 64 * rank);
          col += 64;
          if (--left == 0) {
            const bool first = 6 * q + s < 31;
            col = 6 * q + s == 31 ? 256 : col + (first ? 192 : 256);
            left = first ? 4 : 3;
          }
          if (s == 0 && q == 5) early = ldg_relaxed(cnt + C_ACT + 1);
        }
      }
    }
  } else {
    const int zw = warp - 9;
    const uint32_t epoch = __shfl_sync(0xffffffffu, (ep0 >> 3) + 1, 0);
    if (zw == 0) {
#pragma unroll 1
      for (int e = 0; e < 8; e++) {
        if (e == 3) {
          mbar_wait(bar + 8 * B_XDONE, 0);
          const float4 r0 = ((const float4*)(smem + OFF_XS))[2 * (lane & 15)], r1 = ((const float4*)(smem + OFF_XS))[2 * (lane & 15) + 1];
          const float mu = ((r0.x + r0.z) + (r1.x + r1.z)) * (1.f / D);
          const uint32_t rs = packbf(rsqrtf(fmaxf(fmaf(-mu, mu, ((r0.y + r0.w) + (r1.y + r1.w)) * (1.f / D)), 0.f) + 1e-5f), mu);
          ((uint2*)(smem + OFF_XS - 128))[lane & 15] = make_uint2(rs, packbf(-mu * bflo(rs), -mu * bflo(rs)));
          __syncwarp();
          if (lane == 0) mbar_arrive(bar + 8 * B_XSTAT);
        }
        mbar_wait(bar + 8 * (B_ZFULL + e), 0);
        if (elect()) {
          if (!ZFENCE) fence_async_smem();
#pragma unroll
          for (int p = 0; p < 2; p++)
            asm volatile("cp.async.bulk.global.shared::cta.bulk_group [%0], [%1], 2048;"
                         ::"l"(g_z + (size_t)((e >> 1) * NCTA + c) * S + (e & 1) * 1024 + p * 512), "r"(sb + off_Y(e >> 1) + ((e & 1) ? YH1 + p * YW1 : p * YW0)) : "memory");
          bulk_commit();
          bulk_wait();
          if ((e & 1) || e == 6) mbar_arrive(bar + 8 * (e == 6 ? B_XLOW : B_ZDONE + (e >> 1)));
        }
        __syncwarp();
        if (ZHINT_DELAY) __nanosleep(ZHINT_DELAY);
        if (lane < 8) asm volatile("red.relaxed.gpu.global.add.u32 [%0], 1;" ::"l"(g_cnt + 32 * (8 * (e & 1) + lane) + C_Z + (e >> 1)) : "memory");
        if (lane == 0 && (e & 1)) TS(17 + (e >> 1));
      }
      if (EXP & 2) { if (lane == 0) signal(cnt + C_ACT + 1); return; }
      const int nbox = m < 12 ? 8 : 4, cn = 448 * j + 64 * (m >> 2), ck = 256 * (m & 3);
      const uint32_t wb = sb + OFF_X + 16384;
      if (elect()) {
        fence_async_smem();
#pragma unroll
        for (int b = 0; b < 2; b++) {
          mbar_expect_tx(bar + 8 * (B_WFULL + b), 8192);
          tma2d(wb + b * 8192, &P.tm_w1c, bar + 8 * (B_WFULL + b), cn, ck + 64 * b);
        }
      }
#pragma unroll 1
      for (int tile = 0; tile < nbox / 4; tile++) {
        float cs[8];
#pragma unroll
        for (int i = 0; i < 8; i++) cs[i] = 0.f;
#pragma unroll 1
        for (int box = 4 * tile; box < 4 * tile + 4; box++) {
          const int sl = box & 1;
          mbar_wait(bar + 8 * (B_WFULL + sl), (box >> 1) & 1);
          uint32_t v[16][4];
#pragma unroll
          for (int i = 0; i < 16; i++) {
            const uint4 u = lds128(wb + sl * 8192 + i * 512 + lane * 16);
            v[i][0] = u.x; v[i][1] = u.y; v[i][2] = u.z; v[i][3] = u.w;
          }
#pragma unroll
          for (int e = 0; e < 4; e++) {
#pragma unroll
            for (int st = 1; st < 16; st <<= 1)
#pragma unroll
              for (int i = 0; i < 16; i += 2 * st) v[i][e] = badd2(v[i][e], v[i + st][e]);
            cs[2 * e] += bflo(v[0][e]); cs[2 * e + 1] += bfhi(v[0][e]);
            if (e == 0 && box + 2 < nbox) {
              __syncwarp();
              if (elect()) {
                mbar_expect_tx(bar + 8 * (B_WFULL + sl), 8192);
                tma2d(wb + sl * 8192, &P.tm_w1c, bar + 8 * (B_WFULL + sl), cn + 256 * ((box + 2) >> 2), ck + 64 * ((box + 2) & 3));
              }
            }
          }
        }
#pragma unroll
        for (int o = 8; o < 32; o <<= 1) {
#pragma unroll
          for (int i = 0; i < 8; i++) cs[i] += __shfl_xor_sync(0xffffffffu, cs[i], o);
        }
        const int p = lane >> 3;
        const float c0 = p == 0 ? cs[0] : p == 1 ? cs[2] : p == 2 ? cs[4] : cs[6], c1 = p == 0 ? cs[1] : p == 1 ? cs[3] : p == 2 ? cs[5] : cs[7];
        stg_b128(g_cs + (m & 3) * (F / 2) + (cn + 256 * tile) / 2 + 4 * (lane & 7) + p, __float_as_uint(c0), __float_as_uint(c1), 0, epoch);
        if (lane == 0) TS(38 + tile);
      }
#pragma unroll 1
      for (int tile = 0; tile < 2; tile++) {
        const int n0 = (448 * j + 256 * tile) / 2;
        float2 cv[4];
        uint32_t bv[4];
#pragma unroll
        for (int i = 0; i < 4; i++) bv[i] = __ldg((const uint32_t*)P.b1 + n0 + min(lane + 32 * i, tile ? 95 : 127));
        int it = 0;
        while (true) {
          bool ok = true;
          uint4 v[4][4];
#pragma unroll
          for (int i = 0; i < 4; i++)
#pragma unroll
            for (int k = 0; k < 4; k++) v[i][k] = ldg_b128(g_cs + k * (F / 2) + n0 + min(lane + 32 * i, tile ? 95 : 127));
#pragma unroll
          for (int i = 0; i < 4; i++) {
            ok = ok && v[i][0].w == epoch && v[i][1].w == epoch && v[i][2].w == epoch && v[i][3].w == epoch;
            cv[i].x = (__uint_as_float(v[i][0].x) + __uint_as_float(v[i][1].x)) + (__uint_as_float(v[i][2].x) + __uint_as_float(v[i][3].x));
            cv[i].y = (__uint_as_float(v[i][0].y) + __uint_as_float(v[i][1].y)) + (__uint_as_float(v[i][2].y) + __uint_as_float(v[i][3].y));
          }
          if (__all_sync(0xffffffffu, ok)) break;
          __nanosleep(200);
          if (++it > (1 << 20)) __trap();
        }
        mbar_wait(bar + 8 * (tile ? B_XFREE : B_HOUT + 2), 0);
#pragma unroll
        for (int i = 0; i < 4; i++) {
          const uint32_t hi = packbf(cv[i].x, cv[i].y), lo = packbf(cv[i].x - bflo(hi), cv[i].y - bfhi(hi));
#pragma unroll
          for (int cp = 0; cp < 2; cp++) {
            const uint32_t da = sb + OFF_X + cp * 16384 + (lane + 32 * i) * 32;
            sts128(da, __byte_perm(hi, lo, 0x5410), __byte_perm(hi, bv[i], 0x5410), bv[i] & 0xffffu, 0);
            sts128(da + 16, __byte_perm(hi, lo, 0x7632), __byte_perm(hi, bv[i], 0x7632), bv[i] >> 16, 0);
          }
        }
        if (tile == 1) {
          const uint32_t* b2p = (const uint32_t*)(P.b2 + 128 * j);
          ((uint32_t*)(smem + OFF_RED))[(lane & 3) * 16 + (lane >> 2)] = __ldg(b2p + lane);
          ((uint32_t*)(smem + OFF_RED))[(lane & 3) * 16 + 8 + (lane >> 2)] = __ldg(b2p + 32 + lane);
        }
        fence_async_smem();
        __syncwarp();
        if (lane == 0) { mbar_arrive(bar + 8 * B_CSFULL); TS(21 + 19 * tile); }
      }
    } else {
      if ((EXP & 2) && !(EXP & 4)) { if (lane == 0) mbar_arrive(bar + 8 * B_XREAD); return; }
      const int hw = zw - 1, rowb = 128 * m + 16 * j;
      const int q = lane & 3, sl = ((lane >> 2) & 3) + 16 * (lane >> 4);
      float2* red = (float2*)(smem + OFF_RED);
      uint32_t xr[4][8][4];
      uint32_t pv[4];
      const uint32_t xa = sb + OFF_KVB + q * 8224 + (64 * hw + sl) * 16;
      mbar_wait(bar + 8 * B_XFULL, 0);
#pragma unroll
      for (int a = 0; a < 4; a++) {
#pragma unroll
        for (int i = 0; i < 8; i++) {
          const uint4 v = lds128(xa + a * 2048 + (4 * (i & 3) + 32 * (i >> 2)) * 16);
          xr[a][i][0] = v.x; xr[a][i][1] = v.y; xr[a][i][2] = v.z; xr[a][i][3] = v.w;
        }
      }
      __syncwarp();
      if (lane == 0) mbar_arrive(bar + 8 * B_XREAD);
      auto fetch_z = [&](int r) {
        if (elect()) {
          acquire_async();
          mbar_expect_tx(bar + 8 * (B_ZIN + hw), 4096);
          tma2d(sb + off_hb(r) + hw * HB_WARP, &P.tm_z, bar + 8 * (B_ZIN + hw),
                2 * ((rowb & 1024) + ((rowb >> 6) & 1) * 512 + (m & 7) * 64 + (rowb & 63)), r * NCTA + 64 * hw);
        }
        __syncwarp();
      };
      if ((EXP & 2) && !(EXP & 8)) return;
      uint32_t zph = 0;
      const uint32_t tag = (lane & 12) == 0;
      if (!(EXP & 64)) wait_count_warp(cnt + C_Z, epoch * NCTA);
      fetch_z(0);
      {
        uint32_t rs2[4], nm2[4];
#pragma unroll
        for (int r = 0; r < 4; r++) {
          const uint32_t hb = sb + off_hb(r) + hw * HB_WARP;
          uint32_t zc = 0;
          bool got = r == 3;
          if (r < 3) zc = ldg_relaxed(cnt + C_Z + r + 1 + (T_ZC ? lane & blockIdx.y : 0));
          for (int it = 0;; it++) {
            mbar_wait(bar + 8 * (B_ZIN + hw), zph);
            zph ^= 1;
            uint32_t sum = 0;
#pragma unroll
            for (int i = 0; i < 4; i++) sum += lds32(hb + lane * 32 + (lane & 4) * 4 + i * 1024) & 1;
            if (__all_sync(0xffffffffu, sum == (epoch & 1) * 4)) break;
            if (it > (1 << 16)) __trap();
            if (lane == 0) CNT(16 + r);
            fetch_z(r);
          }
          if (tid == 320) TS(27 + r);
          if (r == 0) {
            mbar_wait(bar + 8 * B_XSTAT, 0);
            const uint4 v0 = lds128(sb + OFF_XS - 128 + q * 32), v1 = lds128(sb + OFF_XS - 112 + q * 32);
            rs2[0] = __byte_perm(v0.x, 0, 0x1010); rs2[1] = __byte_perm(v0.z, 0, 0x1010); rs2[2] = __byte_perm(v1.x, 0, 0x1010); rs2[3] = __byte_perm(v1.z, 0, 0x1010);
            nm2[0] = v0.y; nm2[1] = v0.w; nm2[2] = v1.y; nm2[3] = v1.w;
            if (tid == 320) TS(37);
          }
          if (r < 3 && __all_sync(0xffffffffu, (int)(zc - epoch * NCTA) >= 0 && (r != 1 || mbar_test(bar + 8 * B_XLOW, 0)))) { fetch_z(r + 1); got = true; }
          uint32_t za = hb + sl * 64 + q * 16;
#pragma unroll 1
          for (int once = blockIdx.y; once < 1; once++)
#pragma unroll
          for (int i = 0; i < 8; i += 2) {
            const uint4 z0 = lds128(za + (4 * (i & 3) + 32 * (i >> 2)) * 64), z1 = lds128(za + (4 * (i & 3) + 4 + 32 * (i >> 2)) * 64);
            const uint32_t zz[2][4] = {{z0.x & ~1u, z0.y, z0.z, z0.w}, {z1.x & ~1u, z1.y, z1.z, z1.w}};
#pragma unroll
            for (int e = 0; e < 2; e++)
#pragma unroll
              for (int a = 0; a < 4; a++)
              {
                asm volatile("{.reg .b32 t; fma.rn.bf16x2 t, %0, %1, %2; fma.rn.bf16x2 %0, t, %3, %0;}" : "+r"(xr[a][i + e][r]) : "r"(rs2[a]), "r"(nm2[a]), "r"(zz[e][a]));
                if (e == 0) xr[a][i][r] |= tag;
              }
            if (i == 2) za += xr[3][1][r] & blockIdx.y;
          }
          __syncwarp();
          const uint32_t ha = hb + q * 128 + (((lane >> 4) * 4 + q) << 4) + (lane & 12);
#pragma unroll
          for (int i = 0; i < 4; i++)
#pragma unroll
            for (int a = 0; a < 2; a++) {
              const uint32_t p = ha ^ ((i << 4) | (a * 576));
              asm volatile("st.shared.b32 [%0], %1; st.shared.b32 [%0+1024], %2; st.shared.b32 [%0+2048], %3; st.shared.b32 [%0+3072], %4;"
                           ::"r"(p), "r"(xr[a][i][r]), "r"(xr[a + 2][i][r]), "r"(xr[a][i + 4][r]), "r"(xr[a + 2][i + 4][r]) : "memory");
            }
          fence_async_smem();
          __syncwarp();
          if (tid == 320) TS(23 + r);
          if (r < 3) zc = ldg_relaxed(cnt + C_Z + r + 1 + (T_ZC ? lane & blockIdx.y : 0));
          if (elect()) {
#pragma unroll
            for (int b = 0; b < 2; b++)
              asm volatile("cp.async.bulk.tensor.3d.global.shared::cta.bulk_group [%0, {%2,%3,%4}], [%1];"
                           ::"l"(&P.tm_hst), "r"(hb + b * 2048), "r"(256 * r + 128 * hw + 64 * b), "r"((rowb + (epoch & 1) * S) >> 2), "r"(0) : "memory");
            bulk_commit();
            bulk_wait();
            if (HINT_DELAY) __nanosleep(HINT_DELAY);
            asm volatile("red.relaxed.gpu.global.add.u32 [%0], 1;" ::"l"(cnt + C_H + r) : "memory");
            if (r & 1) mbar_arrive(bar + 8 * (B_HOUT + 2 * (r >> 1) + hw));
            if (r == 0) mbar_arrive(bar + 8 * B_KVFREE);
            if (hw == 0) TS(32 + r);
          }
          __syncwarp();
          if (!got) {
            if (!__all_sync(0xffffffffu, (int)(zc - epoch * NCTA) >= 0)) wait_count_warp(cnt + C_Z + r + 1, epoch * NCTA);
            if (r == 1) mbar_wait(bar + 8 * B_XLOW, 0);
            fetch_z(r + 1);
          }
        }
#pragma unroll
        for (int a = 0; a < 4; a++)
          pv[a] = __byte_perm(((const uint2*)(smem + OFF_XS - 128))[4 * q + a].x, 0, 0x3232);
        float t1[4], t2[4];
#pragma unroll
        for (int a = 0; a < 4; a++) {
          t1[a] = 0.f; t2[a] = 0.f;
          uint32_t p1, p2;
#pragma unroll
          for (int ch = 0; ch < 4; ch++) {
            uint32_t c1 = 0, c2 = 0;
#pragma unroll
            for (int i = 0; i < 8; i++) {
              const uint32_t dd = bsub2(xr[a][2 * ch + (i >> 2)][i & 3], pv[a]);
              c1 = i ? badd2(c1, dd) : dd;
              c2 = i ? bfma2(dd, dd, c2) : bmul2(dd, dd);
            }
            if (ch & 1) {
              p1 = badd2(p1, c1); p2 = badd2(p2, c2);
              t1[a] += bflo(p1) + bfhi(p1);
              t2[a] += bflo(p2) + bfhi(p2);
            } else {
              p1 = c1; p2 = c2;
            }
          }
          const float pf = bflo(pv[a]);
          t2[a] = fmaf(pf, fmaf(pf, 64.f, 2.f * t1[a]), t2[a]);
          t1[a] = fmaf(pf, 64.f, t1[a]);
        }
#pragma unroll
        for (int o = 4; o < 32; o <<= 1) {
#pragma unroll
          for (int a = 0; a < 4; a++) { t1[a] += __shfl_xor_sync(0xffffffffu, t1[a], o); t2[a] += __shfl_xor_sync(0xffffffffu, t2[a], o); }
        }
        if (lane < 4) {
          ((float4*)red)[hw * 8 + 2 * q] = make_float4(t1[0], t2[0], t1[1], t2[1]);
          ((float4*)red)[hw * 8 + 2 * q + 1] = make_float4(t1[2], t2[2], t1[3], t2[3]);
        }
        bar_sync(1, 64);
      }
      if (EXP & 2) return;
      if (hw == 0 && lane < 16) {
        const float2 r0 = red[lane], r1 = red[16 + lane];
        const float mu = (r0.x + r1.x) * (1.f / D);
        const float var = fmaxf(fmaf(-mu, mu, (r0.y + r1.y) * (1.f / D)), 0.f) + 1e-5f;
        const float rs = rsqrtf(var), sd = var * rs;
        const uint32_t hi = packbf(-mu, sd), lo = packbf(-mu - bflo(hi), sd - bfhi(hi));
        stg_b128(g_hstat + rowb + lane, __byte_perm(hi, 0, 0x1010), __byte_perm(lo, hi, 0x7610), __byte_perm(lo, epoch, 0x5432), __float_as_uint(rs * rs));
        if (lane == 0) TS(43);
      }
      __syncwarp();
      if (hw == 0) {
        uint4 hv[4];
        for (int it = 0;; it++) {
          bool ok = true;
#pragma unroll
          for (int i = 0; i < 4; i++) hv[i] = ldg_b128(g_hstat + 128 * m + lane + 32 * i);
#pragma unroll
          for (int i = 0; i < 4; i++) ok = ok && (hv[i].z >> 16) == (epoch & 0xffffu);
          if (__all_sync(0xffffffffu, ok)) break;
          __nanosleep(100);
          if (it > (1 << 20)) __trap();
        }
#pragma unroll
        for (int i = 0; i < 4; i++) sts128(sb + OFF_HS + (lane + 32 * i) * 16, hv[i].x, hv[i].y, hv[i].z & 0xffffu, hv[i].w);
        __syncwarp();
        if (lane == 0) { mbar_arrive(bar + 8 * B_HSFULL); TS(36); }
      }
      if (hw == 0 && elect()) {
#pragma unroll 1
        for (int tile = 0; tile < 2; tile++) {
          const int nb = tile ? 6 : 8;
#pragma unroll 1
          for (int i = nb - 1; i >= 0; i--) {
            if (i == nb - 1 || i == 3) { mbar_wait(bar + 8 * (i == 5 ? B_ASLOT : B_ADONE + tile), 0); fence_async_smem(); }
            if (!(EXP & 1) || tile == 0) tma_store(&P.tm_actst, sb + off_act(tile, i & 1, i >> 1), 448 * j + 256 * tile + 64 * (i >> 1), 128 * m + 64 * (i & 1));
            bulk_commit();
            bulk_wait_read();
            if (tile == 1 && i == 4) mbar_arrive(bar + 8 * B_SFREE);
            if (tile == 0 || i <= 4) __nanosleep(ST_SLEEP);
          }
          if (tile == 0) mbar_arrive(bar + 8 * B_XFREE);
          bulk_wait();
          fence_async_global();
          signal(cnt + C_ACT + tile);
          TS(41 + tile);
          if (tile == 1) {
            mbar_expect_tx(bar + 8 * B_HRES, 32768);
#pragma unroll 1
            for (int i = 0; i < 8; i++) {
              tma3d(sb + OFF_X + i * 4096, &P.tm_hres, bar + 8 * B_HRES, 32 * j, 0, 128 * m + (epoch & 1) * S + 16 * i);
              __nanosleep(HR_SLEEP);
            }
          }
        }
      }
      if (hw == 1 && !(EXP & 256)) {
        if (CLR_LATE) mbar_wait(bar + 8 * B_HRES, 0);
        uint4* p = (uint4*)(g_h + (size_t)((~epoch & 1) * S + rowb) * D) + lane;
#pragma unroll 1
        for (int i = 0; i < 64; i++) {
          p[32 * i] = make_uint4(0, 0, 0, 0);
          __nanosleep(CLR_LATE ? 100 : 32);
        }
      }
    }
  }
}

typedef CUresult (*PFN_encode)(CUtensorMap*, CUtensorMapDataType, cuuint32_t, void*, const cuuint64_t*, const cuuint64_t*, const cuuint32_t*,
                               const cuuint32_t*, CUtensorMapInterleave, CUtensorMapSwizzle, CUtensorMapL2promotion, CUtensorMapFloatOOBfill);

void encode(PFN_encode enc, CUtensorMap* m, const void* ptr, int rank, const cuuint64_t* dims, const cuuint64_t* strides, const cuuint32_t* box,
            CUtensorMapSwizzle swz) {
  const cuuint32_t es[5] = {1, 1, 1, 1, 1};
  enc(m, CU_TENSOR_MAP_DATA_TYPE_BFLOAT16, rank, (void*)ptr, dims, strides, box, es, CU_TENSOR_MAP_INTERLEAVE_NONE, swz,
      CU_TENSOR_MAP_L2_PROMOTION_L2_128B, CU_TENSOR_MAP_FLOAT_OOB_FILL_NONE);
}

}

extern "C" void kernel_launch(void* const* d_in, const int* in_sizes, int n_in, void* d_out, int out_size) {
  static PFN_encode enc = nullptr;
  static void *p_h = nullptr, *p_act = nullptr, *p_z = nullptr;
  if (!enc) {
    cudaDriverEntryPointQueryResult qr;
    cudaGetDriverEntryPoint("cuTensorMapEncodeTiled", (void**)&enc, cudaEnableDefault, &qr);
    cudaGetSymbolAddress(&p_h, g_h);
    cudaGetSymbolAddress(&p_act, g_act);
    cudaGetSymbolAddress(&p_z, g_z);
    cudaFuncSetAttribute(fused_kernel, cudaFuncAttributeMaxDynamicSharedMemorySize, SMEM_BYTES);
  }
  Params P;
  P.x = (const __nv_bfloat16*)d_in[0];
  P.shift_k = (const __nv_bfloat16*)d_in[3];
  P.ssm_k = (const __nv_bfloat16*)d_in[4];
  P.ssm_D = (const __nv_bfloat16*)d_in[5];
  P.w1 = (const __nv_bfloat16*)d_in[7];
  P.b1 = (const __nv_bfloat16*)d_in[8];
  P.w2 = (const __nv_bfloat16*)d_in[9];
  P.b2 = (const __nv_bfloat16*)d_in[10];
  {
    const cuuint64_t dims[3] = {D, S / 8, 8}, str[2] = {8 * D * 2, D * 2};
    const cuuint32_t box[3] = {16, 17, 8};
    encode(enc, &P.tm_k, d_in[1], 3, dims, str, box, CU_TENSOR_MAP_SWIZZLE_32B);
    encode(enc, &P.tm_v, d_in[2], 3, dims, str, box, CU_TENSOR_MAP_SWIZZLE_32B);
  }
  {
    const cuuint64_t dims[2] = {D, S}, dimh[2] = {D, 2 * S}, str[1] = {D * 2};
    const cuuint32_t box[2] = {64, 128}, boxo[2] = {64, 16};
    encode(enc, &P.tm_h, p_h, 2, dimh, str, box, CU_TENSOR_MAP_SWIZZLE_128B);
    encode(enc, &P.tm_out, d_out, 2, dims, str, boxo, CU_TENSOR_MAP_SWIZZLE_128B);
  }
  {
    const cuuint64_t dims[4] = {64, 8, D / 8, F / 64}, str[3] = {F * 2, 8 * F * 2, 128};
    const cuuint32_t boxa[4] = {64, 2, 32, 4}, boxb[4] = {64, 2, 32, 3};
    encode(enc, &P.tm_w1a, P.w1, 4, dims, str, boxa, CU_TENSOR_MAP_SWIZZLE_128B);
    encode(enc, &P.tm_w1b, P.w1, 4, dims, str, boxb, CU_TENSOR_MAP_SWIZZLE_128B);
  }
  {
    const cuuint64_t dims[2] = {2 * S, 4 * NCTA}, str[1] = {S * 4};
    const cuuint32_t box[2] = {32, 64};
    encode(enc, &P.tm_z, p_z, 2, dims, str, box, CU_TENSOR_MAP_SWIZZLE_NONE);
  }
  {
    const cuuint64_t dims[3] = {D, S / 2, 4}, str[2] = {4 * D * 2, D * 2};
    const cuuint32_t box[3] = {64, 4, 4};
    encode(enc, &P.tm_hst, p_h, 3, dims, str, box, CU_TENSOR_MAP_SWIZZLE_128B);
  }
  {
    const cuuint64_t dims[2] = {F, D}, str[1] = {F * 2};
    const cuuint32_t box[2] = {64, 64};
    encode(enc, &P.tm_w1c, P.w1, 2, dims, str, box, CU_TENSOR_MAP_SWIZZLE_NONE);
  }
  {
    const cuuint64_t dims[2] = {F, S}, str[1] = {F * 2};
    const cuuint32_t boxs[2] = {64, 64};
    encode(enc, &P.tm_actst, p_act, 2, dims, str, boxs, CU_TENSOR_MAP_SWIZZLE_128B);
  }
  {
    const cuuint64_t dims[3] = {64, F, D / 64}, str[2] = {D * 2, 128};
    const cuuint32_t box[3] = {64, 64, 2};
    encode(enc, &P.tm_w2, P.w2, 3, dims, str, box, CU_TENSOR_MAP_SWIZZLE_128B);
  }
  {
    const cuuint64_t dims[3] = {256, 4, 2 * S}, str[2] = {512, D * 2};
    const cuuint32_t box[3] = {32, 4, 16};
    encode(enc, &P.tm_hres, p_h, 3, dims, str, box, CU_TENSOR_MAP_SWIZZLE_64B);
  }
  fused_kernel<<<NCTA, NTHREADS, SMEM_BYTES>>>(P);
}
```
